```python
import torch

def _softmax(x, axis=-1):
    return torch.softmax(x, dim=axis)
def _gelu(x):
    return torch.nn.functional.gelu(x, approximate="tanh")
def _silu(x):
    return torch.nn.functional.silu(x)
def _sigmoid(x):
    return torch.sigmoid(x)
def _layernorm(x, axis=-1, eps=1e-5):
    m = x.mean(dim=axis, keepdim=True)
    v = x.var(dim=axis, keepdim=True, unbiased=False)
    return (x - m) / torch.sqrt(v + eps)
def _scatter_add(tgt, idx, src, axis=0):
    return tgt.clone().index_add_(axis, idx, src)
def _segment_sum(src, seg, n):
    out = torch.zeros((n,) + src.shape[1:], dtype=src.dtype)
    return out.index_add_(0, seg, src)
def _pad(x, pw):
    flat = tuple(v for pair in reversed(pw) for v in pair)
    return torch.nn.functional.pad(x, flat)

kernel_name = 'recurrent_scan__mha_block_cached__dense_activation_silu__prompt'

def setup_inputs():

    _w = (lambda a: (lambda t: t.to(torch.bfloat16) if t.is_floating_point() else t)(torch.as_tensor(a)))
    def _A_setup():
        B, Sq, D = 1, 2048, 512
        H, Sk, Dh = 32, 2048, 128
        return {
            "x": _w((lambda *s: torch.randn(*s, dtype=torch.bfloat16) * 0.05)(B, Sq, D)),
            "k_cache": _w((lambda *s: torch.randn(*s, dtype=torch.bfloat16) * 3.2)(B, H, Sk, Dh)),
            "v_cache": _w((lambda *s: torch.randn(*s, dtype=torch.bfloat16) * 3.2)(B, H, Sk, Dh)),
            "wq": _w((lambda *s: torch.randn(*s, dtype=torch.bfloat16) * 3.2)(D, H * Dh) * (D ** -0.5)),
            "wo": _w((lambda *s: torch.randn(*s, dtype=torch.bfloat16) * 3.2)(H * Dh, D) * ((H * Dh) ** -0.5)),
        }
    _A_in = _A_setup()

    def _B_setup():
        B, S, D, F = 1, 2048, 512, 1792
        return {
            "x": _w((lambda *s: torch.randn(*s, dtype=torch.bfloat16) * 0.05)(B, S, D)),
            "w1": _w((lambda *s: torch.randn(*s, dtype=torch.bfloat16) * 3.2)(D, F) * (D ** -0.5)),
            "w2": _w((lambda *s: torch.randn(*s, dtype=torch.bfloat16) * 0.4)(F, D) * (F ** -0.5)),
        }
    _B_in = _B_setup()

    return {
        "A_x": _A_in["x"],
        "A_k_cache": _A_in["k_cache"],
        "A_v_cache": _A_in["v_cache"],
        "A_wq": _A_in["wq"],
        "A_wo": _A_in["wo"],
        "B_x": _B_in["x"],
        "B_w1": _B_in["w1"],
        "B_w2": _B_in["w2"],
    }

def reference(A_x, A_k_cache, A_v_cache, A_wq, A_wo, B_x, B_w1, B_w2):
    def _A_ref(x, k_cache, v_cache, wq, wo):
        B, Sq, D = x.shape
        H, Dh = 32, 128
        q = (lambda x, *d: x.permute(*d))((x @ wq).reshape(B, Sq, H, Dh), 0, 2, 1, 3)
        scores = torch.einsum("bhqd,bhkd->bhqk", q, k_cache) * (Dh ** -0.5)
        p = _softmax(scores, axis=-1)
        o = torch.einsum("bhqk,bhkd->bhqd", p, v_cache)
        return (lambda x, *d: x.permute(*d))(o, 0, 2, 1, 3).reshape(B, Sq, H * Dh) @ wo

    def _B_ref(x, w1, w2):
        h = torch.einsum("bsd,df->bsf", x, w1)
        h = _silu(h)
        out = torch.einsum("bsf,fd->bsd", h, w2)
        return out

    x = A_x
    xn = _layernorm(x, axis=-1)
    s = _A_ref(xn, A_k_cache, A_v_cache, A_wq, A_wo)
    g = _silu(_B_ref(xn, B_w1, B_w2))
    return x + s * g
```

```cpp
#include <cuda_runtime.h>
#include <cuda_bf16.h>
#include <cuda.h>
#include <stdint.h>

typedef __nv_bfloat16 bf16;

constexpr int SEQ = 2048, DM = 512, NH = 32, DH = 128, FF = 1792;

__device__ __align__(1024) bf16 g_xn[SEQ * DM];
__device__ __align__(1024) bf16 g_h[SEQ * FF];
__device__ __align__(1024) bf16 g_o[SEQ * NH * DH];

__device__ __forceinline__ uint32_t smem_u32(const void* p) { return (uint32_t)__cvta_generic_to_shared(p); }

__device__ __forceinline__ void mbar_init(uint32_t bar, uint32_t count) {
    asm volatile("mbarrier.init.shared::cta.b64 [%0], %1;" ::"r"(bar), "r"(count) : "memory");
}
__device__ __forceinline__ void mbar_expect_tx(uint32_t bar, uint32_t bytes) {
    asm volatile("mbarrier.arrive.expect_tx.shared::cta.b64 _, [%0], %1;" ::"r"(bar), "r"(bytes) : "memory");
}
__device__ __forceinline__ void mbar_arrive(uint32_t bar) {
    asm volatile("mbarrier.arrive.shared::cta.b64 _, [%0];" ::"r"(bar) : "memory");
}
__device__ __forceinline__ bool mbar_try_wait(uint32_t bar, uint32_t parity) {
    uint32_t ok;
    asm volatile(
        "{\n.reg .pred p;\n"
        "mbarrier.try_wait.parity.shared::cta.b64 p, [%1], %2;\n"
        "selp.u32 %0, 1, 0, p;\n}\n"
        : "=r"(ok)
        : "r"(bar), "r"(parity)
        : "memory");
    return ok != 0;
}
__device__ __forceinline__ void mbar_wait(uint32_t bar, uint32_t parity) {
    asm volatile(
        "{\n.reg .pred P1;\n.reg .u32 n;\nmov.u32 n, 0;\n"
        "LAB_WAIT:\n"
        "mbarrier.try_wait.parity.shared::cta.b64 P1, [%0], %1;\n"
        "@P1 bra DONE;\n"
        "add.u32 n, n, 1;\n"
        "setp.lt.u32 P1, n, 4194304;\n"
        "@P1 bra LAB_WAIT;\n"
        "trap;\n"
        "DONE:\n}\n" ::"r"(bar), "r"(parity)
        : "memory");
}
__device__ __forceinline__ void tma_load_3d(uint32_t dst, const CUtensorMap* map, uint32_t bar, int c0, int c1, int c2) {
    asm volatile(
        "cp.async.bulk.tensor.3d.shared::cluster.global.mbarrier::complete_tx::bytes [%0], [%1, {%3, %4, %5}], [%2];"
        ::"r"(dst), "l"((uint64_t)map), "r"(bar), "r"(c0), "r"(c1), "r"(c2)
        : "memory");
}
__device__ __forceinline__ void tma_store_3d(const CUtensorMap* map, uint32_t src, int c0, int c1, int c2) {
    asm volatile("cp.async.bulk.tensor.3d.global.shared::cta.bulk_group [%0, {%2, %3, %4}], [%1];"
                 ::"l"((uint64_t)map), "r"(src), "r"(c0), "r"(c1), "r"(c2)
                 : "memory");
}
__device__ __forceinline__ void tma_commit() { asm volatile("cp.async.bulk.commit_group;" ::: "memory"); }
__device__ __forceinline__ void tma_wait_read0() { asm volatile("cp.async.bulk.wait_group.read 0;" ::: "memory"); }
__device__ __forceinline__ void tma_wait_all0() { asm volatile("cp.async.bulk.wait_group 0;" ::: "memory"); }
__device__ __forceinline__ void fence_proxy_async() { asm volatile("fence.proxy.async.shared::cta;" ::: "memory"); }
__device__ __forceinline__ void prefetch_tmap(const CUtensorMap* map) {
    asm volatile("prefetch.tensormap [%0];" ::"l"((uint64_t)map) : "memory");
}
__device__ __forceinline__ void named_sync(int id, int n) { asm volatile("bar.sync %0, %1;" ::"r"(id), "r"(n) : "memory"); }
__device__ __forceinline__ void named_arrive(int id, int n) { asm volatile("bar.arrive %0, %1;" ::"r"(id), "r"(n) : "memory"); }

__device__ __forceinline__ void wgmma_fence() { asm volatile("wgmma.fence.sync.aligned;" ::: "memory"); }
__device__ __forceinline__ void wgmma_commit() { asm volatile("wgmma.commit_group.sync.aligned;" ::: "memory"); }
template <int N>
__device__ __forceinline__ void wgmma_wait() { asm volatile("wgmma.wait_group.sync.aligned %0;" ::"n"(N) : "memory"); }

template <int R>
__device__ __forceinline__ void reg_alloc() { asm volatile("setmaxnreg.inc.sync.aligned.u32 %0;" ::"n"(R)); }
template <int R>
__device__ __forceinline__ void reg_dealloc() { asm volatile("setmaxnreg.dec.sync.aligned.u32 %0;" ::"n"(R)); }

__device__ __forceinline__ uint64_t make_desc(uint32_t saddr, uint32_t lbo_bytes, uint32_t sbo_bytes) {
    uint64_t d = 0;
    d |= (uint64_t)((saddr & 0x3FFFF) >> 4);
    d |= (uint64_t)((lbo_bytes >> 4) & 0x3FFF) << 16;
    d |= (uint64_t)((sbo_bytes >> 4) & 0x3FFF) << 32;
    d |= (uint64_t)1 << 62;
    return d;
}

__device__ __forceinline__ float ex2(float x) {
    float y;
    asm("ex2.approx.ftz.f32 %0, %1;" : "=f"(y) : "f"(x));
    return y;
}
__device__ __forceinline__ uint32_t pack_bf16(float lo, float hi) {
    uint32_t r;
    asm("cvt.rn.bf16x2.f32 %0, %1, %2;" : "=r"(r) : "f"(hi), "f"(lo));
    return r;
}
__device__ __forceinline__ float bf16_round(float x) { return __bfloat162float(__float2bfloat16_rn(x)); }
__device__ __forceinline__ float silu_f(float x) { return x / (1.0f + __expf(-x)); }

__device__ __forceinline__ void stmatrix_x4(uint32_t addr, uint32_t r0, uint32_t r1, uint32_t r2, uint32_t r3) {
    asm volatile("stmatrix.sync.aligned.m8n8.x4.shared.b16 [%0], {%1, %2, %3, %4};"
                 ::"r"(addr), "r"(r0), "r"(r1), "r"(r2), "r"(r3)
                 : "memory");
}

#define ACC64(d) \
    "+f"(d[0]), "+f"(d[1]), "+f"(d[2]), "+f"(d[3]), "+f"(d[4]), "+f"(d[5]), "+f"(d[6]), "+f"(d[7]), \
    "+f"(d[8]), "+f"(d[9]), "+f"(d[10]), "+f"(d[11]), "+f"(d[12]), "+f"(d[13]), "+f"(d[14]), "+f"(d[15]), \
    "+f"(d[16]), "+f"(d[17]), "+f"(d[18]), "+f"(d[19]), "+f"(d[20]), "+f"(d[21]), "+f"(d[22]), "+f"(d[23]), \
    "+f"(d[24]), "+f"(d[25]), "+f"(d[26]), "+f"(d[27]), "+f"(d[28]), "+f"(d[29]), "+f"(d[30]), "+f"(d[31]), \
    "+f"(d[32]), "+f"(d[33]), "+f"(d[34]), "+f"(d[35]), "+f"(d[36]), "+f"(d[37]), "+f"(d[38]), "+f"(d[39]), \
    "+f"(d[40]), "+f"(d[41]), "+f"(d[42]), "+f"(d[43]), "+f"(d[44]), "+f"(d[45]), "+f"(d[46]), "+f"(d[47]), \
    "+f"(d[48]), "+f"(d[49]), "+f"(d[50]), "+f"(d[51]), "+f"(d[52]), "+f"(d[53]), "+f"(d[54]), "+f"(d[55]), \
    "+f"(d[56]), "+f"(d[57]), "+f"(d[58]), "+f"(d[59]), "+f"(d[60]), "+f"(d[61]), "+f"(d[62]), "+f"(d[63])

#define ACC64_STR \
    "{%0, %1, %2, %3, %4, %5, %6, %7, %8, %9, %10, %11, %12, %13, %14, %15, " \
    "%16, %17, %18, %19, %20, %21, %22, %23, %24, %25, %26, %27, %28, %29, %30, %31, " \
    "%32, %33, %34, %35, %36, %37, %38, %39, %40, %41, %42, %43, %44, %45, %46, %47, " \
    "%48, %49, %50, %51, %52, %53, %54, %55, %56, %57, %58, %59, %60, %61, %62, %63}"

template <int TB>
__device__ __forceinline__ void wgmma_ss_n128(float (&d)[64], uint64_t da, uint64_t db, int scale_d) {
    asm volatile(
        "{\n.reg .pred p;\nsetp.ne.b32 p, %66, 0;\n"
        "wgmma.mma_async.sync.aligned.m64n128k16.f32.bf16.bf16 " ACC64_STR ", %64, %65, p, 1, 1, 0, %67;\n}\n"
        : ACC64(d)
        : "l"(da), "l"(db), "r"(scale_d), "n"(TB));
}
template <int TB>
__device__ __forceinline__ void wgmma_rs_n128(float (&d)[64], uint32_t a0, uint32_t a1, uint32_t a2, uint32_t a3,
                                              uint64_t db, int scale_d) {
    asm volatile(
        "{\n.reg .pred p;\nsetp.ne.b32 p, %69, 0;\n"
        "wgmma.mma_async.sync.aligned.m64n128k16.f32.bf16.bf16 " ACC64_STR ", {%64, %65, %66, %67}, %68, p, 1, 1, %70;\n}\n"
        : ACC64(d)
        : "r"(a0), "r"(a1), "r"(a2), "r"(a3), "l"(db), "r"(scale_d), "n"(TB));
}

__global__ void __launch_bounds__(256) ln_kernel(const bf16* __restrict__ x) {
    int warp = threadIdx.x >> 5, lane = threadIdx.x & 31;
    int row = blockIdx.x * 8 + warp;
    const uint4* src = reinterpret_cast<const uint4*>(x + (size_t)row * DM);
    uint4 v[2];
    v[0] = src[lane];
    v[1] = src[lane + 32];
    float f[16];
#pragma unroll
    for (int i = 0; i < 2; i++) {
        const __nv_bfloat162* p = reinterpret_cast<const __nv_bfloat162*>(&v[i]);
#pragma unroll
        for (int j = 0; j < 4; j++) {
            float2 t = __bfloat1622float2(p[j]);
            f[i * 8 + j * 2] = t.x;
            f[i * 8 + j * 2 + 1] = t.y;
        }
    }
    float s = 0.f;
#pragma unroll
    for (int i = 0; i < 16; i++) s += f[i];
#pragma unroll
    for (int o = 16; o > 0; o >>= 1) s += __shfl_xor_sync(0xffffffffu, s, o);
    float mean = s * (1.0f / DM);
    float q = 0.f;
#pragma unroll
    for (int i = 0; i < 16; i++) {
        float d = f[i] - mean;
        q += d * d;
    }
#pragma unroll
    for (int o = 16; o > 0; o >>= 1) q += __shfl_xor_sync(0xffffffffu, q, o);
    float var_b = bf16_round(q * (1.0f / DM));
    float mean_b = bf16_round(mean);
    float den = bf16_round(sqrtf(bf16_round(var_b + 1e-5f)));
    uint4 o[2];
#pragma unroll
    for (int i = 0; i < 2; i++) {
        uint32_t* p = reinterpret_cast<uint32_t*>(&o[i]);
#pragma unroll
        for (int j = 0; j < 4; j++) {
            float a = bf16_round(f[i * 8 + j * 2] - mean_b) / den;
            float b = bf16_round(f[i * 8 + j * 2 + 1] - mean_b) / den;
            p[j] = pack_bf16(a, b);
        }
    }
    uint4* dst = reinterpret_cast<uint4*>(g_xn + (size_t)row * DM);
    dst[lane] = o[0];
    dst[lane + 32] = o[1];
}

constexpr int AT_STAGES = 2;
constexpr int TILE_BYTES = 128 * 128 * 2;
struct __align__(1024) AttnSmem {
    uint8_t k[AT_STAGES][TILE_BYTES];
    uint8_t v[AT_STAGES][TILE_BYTES];
    uint8_t o[TILE_BYTES];
    uint64_t full_k[AT_STAGES], full_v[AT_STAGES], empty_k[AT_STAGES], empty_v[AT_STAGES];
};

constexpr int NUM_AT_TILES = NH * (SEQ / 128);

__global__ void __launch_bounds__(384, 1)
attn_kernel(const __grid_constant__ CUtensorMap tm_xn, const __grid_constant__ CUtensorMap tm_wq,
            const __grid_constant__ CUtensorMap tm_k, const __grid_constant__ CUtensorMap tm_v,
            const __grid_constant__ CUtensorMap tm_o) {
    extern __shared__ uint8_t smem_raw[];
    AttnSmem& sm = *reinterpret_cast<AttnSmem*>((reinterpret_cast<uintptr_t>(smem_raw) + 1023) & ~uintptr_t(1023));
    const int tid = threadIdx.x;
    const int wg = tid >> 7;

    if (tid == 0) {
#pragma unroll
        for (int s = 0; s < AT_STAGES; s++) {
            mbar_init(smem_u32(&sm.full_k[s]), 1);
            mbar_init(smem_u32(&sm.full_v[s]), 1);
            mbar_init(smem_u32(&sm.empty_k[s]), 8);
            mbar_init(smem_u32(&sm.empty_v[s]), 8);
        }
        asm volatile("fence.mbarrier_init.release.cluster;" ::: "memory");
    }
    __syncthreads();

    if (wg == 0) {
        reg_dealloc<24>();
        if (tid == 0) {
            prefetch_tmap(&tm_xn);
            prefetch_tmap(&tm_wq);
            prefetch_tmap(&tm_k);
            prefetch_tmap(&tm_v);
            int stage = 0;
            uint32_t phase = 0;
            for (int tile = blockIdx.x; tile < NUM_AT_TILES; tile += gridDim.x) {
                const int h = tile >> 4, qb = tile & 15;
                for (int kc = 0; kc < 4; kc++) {
                    mbar_wait(smem_u32(&sm.empty_k[stage]), phase ^ 1);
                    mbar_expect_tx(smem_u32(&sm.full_k[stage]), TILE_BYTES);
                    tma_load_3d(smem_u32(sm.k[stage]), &tm_xn, smem_u32(&sm.full_k[stage]), 0, qb * 128, kc * 2);
                    mbar_wait(smem_u32(&sm.empty_v[stage]), phase ^ 1);
                    mbar_expect_tx(smem_u32(&sm.full_v[stage]), TILE_BYTES);
                    tma_load_3d(smem_u32(sm.v[stage]), &tm_wq, smem_u32(&sm.full_v[stage]), 0, kc * 128, h * 2);
                    if (++stage == AT_STAGES) { stage = 0; phase ^= 1; }
                }
                for (int j = 0; j < 16; j++) {
                    mbar_wait(smem_u32(&sm.empty_k[stage]), phase ^ 1);
                    mbar_expect_tx(smem_u32(&sm.full_k[stage]), TILE_BYTES);
                    tma_load_3d(smem_u32(sm.k[stage]), &tm_k, smem_u32(&sm.full_k[stage]), 0, h * SEQ + j * 128, 0);
                    mbar_wait(smem_u32(&sm.empty_v[stage]), phase ^ 1);
                    mbar_expect_tx(smem_u32(&sm.full_v[stage]), TILE_BYTES);
                    tma_load_3d(smem_u32(sm.v[stage]), &tm_v, smem_u32(&sm.full_v[stage]), 0, h * SEQ + j * 128, 0);
                    if (++stage == AT_STAGES) { stage = 0; phase ^= 1; }
                }
            }
        }
    } else {
        reg_alloc<240>();
        const int cw = wg - 1;
        const int lane = tid & 31;
        const int warp_in_wg = (tid >> 5) & 3;
        const float c = 0.08838834764831845f * 1.4426950408889634f;
        constexpr int BAR_SCHED0 = 1, BAR_EPI0 = 3;

        if (cw == 1) named_arrive(BAR_SCHED0 + 0, 256);

        int stage = 0;
        uint32_t phase = 0;
        float S[64], O[64];
        uint32_t P[32], Q[32];

        for (int tile = blockIdx.x; tile < NUM_AT_TILES; tile += gridDim.x) {
            const int h = tile >> 4, qb = tile & 15;
#pragma unroll 1
            for (int kc = 0; kc < 4; kc++) {
                mbar_wait(smem_u32(&sm.full_k[stage]), phase);
                mbar_wait(smem_u32(&sm.full_v[stage]), phase);
                const uint64_t da = make_desc(smem_u32(sm.k[stage]) + cw * 64 * 128, 16, 1024);
                const uint64_t db = make_desc(smem_u32(sm.v[stage]), 16384, 1024);
                wgmma_fence();
#pragma unroll
                for (int kk = 0; kk < 8; kk++) {
                    wgmma_ss_n128<1>(S, da + (uint64_t)(((kk >> 2) * 16384 + (kk & 3) * 32) >> 4),
                                     db + (uint64_t)((kk * 2048) >> 4), (kc | kk) != 0);
                }
                wgmma_commit();
                wgmma_wait<0>();
                if (lane == 0) {
                    mbar_arrive(smem_u32(&sm.empty_k[stage]));
                    mbar_arrive(smem_u32(&sm.empty_v[stage]));
                }
                if (++stage == AT_STAGES) { stage = 0; phase ^= 1; }
            }
#pragma unroll
            for (int i = 0; i < 32; i++) Q[i] = pack_bf16(S[2 * i], S[2 * i + 1]);
#pragma unroll
            for (int i = 0; i < 64; i++) O[i] = 0.f;

            float m0 = -INFINITY, m1 = -INFINITY, l0 = 0.f, l1 = 0.f, a0 = 0.f, a1 = 0.f;

            {
                mbar_wait(smem_u32(&sm.full_k[stage]), phase);
                const uint64_t dk = make_desc(smem_u32(sm.k[stage]), 16, 1024);
                named_sync(BAR_SCHED0 + cw, 256);
                wgmma_fence();
#pragma unroll
                for (int kk = 0; kk < 8; kk++)
                    wgmma_rs_n128<0>(S, Q[4 * kk], Q[4 * kk + 1], Q[4 * kk + 2], Q[4 * kk + 3],
                                     dk + (uint64_t)(((kk >> 2) * 16384 + (kk & 3) * 32) >> 4), kk != 0);
                wgmma_commit();
                named_arrive(BAR_SCHED0 + (cw ^ 1), 256);
                wgmma_wait<0>();
                if (lane == 0) mbar_arrive(smem_u32(&sm.empty_k[stage]));
            }
            int vstage = stage;
            uint32_t vphase = phase;
            if (++stage == AT_STAGES) { stage = 0; phase ^= 1; }

            auto softmax = [&]() {
                float x0 = m0, x1 = m1;
#pragma unroll
                for (int i = 0; i < 16; i++) {
                    x0 = fmaxf(x0, fmaxf(S[4 * i], S[4 * i + 1]));
                    x1 = fmaxf(x1, fmaxf(S[4 * i + 2], S[4 * i + 3]));
                }
                x0 = fmaxf(x0, __shfl_xor_sync(0xffffffffu, x0, 1));
                x1 = fmaxf(x1, __shfl_xor_sync(0xffffffffu, x1, 1));
                x0 = fmaxf(x0, __shfl_xor_sync(0xffffffffu, x0, 2));
                x1 = fmaxf(x1, __shfl_xor_sync(0xffffffffu, x1, 2));
                a0 = ex2((m0 - x0) * c);
                a1 = ex2((m1 - x1) * c);
                m0 = x0;
                m1 = x1;
                const float n0 = -x0 * c, n1 = -x1 * c;
                float s0 = 0.f, s1 = 0.f;
#pragma unroll
                for (int i = 0; i < 16; i++) {
                    S[4 * i] = ex2(fmaf(S[4 * i], c, n0));
                    S[4 * i + 1] = ex2(fmaf(S[4 * i + 1], c, n0));
                    S[4 * i + 2] = ex2(fmaf(S[4 * i + 2], c, n1));
                    S[4 * i + 3] = ex2(fmaf(S[4 * i + 3], c, n1));
                    s0 += S[4 * i] + S[4 * i + 1];
                    s1 += S[4 * i + 2] + S[4 * i + 3];
                }
                l0 = l0 * a0 + s0;
                l1 = l1 * a1 + s1;
            };
            softmax();
#pragma unroll
            for (int i = 0; i < 32; i++) P[i] = pack_bf16(S[2 * i], S[2 * i + 1]);

#pragma unroll 1
            for (int j = 1; j < 16; j++) {
                mbar_wait(smem_u32(&sm.full_k[stage]), phase);
                const uint64_t dk = make_desc(smem_u32(sm.k[stage]), 16, 1024);
                const uint64_t dv = make_desc(smem_u32(sm.v[vstage]), 16384, 1024);
                named_sync(BAR_SCHED0 + cw, 256);
                wgmma_fence();
#pragma unroll
                for (int kk = 0; kk < 8; kk++)
                    wgmma_rs_n128<0>(S, Q[4 * kk], Q[4 * kk + 1], Q[4 * kk + 2], Q[4 * kk + 3],
                                     dk + (uint64_t)(((kk >> 2) * 16384 + (kk & 3) * 32) >> 4), kk != 0);
                wgmma_commit();
#pragma unroll
                for (int i = 0; i < 16; i++) {
                    O[4 * i] *= a0;
                    O[4 * i + 1] *= a0;
                    O[4 * i + 2] *= a1;
                    O[4 * i + 3] *= a1;
                }
                mbar_wait(smem_u32(&sm.full_v[vstage]), vphase);
                wgmma_fence();
#pragma unroll
                for (int kk = 0; kk < 8; kk++)
                    wgmma_rs_n128<1>(O, P[4 * kk], P[4 * kk + 1], P[4 * kk + 2], P[4 * kk + 3],
                                     dv + (uint64_t)((kk * 2048) >> 4), 1);
                wgmma_commit();
                named_arrive(BAR_SCHED0 + (cw ^ 1), 256);
                wgmma_wait<1>();
                if (lane == 0) mbar_arrive(smem_u32(&sm.empty_k[stage]));
                softmax();
                wgmma_wait<0>();
                if (lane == 0) mbar_arrive(smem_u32(&sm.empty_v[vstage]));
#pragma unroll
                for (int i = 0; i < 32; i++) P[i] = pack_bf16(S[2 * i], S[2 * i + 1]);
                vstage = stage;
                vphase = phase;
                if (++stage == AT_STAGES) { stage = 0; phase ^= 1; }
            }
            {
#pragma unroll
                for (int i = 0; i < 16; i++) {
                    O[4 * i] *= a0;
                    O[4 * i + 1] *= a0;
                    O[4 * i + 2] *= a1;
                    O[4 * i + 3] *= a1;
                }
                const uint64_t dv = make_desc(smem_u32(sm.v[vstage]), 16384, 1024);
                mbar_wait(smem_u32(&sm.full_v[vstage]), vphase);
                wgmma_fence();
#pragma unroll
                for (int kk = 0; kk < 8; kk++)
                    wgmma_rs_n128<1>(O, P[4 * kk], P[4 * kk + 1], P[4 * kk + 2], P[4 * kk + 3],
                                     dv + (uint64_t)((kk * 2048) >> 4), 1);
                wgmma_commit();
                wgmma_wait<0>();
                if (lane == 0) mbar_arrive(smem_u32(&sm.empty_v[vstage]));
            }
            l0 += __shfl_xor_sync(0xffffffffu, l0, 1);
            l1 += __shfl_xor_sync(0xffffffffu, l1, 1);
            l0 += __shfl_xor_sync(0xffffffffu, l0, 2);
            l1 += __shfl_xor_sync(0xffffffffu, l1, 2);
            const float i0 = 1.0f / l0, i1 = 1.0f / l1;
            const uint32_t obase = smem_u32(sm.o) + cw * 16384;
            if ((tid & 127) == 0) tma_wait_read0();
            named_sync(BAR_EPI0 + cw, 128);
            {
                const int row = warp_in_wg * 16 + ((lane >> 3) & 1) * 8 + (lane & 7);
#pragma unroll
                for (int i = 0; i < 16; i += 2) {
                    const int cc = i + (lane >> 4);
                    const uint32_t addr = obase + (cc >> 3) * 8192 + row * 128 + (((cc & 7) ^ (row & 7)) << 4);
                    stmatrix_x4(addr, pack_bf16(O[4 * i] * i0, O[4 * i + 1] * i0), pack_bf16(O[4 * i + 2] * i1, O[4 * i + 3] * i1),
                                pack_bf16(O[4 * i + 4] * i0, O[4 * i + 5] * i0), pack_bf16(O[4 * i + 6] * i1, O[4 * i + 7] * i1));
                }
            }
            fence_proxy_async();
            named_sync(BAR_EPI0 + cw, 128);
            if ((tid & 127) == 0) {
                tma_store_3d(&tm_o, obase, 0, qb * 128 + cw * 64, h * 2);
                tma_commit();
            }
        }
        if ((tid & 127) == 0) tma_wait_all0();
    }
}

constexpr int G_STAGES = 4;
struct __align__(1024) GemmSmem {
    uint8_t a[G_STAGES][128 * 64 * 2];
    uint8_t b[G_STAGES][64 * 128 * 2];
    uint64_t full[G_STAGES], empty[G_STAGES];
};

__device__ __forceinline__ void gemm_producer(GemmSmem& sm, const CUtensorMap* ta, const CUtensorMap* tb, int m0, int n0,
                                              int ktiles, int& stage, uint32_t& phase) {
    for (int kt = 0; kt < ktiles; kt++) {
        mbar_wait(smem_u32(&sm.empty[stage]), phase ^ 1);
        mbar_expect_tx(smem_u32(&sm.full[stage]), 32768);
        tma_load_3d(smem_u32(sm.a[stage]), ta, smem_u32(&sm.full[stage]), 0, m0, kt);
        tma_load_3d(smem_u32(sm.b[stage]), tb, smem_u32(&sm.full[stage]), 0, kt * 64, n0 >> 6);
        if (++stage == G_STAGES) { stage = 0; phase ^= 1; }
    }
}

__device__ __forceinline__ void gemm_consumer(GemmSmem& sm, float (&acc)[64], int cw, int lane, int ktiles, int& stage,
                                              uint32_t& phase) {
    int prev = -1;
#pragma unroll 1
    for (int kt = 0; kt < ktiles; kt++) {
        mbar_wait(smem_u32(&sm.full[stage]), phase);
        const uint64_t da = make_desc(smem_u32(sm.a[stage]) + cw * 64 * 128, 16, 1024);
        const uint64_t db = make_desc(smem_u32(sm.b[stage]), 8192, 1024);
        wgmma_fence();
#pragma unroll
        for (int kk = 0; kk < 4; kk++)
            wgmma_ss_n128<1>(acc, da + (uint64_t)((kk * 32) >> 4), db + (uint64_t)((kk * 2048) >> 4), (kt | kk) != 0);
        wgmma_commit();
        wgmma_wait<1>();
        if (prev >= 0 && lane == 0) mbar_arrive(smem_u32(&sm.empty[prev]));
        prev = stage;
        if (++stage == G_STAGES) { stage = 0; phase ^= 1; }
    }
    wgmma_wait<0>();
    if (lane == 0) mbar_arrive(smem_u32(&sm.empty[prev]));
}

__global__ void __launch_bounds__(384, 1)
ffn1_kernel(const __grid_constant__ CUtensorMap tm_a, const __grid_constant__ CUtensorMap tm_b) {
    extern __shared__ uint8_t smem_raw[];
    GemmSmem& sm = *reinterpret_cast<GemmSmem*>((reinterpret_cast<uintptr_t>(smem_raw) + 1023) & ~uintptr_t(1023));
    const int tid = threadIdx.x, wg = tid >> 7;
    const int m0 = blockIdx.y * 128, n0 = blockIdx.x * 128;
    if (tid == 0) {
        for (int s = 0; s < G_STAGES; s++) {
            mbar_init(smem_u32(&sm.full[s]), 1);
            mbar_init(smem_u32(&sm.empty[s]), 8);
        }
        asm volatile("fence.mbarrier_init.release.cluster;" ::: "memory");
    }
    __syncthreads();
    int stage = 0;
    uint32_t phase = 0;
    if (wg == 0) {
        if (tid == 0) gemm_producer(sm, &tm_a, &tm_b, m0, n0, DM / 64, stage, phase);
    } else {
        const int cw = wg - 1, lane = tid & 31, warp_in_wg = (tid >> 5) & 3;
        float acc[64];
        gemm_consumer(sm, acc, cw, lane, DM / 64, stage, phase);
        const int r0 = m0 + cw * 64 + warp_in_wg * 16 + (lane >> 2);
#pragma unroll
        for (int i = 0; i < 16; i++) {
            const int col = n0 + i * 8 + (lane & 3) * 2;
            float v0 = silu_f(bf16_round(acc[4 * i])), v1 = silu_f(bf16_round(acc[4 * i + 1]));
            float v2 = silu_f(bf16_round(acc[4 * i + 2])), v3 = silu_f(bf16_round(acc[4 * i + 3]));
            *reinterpret_cast<uint32_t*>(g_h + (size_t)r0 * FF + col) = pack_bf16(v0, v1);
            *reinterpret_cast<uint32_t*>(g_h + (size_t)(r0 + 8) * FF + col) = pack_bf16(v2, v3);
        }
    }
}

__global__ void __launch_bounds__(384, 1)
final_kernel(const __grid_constant__ CUtensorMap tm_o, const __grid_constant__ CUtensorMap tm_wo,
             const __grid_constant__ CUtensorMap tm_h, const __grid_constant__ CUtensorMap tm_w2,
             const bf16* __restrict__ x, bf16* __restrict__ out) {
    extern __shared__ uint8_t smem_raw[];
    GemmSmem& sm = *reinterpret_cast<GemmSmem*>((reinterpret_cast<uintptr_t>(smem_raw) + 1023) & ~uintptr_t(1023));
    const int tid = threadIdx.x, wg = tid >> 7;
    const int m0 = blockIdx.y * 128, n0 = blockIdx.x * 128;
    if (tid == 0) {
        for (int s = 0; s < G_STAGES; s++) {
            mbar_init(smem_u32(&sm.full[s]), 1);
            mbar_init(smem_u32(&sm.empty[s]), 8);
        }
        asm volatile("fence.mbarrier_init.release.cluster;" ::: "memory");
    }
    __syncthreads();
    int stage = 0;
    uint32_t phase = 0;
    if (wg == 0) {
        if (tid == 0) {
            gemm_producer(sm, &tm_h, &tm_w2, m0, n0, FF / 64, stage, phase);
            gemm_producer(sm, &tm_o, &tm_wo, m0, n0, NH * DH / 64, stage, phase);
        }
    } else {
        const int cw = wg - 1, lane = tid & 31, warp_in_wg = (tid >> 5) & 3;
        float accf[64], accs[64];
        gemm_consumer(sm, accf, cw, lane, FF / 64, stage, phase);
        gemm_consumer(sm, accs, cw, lane, NH * DH / 64, stage, phase);
        const int r0 = m0 + cw * 64 + warp_in_wg * 16 + (lane >> 2);
#pragma unroll
        for (int i = 0; i < 16; i++) {
            const int col = n0 + i * 8 + (lane & 3) * 2;
#pragma unroll
            for (int hh = 0; hh < 2; hh++) {
                const int r = r0 + hh * 8;
                const __nv_bfloat162 xv = *reinterpret_cast<const __nv_bfloat162*>(x + (size_t)r * DM + col);
                float g0 = bf16_round(silu_f(bf16_round(accf[4 * i + 2 * hh])));
                float g1 = bf16_round(silu_f(bf16_round(accf[4 * i + 2 * hh + 1])));
                float s0 = bf16_round(accs[4 * i + 2 * hh]), s1 = bf16_round(accs[4 * i + 2 * hh + 1]);
                float o0 = __bfloat162float(xv.x) + bf16_round(s0 * g0);
                float o1 = __bfloat162float(xv.y) + bf16_round(s1 * g1);
                *reinterpret_cast<uint32_t*>(out + (size_t)r * DM + col) = pack_bf16(o0, o1);
            }
        }
    }
}

typedef CUresult (*EncodeFn)(CUtensorMap*, CUtensorMapDataType, cuuint32_t, void*, const cuuint64_t*, const cuuint64_t*,
                             const cuuint32_t*, const cuuint32_t*, CUtensorMapInterleave, CUtensorMapSwizzle,
                             CUtensorMapL2promotion, CUtensorMapFloatOOBfill);

static CUtensorMap make_map(EncodeFn fn, const void* ptr, uint64_t rows, uint64_t cols, uint32_t box_rows, uint32_t box_blk) {
    CUtensorMap m;
    cuuint64_t dims[3] = {64, rows, cols / 64};
    cuuint64_t strides[2] = {cols * 2, 128};
    cuuint32_t box[3] = {64, box_rows, box_blk};
    cuuint32_t es[3] = {1, 1, 1};
    fn(&m, CU_TENSOR_MAP_DATA_TYPE_BFLOAT16, 3, const_cast<void*>(ptr), dims, strides, box, es, CU_TENSOR_MAP_INTERLEAVE_NONE,
       CU_TENSOR_MAP_SWIZZLE_128B, CU_TENSOR_MAP_L2_PROMOTION_L2_256B, CU_TENSOR_MAP_FLOAT_OOB_FILL_NONE);
    return m;
}

extern "C" void kernel_launch(void* const* d_in, const int* in_sizes, int n_in, void* d_out, int out_size) {
    const bf16* x = (const bf16*)d_in[0];
    const bf16* kc = (const bf16*)d_in[1];
    const bf16* vc = (const bf16*)d_in[2];
    const bf16* wq = (const bf16*)d_in[3];
    const bf16* wo = (const bf16*)d_in[4];
    const bf16* w1 = (const bf16*)d_in[6];
    const bf16* w2 = (const bf16*)d_in[7];
    bf16* out = (bf16*)d_out;

    static EncodeFn fn = nullptr;
    static void *p_xn = nullptr, *p_h = nullptr, *p_o = nullptr;
    if (!fn) {
        void* f = nullptr;
        cudaDriverEntryPointQueryResult st;
        cudaGetDriverEntryPoint("cuTensorMapEncodeTiled", &f, cudaEnableDefault, &st);
        fn = (EncodeFn)f;
        cudaGetSymbolAddress(&p_xn, g_xn);
        cudaGetSymbolAddress(&p_h, g_h);
        cudaGetSymbolAddress(&p_o, g_o);
        cudaFuncSetAttribute(attn_kernel, cudaFuncAttributeMaxDynamicSharedMemorySize, (int)sizeof(AttnSmem) + 1024);
        cudaFuncSetAttribute(ffn1_kernel, cudaFuncAttributeMaxDynamicSharedMemorySize, (int)sizeof(GemmSmem) + 1024);
        cudaFuncSetAttribute(final_kernel, cudaFuncAttributeMaxDynamicSharedMemorySize, (int)sizeof(GemmSmem) + 1024);
    }
    CUtensorMap tm_xn_at = make_map(fn, p_xn, SEQ, DM, 128, 2);
    CUtensorMap tm_wq = make_map(fn, wq, DM, NH * DH, 128, 2);
    CUtensorMap tm_k = make_map(fn, kc, NH * SEQ, DH, 128, 2);
    CUtensorMap tm_v = make_map(fn, vc, NH * SEQ, DH, 128, 2);
    CUtensorMap tm_o_st = make_map(fn, p_o, SEQ, NH * DH, 64, 2);
    CUtensorMap tm_xn_g = make_map(fn, p_xn, SEQ, DM, 128, 1);
    CUtensorMap tm_w1 = make_map(fn, w1, DM, FF, 64, 2);
    CUtensorMap tm_o_g = make_map(fn, p_o, SEQ, NH * DH, 128, 1);
    CUtensorMap tm_wo = make_map(fn, wo, NH * DH, DM, 64, 2);
    CUtensorMap tm_h_g = make_map(fn, p_h, SEQ, FF, 128, 1);
    CUtensorMap tm_w2 = make_map(fn, w2, FF, DM, 64, 2);

    ln_kernel<<<SEQ / 8, 256>>>(x);
    ffn1_kernel<<<dim3(FF / 128, SEQ / 128), 384, sizeof(GemmSmem) + 1024>>>(tm_xn_g, tm_w1);
    attn_kernel<<<132, 384, sizeof(AttnSmem) + 1024>>>(tm_xn_at, tm_wq, tm_k, tm_v, tm_o_st);
    final_kernel<<<dim3(DM / 128, SEQ / 128), 384, sizeof(GemmSmem) + 1024>>>(tm_o_g, tm_wo, tm_h_g, tm_w2, x, out);
}
```

```cpp
#include <cuda_runtime.h>
#include <cuda_bf16.h>
#include <cuda.h>
#include <stdint.h>

typedef __nv_bfloat16 bf16;

constexpr int SEQ = 2048, DM = 512, NH = 32, DH = 128, FF = 1792;

__device__ __align__(1024) bf16 g_xn[SEQ * DM];
__device__ __align__(1024) bf16 g_h[SEQ * FF];
__device__ __align__(1024) bf16 g_o[SEQ * NH * DH];

__device__ __forceinline__ uint32_t smem_u32(const void* p) { return (uint32_t)__cvta_generic_to_shared(p); }

__device__ __forceinline__ void mbar_init(uint32_t bar, uint32_t count) {
    asm volatile("mbarrier.init.shared::cta.b64 [%0], %1;" ::"r"(bar), "r"(count) : "memory");
}
__device__ __forceinline__ void mbar_expect_tx(uint32_t bar, uint32_t bytes) {
    asm volatile("mbarrier.arrive.expect_tx.shared::cta.b64 _, [%0], %1;" ::"r"(bar), "r"(bytes) : "memory");
}
__device__ __forceinline__ void mbar_arrive(uint32_t bar) {
    asm volatile("mbarrier.arrive.shared::cta.b64 _, [%0];" ::"r"(bar) : "memory");
}
__device__ __forceinline__ bool mbar_try_wait(uint32_t bar, uint32_t parity) {
    uint32_t ok;
    asm volatile(
        "{\n.reg .pred p;\n"
        "mbarrier.try_wait.parity.shared::cta.b64 p, [%1], %2;\n"
        "selp.u32 %0, 1, 0, p;\n}\n"
        : "=r"(ok)
        : "r"(bar), "r"(parity)
        : "memory");
    return ok != 0;
}
__device__ __forceinline__ void mbar_wait(uint32_t bar, uint32_t parity) {
    asm volatile(
        "{\n.reg .pred P1;\n.reg .u32 n;\nmov.u32 n, 0;\n"
        "LAB_WAIT:\n"
        "mbarrier.try_wait.parity.shared::cta.b64 P1, [%0], %1;\n"
        "@P1 bra DONE;\n"
        "add.u32 n, n, 1;\n"
        "setp.lt.u32 P1, n, 4194304;\n"
        "@P1 bra LAB_WAIT;\n"
        "trap;\n"
        "DONE:\n}\n" ::"r"(bar), "r"(parity)
        : "memory");
}
__device__ __forceinline__ void tma_load_3d(uint32_t dst, const CUtensorMap* map, uint32_t bar, int c0, int c1, int c2) {
    asm volatile(
        "cp.async.bulk.tensor.3d.shared::cluster.global.mbarrier::complete_tx::bytes [%0], [%1, {%3, %4, %5}], [%2];"
        ::"r"(dst), "l"((uint64_t)map), "r"(bar), "r"(c0), "r"(c1), "r"(c2)
        : "memory");
}
__device__ __forceinline__ void tma_store_3d(const CUtensorMap* map, uint32_t src, int c0, int c1, int c2) {
    asm volatile("cp.async.bulk.tensor.3d.global.shared::cta.bulk_group [%0, {%2, %3, %4}], [%1];"
                 ::"l"((uint64_t)map), "r"(src), "r"(c0), "r"(c1), "r"(c2)
                 : "memory");
}
__device__ __forceinline__ void tma_commit() { asm volatile("cp.async.bulk.commit_group;" ::: "memory"); }
__device__ __forceinline__ void tma_wait_read0() { asm volatile("cp.async.bulk.wait_group.read 0;" ::: "memory"); }
__device__ __forceinline__ void tma_wait_all0() { asm volatile("cp.async.bulk.wait_group 0;" ::: "memory"); }
__device__ __forceinline__ void fence_proxy_async() { asm volatile("fence.proxy.async.shared::cta;" ::: "memory"); }
__device__ __forceinline__ void prefetch_tmap(const CUtensorMap* map) {
    asm volatile("prefetch.tensormap [%0];" ::"l"((uint64_t)map) : "memory");
}
__device__ __forceinline__ void named_sync(int id, int n) { asm volatile("bar.sync %0, %1;" ::"r"(id), "r"(n) : "memory"); }
__device__ __forceinline__ void named_arrive(int id, int n) { asm volatile("bar.arrive %0, %1;" ::"r"(id), "r"(n) : "memory"); }

__device__ __forceinline__ void wgmma_fence() { asm volatile("wgmma.fence.sync.aligned;" ::: "memory"); }
__device__ __forceinline__ void wgmma_commit() { asm volatile("wgmma.commit_group.sync.aligned;" ::: "memory"); }
template <int N>
__device__ __forceinline__ void wgmma_wait() { asm volatile("wgmma.wait_group.sync.aligned %0;" ::"n"(N) : "memory"); }

template <int R>
__device__ __forceinline__ void reg_alloc() { asm volatile("setmaxnreg.inc.sync.aligned.u32 %0;" ::"n"(R)); }
template <int R>
__device__ __forceinline__ void reg_dealloc() { asm volatile("setmaxnreg.dec.sync.aligned.u32 %0;" ::"n"(R)); }

__device__ __forceinline__ uint64_t make_desc(uint32_t saddr, uint32_t lbo_bytes, uint32_t sbo_bytes) {
    uint64_t d = 0;
    d |= (uint64_t)((saddr & 0x3FFFF) >> 4);
    d |= (uint64_t)((lbo_bytes >> 4) & 0x3FFF) << 16;
    d |= (uint64_t)((sbo_bytes >> 4) & 0x3FFF) << 32;
    d |= (uint64_t)1 << 62;
    return d;
}

__device__ __forceinline__ float ex2(float x) {
    float y;
    asm("ex2.approx.ftz.f32 %0, %1;" : "=f"(y) : "f"(x));
    return y;
}
__device__ __forceinline__ uint32_t pack_bf16(float lo, float hi) {
    uint32_t r;
    asm("cvt.rn.bf16x2.f32 %0, %1, %2;" : "=r"(r) : "f"(hi), "f"(lo));
    return r;
}
__device__ __forceinline__ uint32_t mul_bf16x2(uint32_t a, uint32_t b) {
    uint32_t r;
    asm("mul.rn.bf16x2 %0, %1, %2;" : "=r"(r) : "r"(a), "r"(b));
    return r;
}
__device__ __forceinline__ uint32_t fma_bf16x2(uint32_t a, uint32_t b, uint32_t c) {
    uint32_t r;
    asm("fma.rn.bf16x2 %0, %1, %2, %3;" : "=r"(r) : "r"(a), "r"(b), "r"(c));
    return r;
}
__device__ __forceinline__ uint32_t max_bf16x2(uint32_t a, uint32_t b) {
    uint32_t r;
    asm("max.bf16x2 %0, %1, %2;" : "=r"(r) : "r"(a), "r"(b));
    return r;
}
__device__ __forceinline__ float bf16lo(uint32_t v) { return __uint_as_float(v << 16); }
__device__ __forceinline__ float bf16hi(uint32_t v) { return __uint_as_float(v & 0xffff0000u); }
__device__ __forceinline__ float bf16_round(float x) { return __bfloat162float(__float2bfloat16_rn(x)); }
__device__ __forceinline__ float silu_f(float x) { return x / (1.0f + __expf(-x)); }

__device__ __forceinline__ void stmatrix_x4(uint32_t addr, uint32_t r0, uint32_t r1, uint32_t r2, uint32_t r3) {
    asm volatile("stmatrix.sync.aligned.m8n8.x4.shared.b16 [%0], {%1, %2, %3, %4};"
                 ::"r"(addr), "r"(r0), "r"(r1), "r"(r2), "r"(r3)
                 : "memory");
}

#define ACC64(d) \
    "+f"(d[0]), "+f"(d[1]), "+f"(d[2]), "+f"(d[3]), "+f"(d[4]), "+f"(d[5]), "+f"(d[6]), "+f"(d[7]), \
    "+f"(d[8]), "+f"(d[9]), "+f"(d[10]), "+f"(d[11]), "+f"(d[12]), "+f"(d[13]), "+f"(d[14]), "+f"(d[15]), \
    "+f"(d[16]), "+f"(d[17]), "+f"(d[18]), "+f"(d[19]), "+f"(d[20]), "+f"(d[21]), "+f"(d[22]), "+f"(d[23]), \
    "+f"(d[24]), "+f"(d[25]), "+f"(d[26]), "+f"(d[27]), "+f"(d[28]), "+f"(d[29]), "+f"(d[30]), "+f"(d[31]), \
    "+f"(d[32]), "+f"(d[33]), "+f"(d[34]), "+f"(d[35]), "+f"(d[36]), "+f"(d[37]), "+f"(d[38]), "+f"(d[39]), \
    "+f"(d[40]), "+f"(d[41]), "+f"(d[42]), "+f"(d[43]), "+f"(d[44]), "+f"(d[45]), "+f"(d[46]), "+f"(d[47]), \
    "+f"(d[48]), "+f"(d[49]), "+f"(d[50]), "+f"(d[51]), "+f"(d[52]), "+f"(d[53]), "+f"(d[54]), "+f"(d[55]), \
    "+f"(d[56]), "+f"(d[57]), "+f"(d[58]), "+f"(d[59]), "+f"(d[60]), "+f"(d[61]), "+f"(d[62]), "+f"(d[63])

#define ACC64_STR \
    "{%0, %1, %2, %3, %4, %5, %6, %7, %8, %9, %10, %11, %12, %13, %14, %15, " \
    "%16, %17, %18, %19, %20, %21, %22, %23, %24, %25, %26, %27, %28, %29, %30, %31, " \
    "%32, %33, %34, %35, %36, %37, %38, %39, %40, %41, %42, %43, %44, %45, %46, %47, " \
    "%48, %49, %50, %51, %52, %53, %54, %55, %56, %57, %58, %59, %60, %61, %62, %63}"

template <int TB>
__device__ __forceinline__ void wgmma_ss_n128(float (&d)[64], uint64_t da, uint64_t db, int scale_d) {
    asm volatile(
        "{\n.reg .pred p;\nsetp.ne.b32 p, %66, 0;\n"
        "wgmma.mma_async.sync.aligned.m64n128k16.f32.bf16.bf16 " ACC64_STR ", %64, %65, p, 1, 1, 0, %67;\n}\n"
        : ACC64(d)
        : "l"(da), "l"(db), "r"(scale_d), "n"(TB));
}
template <int TB>
__device__ __forceinline__ void wgmma_rs_n128(float (&d)[64], uint32_t a0, uint32_t a1, uint32_t a2, uint32_t a3,
                                              uint64_t db, int scale_d) {
    asm volatile(
        "{\n.reg .pred p;\nsetp.ne.b32 p, %69, 0;\n"
        "wgmma.mma_async.sync.aligned.m64n128k16.f32.bf16.bf16 " ACC64_STR ", {%64, %65, %66, %67}, %68, p, 1, 1, %70;\n}\n"
        : ACC64(d)
        : "r"(a0), "r"(a1), "r"(a2), "r"(a3), "l"(db), "r"(scale_d), "n"(TB));
}

__global__ void __launch_bounds__(256) ln_kernel(const bf16* __restrict__ x) {
    int warp = threadIdx.x >> 5, lane = threadIdx.x & 31;
    int row = blockIdx.x * 8 + warp;
    const uint4* src = reinterpret_cast<const uint4*>(x + (size_t)row * DM);
    uint4 v[2];
    v[0] = src[lane];
    v[1] = src[lane + 32];
    float f[16];
#pragma unroll
    for (int i = 0; i < 2; i++) {
        const __nv_bfloat162* p = reinterpret_cast<const __nv_bfloat162*>(&v[i]);
#pragma unroll
        for (int j = 0; j < 4; j++) {
            float2 t = __bfloat1622float2(p[j]);
            f[i * 8 + j * 2] = t.x;
            f[i * 8 + j * 2 + 1] = t.y;
        }
    }
    float s = 0.f;
#pragma unroll
    for (int i = 0; i < 16; i++) s += f[i];
#pragma unroll
    for (int o = 16; o > 0; o >>= 1) s += __shfl_xor_sync(0xffffffffu, s, o);
    float mean = s * (1.0f / DM);
    float q = 0.f;
#pragma unroll
    for (int i = 0; i < 16; i++) {
        float d = f[i] - mean;
        q += d * d;
    }
#pragma unroll
    for (int o = 16; o > 0; o >>= 1) q += __shfl_xor_sync(0xffffffffu, q, o);
    float var_b = bf16_round(q * (1.0f / DM));
    float mean_b = bf16_round(mean);
    float den = bf16_round(sqrtf(bf16_round(var_b + 1e-5f)));
    uint4 o[2];
#pragma unroll
    for (int i = 0; i < 2; i++) {
        uint32_t* p = reinterpret_cast<uint32_t*>(&o[i]);
#pragma unroll
        for (int j = 0; j < 4; j++) {
            float a = bf16_round(f[i * 8 + j * 2] - mean_b) / den;
            float b = bf16_round(f[i * 8 + j * 2 + 1] - mean_b) / den;
            p[j] = pack_bf16(a, b);
        }
    }
    uint4* dst = reinterpret_cast<uint4*>(g_xn + (size_t)row * DM);
    dst[lane] = o[0];
    dst[lane + 32] = o[1];
}

constexpr int AT_STAGES = 2;
constexpr int TILE_BYTES = 128 * 128 * 2;
struct __align__(1024) AttnSmem {
    uint8_t k[AT_STAGES][TILE_BYTES];
    uint8_t v[AT_STAGES][TILE_BYTES];
    uint8_t o[TILE_BYTES];
    uint64_t full_k[AT_STAGES], full_v[AT_STAGES], empty_k[AT_STAGES], empty_v[AT_STAGES];
};

constexpr int NUM_AT_TILES = NH * (SEQ / 128);

__global__ void __launch_bounds__(384, 1)
attn_kernel(const __grid_constant__ CUtensorMap tm_xn, const __grid_constant__ CUtensorMap tm_wq,
            const __grid_constant__ CUtensorMap tm_k, const __grid_constant__ CUtensorMap tm_v,
            const __grid_constant__ CUtensorMap tm_o) {
    extern __shared__ uint8_t smem_raw[];
    AttnSmem& sm = *reinterpret_cast<AttnSmem*>((reinterpret_cast<uintptr_t>(smem_raw) + 1023) & ~uintptr_t(1023));
    const int tid = threadIdx.x;
    const int wg = tid >> 7;

    if (tid == 0) {
#pragma unroll
        for (int s = 0; s < AT_STAGES; s++) {
            mbar_init(smem_u32(&sm.full_k[s]), 1);
            mbar_init(smem_u32(&sm.full_v[s]), 1);
            mbar_init(smem_u32(&sm.empty_k[s]), 8);
            mbar_init(smem_u32(&sm.empty_v[s]), 8);
        }
        asm volatile("fence.mbarrier_init.release.cluster;" ::: "memory");
    }
    __syncthreads();

    if (wg == 0) {
        reg_dealloc<24>();
        if (tid == 0) {
            prefetch_tmap(&tm_xn);
            prefetch_tmap(&tm_wq);
            prefetch_tmap(&tm_k);
            prefetch_tmap(&tm_v);
            int stage = 0;
            uint32_t phase = 0;
            for (int tile = blockIdx.x; tile < NUM_AT_TILES; tile += gridDim.x) {
                const int h = tile >> 4, qb = tile & 15;
                for (int kc = 0; kc < 4; kc++) {
                    mbar_wait(smem_u32(&sm.empty_k[stage]), phase ^ 1);
                    mbar_expect_tx(smem_u32(&sm.full_k[stage]), TILE_BYTES);
                    tma_load_3d(smem_u32(sm.k[stage]), &tm_xn, smem_u32(&sm.full_k[stage]), 0, qb * 128, kc * 2);
                    mbar_wait(smem_u32(&sm.empty_v[stage]), phase ^ 1);
                    mbar_expect_tx(smem_u32(&sm.full_v[stage]), TILE_BYTES);
                    tma_load_3d(smem_u32(sm.v[stage]), &tm_wq, smem_u32(&sm.full_v[stage]), 0, kc * 128, h * 2);
                    if (++stage == AT_STAGES) { stage = 0; phase ^= 1; }
                }
                for (int j = 0; j < 16; j++) {
                    mbar_wait(smem_u32(&sm.empty_k[stage]), phase ^ 1);
                    mbar_expect_tx(smem_u32(&sm.full_k[stage]), TILE_BYTES);
                    tma_load_3d(smem_u32(sm.k[stage]), &tm_k, smem_u32(&sm.full_k[stage]), 0, h * SEQ + j * 128, 0);
                    mbar_wait(smem_u32(&sm.empty_v[stage]), phase ^ 1);
                    mbar_expect_tx(smem_u32(&sm.full_v[stage]), TILE_BYTES);
                    tma_load_3d(smem_u32(sm.v[stage]), &tm_v, smem_u32(&sm.full_v[stage]), 0, h * SEQ + j * 128, 0);
                    if (++stage == AT_STAGES) { stage = 0; phase ^= 1; }
                }
            }
        }
    } else {
        reg_alloc<240>();
        const int cw = wg - 1;
        const int lane = tid & 31;
        const int warp_in_wg = (tid >> 5) & 3;
        const float c = 1.4426950408889634f;
        const uint32_t SCALE_HI2 = 0x3DB53DB5u, SCALE_LO2 = 0x371E371Eu;
        constexpr int BAR_SCHED0 = 1, BAR_EPI0 = 3;

        if (cw == 1) named_arrive(BAR_SCHED0 + 0, 256);

        int stage = 0;
        uint32_t phase = 0;
        float S[64], O[64];
        uint32_t P[32], Q[32];

        for (int tile = blockIdx.x; tile < NUM_AT_TILES; tile += gridDim.x) {
            const int h = tile >> 4, qb = tile & 15;
#pragma unroll 1
            for (int kc = 0; kc < 4; kc++) {
                mbar_wait(smem_u32(&sm.full_k[stage]), phase);
                mbar_wait(smem_u32(&sm.full_v[stage]), phase);
                const uint64_t da = make_desc(smem_u32(sm.k[stage]) + cw * 64 * 128, 16, 1024);
                const uint64_t db = make_desc(smem_u32(sm.v[stage]), 16384, 1024);
                wgmma_fence();
#pragma unroll
                for (int kk = 0; kk < 8; kk++) {
                    wgmma_ss_n128<1>(S, da + (uint64_t)(((kk >> 2) * 16384 + (kk & 3) * 32) >> 4),
                                     db + (uint64_t)((kk * 2048) >> 4), (kc | kk) != 0);
                }
                wgmma_commit();
                wgmma_wait<0>();
                if (lane == 0) {
                    mbar_arrive(smem_u32(&sm.empty_k[stage]));
                    mbar_arrive(smem_u32(&sm.empty_v[stage]));
                }
                if (++stage == AT_STAGES) { stage = 0; phase ^= 1; }
            }
#pragma unroll
            for (int i = 0; i < 32; i++) Q[i] = pack_bf16(S[2 * i], S[2 * i + 1]);
#pragma unroll
            for (int i = 0; i < 64; i++) O[i] = 0.f;

            float m0 = -INFINITY, m1 = -INFINITY, l0 = 0.f, l1 = 0.f, a0 = 0.f, a1 = 0.f;

            {
                mbar_wait(smem_u32(&sm.full_k[stage]), phase);
                const uint64_t dk = make_desc(smem_u32(sm.k[stage]), 16, 1024);
                named_sync(BAR_SCHED0 + cw, 256);
                wgmma_fence();
#pragma unroll
                for (int kk = 0; kk < 8; kk++)
                    wgmma_rs_n128<0>(S, Q[4 * kk], Q[4 * kk + 1], Q[4 * kk + 2], Q[4 * kk + 3],
                                     dk + (uint64_t)(((kk >> 2) * 16384 + (kk & 3) * 32) >> 4), kk != 0);
                wgmma_commit();
                named_arrive(BAR_SCHED0 + (cw ^ 1), 256);
                wgmma_wait<0>();
                if (lane == 0) mbar_arrive(smem_u32(&sm.empty_k[stage]));
            }
            int vstage = stage;
            uint32_t vphase = phase;
            if (++stage == AT_STAGES) { stage = 0; phase ^= 1; }

            auto softmax = [&]() {
                uint32_t T[32];
#pragma unroll
                for (int i = 0; i < 32; i++) {
                    const uint32_t sb = pack_bf16(S[2 * i], S[2 * i + 1]);
                    T[i] = fma_bf16x2(sb, SCALE_HI2, mul_bf16x2(sb, SCALE_LO2));
                }
                uint32_t y0 = max_bf16x2(T[0], T[2]), y1 = max_bf16x2(T[1], T[3]);
#pragma unroll
                for (int i = 2; i < 16; i++) {
                    y0 = max_bf16x2(y0, T[2 * i]);
                    y1 = max_bf16x2(y1, T[2 * i + 1]);
                }
                float x0 = fmaxf(m0, fmaxf(bf16lo(y0), bf16hi(y0)));
                float x1 = fmaxf(m1, fmaxf(bf16lo(y1), bf16hi(y1)));
                x0 = fmaxf(x0, __shfl_xor_sync(0xffffffffu, x0, 1));
                x1 = fmaxf(x1, __shfl_xor_sync(0xffffffffu, x1, 1));
                x0 = fmaxf(x0, __shfl_xor_sync(0xffffffffu, x0, 2));
                x1 = fmaxf(x1, __shfl_xor_sync(0xffffffffu, x1, 2));
                a0 = ex2((m0 - x0) * c);
                a1 = ex2((m1 - x1) * c);
                m0 = x0;
                m1 = x1;
                const float n0 = -x0 * c, n1 = -x1 * c;
                float s0 = 0.f, s1 = 0.f;
#pragma unroll
                for (int i = 0; i < 16; i++) {
                    S[4 * i] = ex2(fmaf(bf16lo(T[2 * i]), c, n0));
                    S[4 * i + 1] = ex2(fmaf(bf16hi(T[2 * i]), c, n0));
                    S[4 * i + 2] = ex2(fmaf(bf16lo(T[2 * i + 1]), c, n1));
                    S[4 * i + 3] = ex2(fmaf(bf16hi(T[2 * i + 1]), c, n1));
                    s0 += S[4 * i] + S[4 * i + 1];
                    s1 += S[4 * i + 2] + S[4 * i + 3];
                }
                l0 = l0 * a0 + s0;
                l1 = l1 * a1 + s1;
            };
            softmax();
#pragma unroll
            for (int i = 0; i < 32; i++) P[i] = pack_bf16(S[2 * i], S[2 * i + 1]);

#pragma unroll 1
            for (int j = 1; j < 16; j++) {
                mbar_wait(smem_u32(&sm.full_k[stage]), phase);
                const uint64_t dk = make_desc(smem_u32(sm.k[stage]), 16, 1024);
                const uint64_t dv = make_desc(smem_u32(sm.v[vstage]), 16384, 1024);
                named_sync(BAR_SCHED0 + cw, 256);
                wgmma_fence();
#pragma unroll
                for (int kk = 0; kk < 8; kk++)
                    wgmma_rs_n128<0>(S, Q[4 * kk], Q[4 * kk + 1], Q[4 * kk + 2], Q[4 * kk + 3],
                                     dk + (uint64_t)(((kk >> 2) * 16384 + (kk & 3) * 32) >> 4), kk != 0);
                wgmma_commit();
#pragma unroll
                for (int i = 0; i < 16; i++) {
                    O[4 * i] *= a0;
                    O[4 * i + 1] *= a0;
                    O[4 * i + 2] *= a1;
                    O[4 * i + 3] *= a1;
                }
                mbar_wait(smem_u32(&sm.full_v[vstage]), vphase);
                wgmma_fence();
#pragma unroll
                for (int kk = 0; kk < 8; kk++)
                    wgmma_rs_n128<1>(O, P[4 * kk], P[4 * kk + 1], P[4 * kk + 2], P[4 * kk + 3],
                                     dv + (uint64_t)((kk * 2048) >> 4), 1);
                wgmma_commit();
                named_arrive(BAR_SCHED0 + (cw ^ 1), 256);
                wgmma_wait<1>();
                if (lane == 0) mbar_arrive(smem_u32(&sm.empty_k[stage]));
                softmax();
                wgmma_wait<0>();
                if (lane == 0) mbar_arrive(smem_u32(&sm.empty_v[vstage]));
#pragma unroll
                for (int i = 0; i < 32; i++) P[i] = pack_bf16(S[2 * i], S[2 * i + 1]);
                vstage = stage;
                vphase = phase;
                if (++stage == AT_STAGES) { stage = 0; phase ^= 1; }
            }
            {
#pragma unroll
                for (int i = 0; i < 16; i++) {
                    O[4 * i] *= a0;
                    O[4 * i + 1] *= a0;
                    O[4 * i + 2] *= a1;
                    O[4 * i + 3] *= a1;
                }
                const uint64_t dv = make_desc(smem_u32(sm.v[vstage]), 16384, 1024);
                mbar_wait(smem_u32(&sm.full_v[vstage]), vphase);
                wgmma_fence();
#pragma unroll
                for (int kk = 0; kk < 8; kk++)
                    wgmma_rs_n128<1>(O, P[4 * kk], P[4 * kk + 1], P[4 * kk + 2], P[4 * kk + 3],
                                     dv + (uint64_t)((kk * 2048) >> 4), 1);
                wgmma_commit();
                wgmma_wait<0>();
                if (lane == 0) mbar_arrive(smem_u32(&sm.empty_v[vstage]));
            }
            l0 += __shfl_xor_sync(0xffffffffu, l0, 1);
            l1 += __shfl_xor_sync(0xffffffffu, l1, 1);
            l0 += __shfl_xor_sync(0xffffffffu, l0, 2);
            l1 += __shfl_xor_sync(0xffffffffu, l1, 2);
            const float i0 = 1.0f / l0, i1 = 1.0f / l1;
            const uint32_t obase = smem_u32(sm.o) + cw * 16384;
            if ((tid & 127) == 0) tma_wait_read0();
            named_sync(BAR_EPI0 + cw, 128);
            {
                const int row = warp_in_wg * 16 + ((lane >> 3) & 1) * 8 + (lane & 7);
#pragma unroll
                for (int i = 0; i < 16; i += 2) {
                    const int cc = i + (lane >> 4);
                    const uint32_t addr = obase + (cc >> 3) * 8192 + row * 128 + (((cc & 7) ^ (row & 7)) << 4);
                    stmatrix_x4(addr, pack_bf16(O[4 * i] * i0, O[4 * i + 1] * i0), pack_bf16(O[4 * i + 2] * i1, O[4 * i + 3] * i1),
                                pack_bf16(O[4 * i + 4] * i0, O[4 * i + 5] * i0), pack_bf16(O[4 * i + 6] * i1, O[4 * i + 7] * i1));
                }
            }
            fence_proxy_async();
            named_sync(BAR_EPI0 + cw, 128);
            if ((tid & 127) == 0) {
                tma_store_3d(&tm_o, obase, 0, qb * 128 + cw * 64, h * 2);
                tma_commit();
            }
        }
        if ((tid & 127) == 0) tma_wait_all0();
    }
}

constexpr int G_STAGES = 4;
struct __align__(1024) GemmSmem {
    uint8_t a[G_STAGES][128 * 64 * 2];
    uint8_t b[G_STAGES][64 * 128 * 2];
    uint64_t full[G_STAGES], empty[G_STAGES];
};

__device__ __forceinline__ void gemm_producer(GemmSmem& sm, const CUtensorMap* ta, const CUtensorMap* tb, int m0, int n0,
                                              int ktiles, int& stage, uint32_t& phase) {
    for (int kt = 0; kt < ktiles; kt++) {
        mbar_wait(smem_u32(&sm.empty[stage]), phase ^ 1);
        mbar_expect_tx(smem_u32(&sm.full[stage]), 32768);
        tma_load_3d(smem_u32(sm.a[stage]), ta, smem_u32(&sm.full[stage]), 0, m0, kt);
        tma_load_3d(smem_u32(sm.b[stage]), tb, smem_u32(&sm.full[stage]), 0, kt * 64, n0 >> 6);
        if (++stage == G_STAGES) { stage = 0; phase ^= 1; }
    }
}

__device__ __forceinline__ void gemm_consumer(GemmSmem& sm, float (&acc)[64], int cw, int lane, int ktiles, int& stage,
                                              uint32_t& phase) {
    int prev = -1;
#pragma unroll 1
    for (int kt = 0; kt < ktiles; kt++) {
        mbar_wait(smem_u32(&sm.full[stage]), phase);
        const uint64_t da = make_desc(smem_u32(sm.a[stage]) + cw * 64 * 128, 16, 1024);
        const uint64_t db = make_desc(smem_u32(sm.b[stage]), 8192, 1024);
        wgmma_fence();
#pragma unroll
        for (int kk = 0; kk < 4; kk++)
            wgmma_ss_n128<1>(acc, da + (uint64_t)((kk * 32) >> 4), db + (uint64_t)((kk * 2048) >> 4), (kt | kk) != 0);
        wgmma_commit();
        wgmma_wait<1>();
        if (prev >= 0 && lane == 0) mbar_arrive(smem_u32(&sm.empty[prev]));
        prev = stage;
        if (++stage == G_STAGES) { stage = 0; phase ^= 1; }
    }
    wgmma_wait<0>();
    if (lane == 0) mbar_arrive(smem_u32(&sm.empty[prev]));
}

__global__ void __launch_bounds__(384, 1)
ffn1_kernel(const __grid_constant__ CUtensorMap tm_a, const __grid_constant__ CUtensorMap tm_b) {
    extern __shared__ uint8_t smem_raw[];
    GemmSmem& sm = *reinterpret_cast<GemmSmem*>((reinterpret_cast<uintptr_t>(smem_raw) + 1023) & ~uintptr_t(1023));
    const int tid = threadIdx.x, wg = tid >> 7;
    const int m0 = blockIdx.y * 128, n0 = blockIdx.x * 128;
    if (tid == 0) {
        for (int s = 0; s < G_STAGES; s++) {
            mbar_init(smem_u32(&sm.full[s]), 1);
            mbar_init(smem_u32(&sm.empty[s]), 8);
        }
        asm volatile("fence.mbarrier_init.release.cluster;" ::: "memory");
    }
    __syncthreads();
    int stage = 0;
    uint32_t phase = 0;
    if (wg == 0) {
        if (tid == 0) gemm_producer(sm, &tm_a, &tm_b, m0, n0, DM / 64, stage, phase);
    } else {
        const int cw = wg - 1, lane = tid & 31, warp_in_wg = (tid >> 5) & 3;
        float acc[64];
        gemm_consumer(sm, acc, cw, lane, DM / 64, stage, phase);
        const int r0 = m0 + cw * 64 + warp_in_wg * 16 + (lane >> 2);
#pragma unroll
        for (int i = 0; i < 16; i++) {
            const int col = n0 + i * 8 + (lane & 3) * 2;
            float v0 = silu_f(bf16_round(acc[4 * i])), v1 = silu_f(bf16_round(acc[4 * i + 1]));
            float v2 = silu_f(bf16_round(acc[4 * i + 2])), v3 = silu_f(bf16_round(acc[4 * i + 3]));
            *reinterpret_cast<uint32_t*>(g_h + (size_t)r0 * FF + col) = pack_bf16(v0, v1);
            *reinterpret_cast<uint32_t*>(g_h + (size_t)(r0 + 8) * FF + col) = pack_bf16(v2, v3);
        }
    }
}

__global__ void __launch_bounds__(384, 1)
final_kernel(const __grid_constant__ CUtensorMap tm_o, const __grid_constant__ CUtensorMap tm_wo,
             const __grid_constant__ CUtensorMap tm_h, const __grid_constant__ CUtensorMap tm_w2,
             const bf16* __restrict__ x, bf16* __restrict__ out) {
    extern __shared__ uint8_t smem_raw[];
    GemmSmem& sm = *reinterpret_cast<GemmSmem*>((reinterpret_cast<uintptr_t>(smem_raw) + 1023) & ~uintptr_t(1023));
    const int tid = threadIdx.x, wg = tid >> 7;
    const int m0 = blockIdx.y * 128, n0 = blockIdx.x * 128;
    if (tid == 0) {
        for (int s = 0; s < G_STAGES; s++) {
            mbar_init(smem_u32(&sm.full[s]), 1);
            mbar_init(smem_u32(&sm.empty[s]), 8);
        }
        asm volatile("fence.mbarrier_init.release.cluster;" ::: "memory");
    }
    __syncthreads();
    int stage = 0;
    uint32_t phase = 0;
    if (wg == 0) {
        if (tid == 0) {
            gemm_producer(sm, &tm_h, &tm_w2, m0, n0, FF / 64, stage, phase);
            gemm_producer(sm, &tm_o, &tm_wo, m0, n0, NH * DH / 64, stage, phase);
        }
    } else {
        const int cw = wg - 1, lane = tid & 31, warp_in_wg = (tid >> 5) & 3;
        float accf[64], accs[64];
        gemm_consumer(sm, accf, cw, lane, FF / 64, stage, phase);
        gemm_consumer(sm, accs, cw, lane, NH * DH / 64, stage, phase);
        const int r0 = m0 + cw * 64 + warp_in_wg * 16 + (lane >> 2);
#pragma unroll
        for (int i = 0; i < 16; i++) {
            const int col = n0 + i * 8 + (lane & 3) * 2;
#pragma unroll
            for (int hh = 0; hh < 2; hh++) {
                const int r = r0 + hh * 8;
                const __nv_bfloat162 xv = *reinterpret_cast<const __nv_bfloat162*>(x + (size_t)r * DM + col);
                float g0 = bf16_round(silu_f(bf16_round(accf[4 * i + 2 * hh])));
                float g1 = bf16_round(silu_f(bf16_round(accf[4 * i + 2 * hh + 1])));
                float s0 = bf16_round(accs[4 * i + 2 * hh]), s1 = bf16_round(accs[4 * i + 2 * hh + 1]);
                float o0 = __bfloat162float(xv.x) + bf16_round(s0 * g0);
                float o1 = __bfloat162float(xv.y) + bf16_round(s1 * g1);
                *reinterpret_cast<uint32_t*>(out + (size_t)r * DM + col) = pack_bf16(o0, o1);
            }
        }
    }
}

typedef CUresult (*EncodeFn)(CUtensorMap*, CUtensorMapDataType, cuuint32_t, void*, const cuuint64_t*, const cuuint64_t*,
                             const cuuint32_t*, const cuuint32_t*, CUtensorMapInterleave, CUtensorMapSwizzle,
                             CUtensorMapL2promotion, CUtensorMapFloatOOBfill);

static CUtensorMap make_map(EncodeFn fn, const void* ptr, uint64_t rows, uint64_t cols, uint32_t box_rows, uint32_t box_blk) {
    CUtensorMap m;
    cuuint64_t dims[3] = {64, rows, cols / 64};
    cuuint64_t strides[2] = {cols * 2, 128};
    cuuint32_t box[3] = {64, box_rows, box_blk};
    cuuint32_t es[3] = {1, 1, 1};
    fn(&m, CU_TENSOR_MAP_DATA_TYPE_BFLOAT16, 3, const_cast<void*>(ptr), dims, strides, box, es, CU_TENSOR_MAP_INTERLEAVE_NONE,
       CU_TENSOR_MAP_SWIZZLE_128B, CU_TENSOR_MAP_L2_PROMOTION_L2_256B, CU_TENSOR_MAP_FLOAT_OOB_FILL_NONE);
    return m;
}

extern "C" void kernel_launch(void* const* d_in, const int* in_sizes, int n_in, void* d_out, int out_size) {
    const bf16* x = (const bf16*)d_in[0];
    const bf16* kc = (const bf16*)d_in[1];
    const bf16* vc = (const bf16*)d_in[2];
    const bf16* wq = (const bf16*)d_in[3];
    const bf16* wo = (const bf16*)d_in[4];
    const bf16* w1 = (const bf16*)d_in[6];
    const bf16* w2 = (const bf16*)d_in[7];
    bf16* out = (bf16*)d_out;

    static EncodeFn fn = nullptr;
    static void *p_xn = nullptr, *p_h = nullptr, *p_o = nullptr;
    if (!fn) {
        void* f = nullptr;
        cudaDriverEntryPointQueryResult st;
        cudaGetDriverEntryPoint("cuTensorMapEncodeTiled", &f, cudaEnableDefault, &st);
        fn = (EncodeFn)f;
        cudaGetSymbolAddress(&p_xn, g_xn);
        cudaGetSymbolAddress(&p_h, g_h);
        cudaGetSymbolAddress(&p_o, g_o);
        cudaFuncSetAttribute(attn_kernel, cudaFuncAttributeMaxDynamicSharedMemorySize, (int)sizeof(AttnSmem) + 1024);
        cudaFuncSetAttribute(ffn1_kernel, cudaFuncAttributeMaxDynamicSharedMemorySize, (int)sizeof(GemmSmem) + 1024);
        cudaFuncSetAttribute(final_kernel, cudaFuncAttributeMaxDynamicSharedMemorySize, (int)sizeof(GemmSmem) + 1024);
    }
    CUtensorMap tm_xn_at = make_map(fn, p_xn, SEQ, DM, 128, 2);
    CUtensorMap tm_wq = make_map(fn, wq, DM, NH * DH, 128, 2);
    CUtensorMap tm_k = make_map(fn, kc, NH * SEQ, DH, 128, 2);
    CUtensorMap tm_v = make_map(fn, vc, NH * SEQ, DH, 128, 2);
    CUtensorMap tm_o_st = make_map(fn, p_o, SEQ, NH * DH, 64, 2);
    CUtensorMap tm_xn_g = make_map(fn, p_xn, SEQ, DM, 128, 1);
    CUtensorMap tm_w1 = make_map(fn, w1, DM, FF, 64, 2);
    CUtensorMap tm_o_g = make_map(fn, p_o, SEQ, NH * DH, 128, 1);
    CUtensorMap tm_wo = make_map(fn, wo, NH * DH, DM, 64, 2);
    CUtensorMap tm_h_g = make_map(fn, p_h, SEQ, FF, 128, 1);
    CUtensorMap tm_w2 = make_map(fn, w2, FF, DM, 64, 2);

    ln_kernel<<<SEQ / 8, 256>>>(x);
    ffn1_kernel<<<dim3(FF / 128, SEQ / 128), 384, sizeof(GemmSmem) + 1024>>>(tm_xn_g, tm_w1);
    attn_kernel<<<132, 384, sizeof(AttnSmem) + 1024>>>(tm_xn_at, tm_wq, tm_k, tm_v, tm_o_st);
    final_kernel<<<dim3(DM / 128, SEQ / 128), 384, sizeof(GemmSmem) + 1024>>>(tm_o_g, tm_wo, tm_h_g, tm_w2, x, out);
}
```

```cpp
#include <cuda_runtime.h>
#include <cuda_bf16.h>
#include <cuda.h>
#include <stdint.h>

typedef __nv_bfloat16 bf16;

constexpr int SEQ = 2048, DM = 512, NH = 32, DH = 128, FF = 1792;

__device__ __align__(1024) bf16 g_xn[SEQ * DM];
__device__ __align__(1024) bf16 g_h[SEQ * FF];
__device__ __align__(1024) bf16 g_o[SEQ * NH * DH];
__device__ volatile float g_dummy;

__device__ __forceinline__ uint32_t smem_u32(const void* p) { return (uint32_t)__cvta_generic_to_shared(p); }

__device__ __forceinline__ void mbar_init(uint32_t bar, uint32_t count) {
    asm volatile("mbarrier.init.shared::cta.b64 [%0], %1;" ::"r"(bar), "r"(count) : "memory");
}
__device__ __forceinline__ void mbar_expect_tx(uint32_t bar, uint32_t bytes) {
    asm volatile("mbarrier.arrive.expect_tx.shared::cta.b64 _, [%0], %1;" ::"r"(bar), "r"(bytes) : "memory");
}
__device__ __forceinline__ void mbar_arrive(uint32_t bar) {
    asm volatile("mbarrier.arrive.shared::cta.b64 _, [%0];" ::"r"(bar) : "memory");
}
__device__ __forceinline__ bool mbar_try_wait(uint32_t bar, uint32_t parity) {
    uint32_t ok;
    asm volatile(
        "{\n.reg .pred p;\n"
        "mbarrier.try_wait.parity.shared::cta.b64 p, [%1], %2;\n"
        "selp.u32 %0, 1, 0, p;\n}\n"
        : "=r"(ok)
        : "r"(bar), "r"(parity)
        : "memory");
    return ok != 0;
}
__device__ __forceinline__ void mbar_wait(uint32_t bar, uint32_t parity) {
    asm volatile(
        "{\n.reg .pred P1;\n.reg .u32 n;\nmov.u32 n, 0;\n"
        "LAB_WAIT:\n"
        "mbarrier.try_wait.parity.shared::cta.b64 P1, [%0], %1;\n"
        "@P1 bra DONE;\n"
        "add.u32 n, n, 1;\n"
        "setp.lt.u32 P1, n, 4194304;\n"
        "@P1 bra LAB_WAIT;\n"
        "trap;\n"
        "DONE:\n}\n" ::"r"(bar), "r"(parity)
        : "memory");
}
__device__ __forceinline__ void tma_load_3d(uint32_t dst, const CUtensorMap* map, uint32_t bar, int c0, int c1, int c2) {
    asm volatile(
        "cp.async.bulk.tensor.3d.shared::cluster.global.mbarrier::complete_tx::bytes [%0], [%1, {%3, %4, %5}], [%2];"
        ::"r"(dst), "l"((uint64_t)map), "r"(bar), "r"(c0), "r"(c1), "r"(c2)
        : "memory");
}
__device__ __forceinline__ void tma_store_3d(const CUtensorMap* map, uint32_t src, int c0, int c1, int c2) {
    asm volatile("cp.async.bulk.tensor.3d.global.shared::cta.bulk_group [%0, {%2, %3, %4}], [%1];"
                 ::"l"((uint64_t)map), "r"(src), "r"(c0), "r"(c1), "r"(c2)
                 : "memory");
}
__device__ __forceinline__ void tma_commit() { asm volatile("cp.async.bulk.commit_group;" ::: "memory"); }
__device__ __forceinline__ void tma_wait_read0() { asm volatile("cp.async.bulk.wait_group.read 0;" ::: "memory"); }
__device__ __forceinline__ void tma_wait_all0() { asm volatile("cp.async.bulk.wait_group 0;" ::: "memory"); }
__device__ __forceinline__ void fence_proxy_async() { asm volatile("fence.proxy.async.shared::cta;" ::: "memory"); }
__device__ __forceinline__ void prefetch_tmap(const CUtensorMap* map) {
    asm volatile("prefetch.tensormap [%0];" ::"l"((uint64_t)map) : "memory");
}
__device__ __forceinline__ void named_sync(int id, int n) { asm volatile("bar.sync %0, %1;" ::"r"(id), "r"(n) : "memory"); }
__device__ __forceinline__ void named_arrive(int id, int n) { asm volatile("bar.arrive %0, %1;" ::"r"(id), "r"(n) : "memory"); }

__device__ __forceinline__ void wgmma_fence() { asm volatile("wgmma.fence.sync.aligned;" ::: "memory"); }
__device__ __forceinline__ void wgmma_commit() { asm volatile("wgmma.commit_group.sync.aligned;" ::: "memory"); }
template <int N>
__device__ __forceinline__ void wgmma_wait() { asm volatile("wgmma.wait_group.sync.aligned %0;" ::"n"(N) : "memory"); }

template <int R>
__device__ __forceinline__ void reg_alloc() { asm volatile("setmaxnreg.inc.sync.aligned.u32 %0;" ::"n"(R)); }
template <int R>
__device__ __forceinline__ void reg_dealloc() { asm volatile("setmaxnreg.dec.sync.aligned.u32 %0;" ::"n"(R)); }

__device__ __forceinline__ uint64_t make_desc(uint32_t saddr, uint32_t lbo_bytes, uint32_t sbo_bytes) {
    uint64_t d = 0;
    d |= (uint64_t)((saddr & 0x3FFFF) >> 4);
    d |= (uint64_t)((lbo_bytes >> 4) & 0x3FFF) << 16;
    d |= (uint64_t)((sbo_bytes >> 4) & 0x3FFF) << 32;
    d |= (uint64_t)1 << 62;
    return d;
}

__device__ __forceinline__ float ex2(float x) {
    float y;
    asm volatile("ex2.approx.ftz.f32 %0, %1;" : "=f"(y) : "f"(x));
    return y;
}
__device__ __forceinline__ uint32_t pack_bf16(float lo, float hi) {
    uint32_t r;
    asm("cvt.rn.bf16x2.f32 %0, %1, %2;" : "=r"(r) : "f"(hi), "f"(lo));
    return r;
}
__device__ __forceinline__ uint32_t mul_bf16x2(uint32_t a, uint32_t b) {
    uint32_t r;
    asm("mul.rn.bf16x2 %0, %1, %2;" : "=r"(r) : "r"(a), "r"(b));
    return r;
}
__device__ __forceinline__ uint32_t fma_bf16x2(uint32_t a, uint32_t b, uint32_t c) {
    uint32_t r;
    asm("fma.rn.bf16x2 %0, %1, %2, %3;" : "=r"(r) : "r"(a), "r"(b), "r"(c));
    return r;
}
__device__ __forceinline__ uint32_t max_bf16x2(uint32_t a, uint32_t b) {
    uint32_t r;
    asm("max.bf16x2 %0, %1, %2;" : "=r"(r) : "r"(a), "r"(b));
    return r;
}
__device__ __forceinline__ float bf16lo(uint32_t v) { return __uint_as_float(v << 16); }
__device__ __forceinline__ float bf16hi(uint32_t v) { return __uint_as_float(v & 0xffff0000u); }
__device__ __forceinline__ float bf16_round(float x) { return __bfloat162float(__float2bfloat16_rn(x)); }
__device__ __forceinline__ float silu_f(float x) { return x / (1.0f + __expf(-x)); }

__device__ __forceinline__ void stmatrix_x4(uint32_t addr, uint32_t r0, uint32_t r1, uint32_t r2, uint32_t r3) {
    asm volatile("stmatrix.sync.aligned.m8n8.x4.shared.b16 [%0], {%1, %2, %3, %4};"
                 ::"r"(addr), "r"(r0), "r"(r1), "r"(r2), "r"(r3)
                 : "memory");
}

#define ACC64(d) \
    "+f"(d[0]), "+f"(d[1]), "+f"(d[2]), "+f"(d[3]), "+f"(d[4]), "+f"(d[5]), "+f"(d[6]), "+f"(d[7]), \
    "+f"(d[8]), "+f"(d[9]), "+f"(d[10]), "+f"(d[11]), "+f"(d[12]), "+f"(d[13]), "+f"(d[14]), "+f"(d[15]), \
    "+f"(d[16]), "+f"(d[17]), "+f"(d[18]), "+f"(d[19]), "+f"(d[20]), "+f"(d[21]), "+f"(d[22]), "+f"(d[23]), \
    "+f"(d[24]), "+f"(d[25]), "+f"(d[26]), "+f"(d[27]), "+f"(d[28]), "+f"(d[29]), "+f"(d[30]), "+f"(d[31]), \
    "+f"(d[32]), "+f"(d[33]), "+f"(d[34]), "+f"(d[35]), "+f"(d[36]), "+f"(d[37]), "+f"(d[38]), "+f"(d[39]), \
    "+f"(d[40]), "+f"(d[41]), "+f"(d[42]), "+f"(d[43]), "+f"(d[44]), "+f"(d[45]), "+f"(d[46]), "+f"(d[47]), \
    "+f"(d[48]), "+f"(d[49]), "+f"(d[50]), "+f"(d[51]), "+f"(d[52]), "+f"(d[53]), "+f"(d[54]), "+f"(d[55]), \
    "+f"(d[56]), "+f"(d[57]), "+f"(d[58]), "+f"(d[59]), "+f"(d[60]), "+f"(d[61]), "+f"(d[62]), "+f"(d[63])

#define ACC64_STR \
    "{%0, %1, %2, %3, %4, %5, %6, %7, %8, %9, %10, %11, %12, %13, %14, %15, " \
    "%16, %17, %18, %19, %20, %21, %22, %23, %24, %25, %26, %27, %28, %29, %30, %31, " \
    "%32, %33, %34, %35, %36, %37, %38, %39, %40, %41, %42, %43, %44, %45, %46, %47, " \
    "%48, %49, %50, %51, %52, %53, %54, %55, %56, %57, %58, %59, %60, %61, %62, %63}"

template <int TB>
__device__ __forceinline__ void wgmma_ss_n128(float (&d)[64], uint64_t da, uint64_t db, int scale_d) {
    asm volatile(
        "{\n.reg .pred p;\nsetp.ne.b32 p, %66, 0;\n"
        "wgmma.mma_async.sync.aligned.m64n128k16.f32.bf16.bf16 " ACC64_STR ", %64, %65, p, 1, 1, 0, %67;\n}\n"
        : ACC64(d)
        : "l"(da), "l"(db), "r"(scale_d), "n"(TB));
}
template <int TB>
__device__ __forceinline__ void wgmma_rs_n128(float (&d)[64], uint32_t a0, uint32_t a1, uint32_t a2, uint32_t a3,
                                              uint64_t db, int scale_d) {
    asm volatile(
        "{\n.reg .pred p;\nsetp.ne.b32 p, %69, 0;\n"
        "wgmma.mma_async.sync.aligned.m64n128k16.f32.bf16.bf16 " ACC64_STR ", {%64, %65, %66, %67}, %68, p, 1, 1, %70;\n}\n"
        : ACC64(d)
        : "r"(a0), "r"(a1), "r"(a2), "r"(a3), "l"(db), "r"(scale_d), "n"(TB));
}

__global__ void __launch_bounds__(256) ln_kernel(const bf16* __restrict__ x) {
    int warp = threadIdx.x >> 5, lane = threadIdx.x & 31;
    int row = blockIdx.x * 8 + warp;
    const uint4* src = reinterpret_cast<const uint4*>(x + (size_t)row * DM);
    uint4 v[2];
    v[0] = src[lane];
    v[1] = src[lane + 32];
    float f[16];
#pragma unroll
    for (int i = 0; i < 2; i++) {
        const __nv_bfloat162* p = reinterpret_cast<const __nv_bfloat162*>(&v[i]);
#pragma unroll
        for (int j = 0; j < 4; j++) {
            float2 t = __bfloat1622float2(p[j]);
            f[i * 8 + j * 2] = t.x;
            f[i * 8 + j * 2 + 1] = t.y;
        }
    }
    float s = 0.f;
#pragma unroll
    for (int i = 0; i < 16; i++) s += f[i];
#pragma unroll
    for (int o = 16; o > 0; o >>= 1) s += __shfl_xor_sync(0xffffffffu, s, o);
    float mean = s * (1.0f / DM);
    float q = 0.f;
#pragma unroll
    for (int i = 0; i < 16; i++) {
        float d = f[i] - mean;
        q += d * d;
    }
#pragma unroll
    for (int o = 16; o > 0; o >>= 1) q += __shfl_xor_sync(0xffffffffu, q, o);
    float var_b = bf16_round(q * (1.0f / DM));
    float mean_b = bf16_round(mean);
    float den = bf16_round(sqrtf(bf16_round(var_b + 1e-5f)));
    uint4 o[2];
#pragma unroll
    for (int i = 0; i < 2; i++) {
        uint32_t* p = reinterpret_cast<uint32_t*>(&o[i]);
#pragma unroll
        for (int j = 0; j < 4; j++) {
            float a = bf16_round(f[i * 8 + j * 2] - mean_b) / den;
            float b = bf16_round(f[i * 8 + j * 2 + 1] - mean_b) / den;
            p[j] = pack_bf16(a, b);
        }
    }
    uint4* dst = reinterpret_cast<uint4*>(g_xn + (size_t)row * DM);
    dst[lane] = o[0];
    dst[lane + 32] = o[1];
}

constexpr int AT_STAGES = 2;
constexpr int TILE_BYTES = 128 * 128 * 2;
struct __align__(1024) AttnSmem {
    uint8_t k[AT_STAGES][TILE_BYTES];
    uint8_t v[AT_STAGES][TILE_BYTES];
    uint8_t o[TILE_BYTES];
    uint64_t full_k[AT_STAGES], full_v[AT_STAGES], empty_k[AT_STAGES], empty_v[AT_STAGES];
};

constexpr int NUM_AT_TILES = NH * (SEQ / 128);

__global__ void __launch_bounds__(384, 1)
attn_kernel(const __grid_constant__ CUtensorMap tm_xn, const __grid_constant__ CUtensorMap tm_wq,
            const __grid_constant__ CUtensorMap tm_k, const __grid_constant__ CUtensorMap tm_v,
            const __grid_constant__ CUtensorMap tm_o) {
    extern __shared__ uint8_t smem_raw[];
    AttnSmem& sm = *reinterpret_cast<AttnSmem*>((reinterpret_cast<uintptr_t>(smem_raw) + 1023) & ~uintptr_t(1023));
    const int tid = threadIdx.x;
    const int wg = tid >> 7;

    if (tid == 0) {
#pragma unroll
        for (int s = 0; s < AT_STAGES; s++) {
            mbar_init(smem_u32(&sm.full_k[s]), 1);
            mbar_init(smem_u32(&sm.full_v[s]), 1);
            mbar_init(smem_u32(&sm.empty_k[s]), 8);
            mbar_init(smem_u32(&sm.empty_v[s]), 8);
        }
        asm volatile("fence.mbarrier_init.release.cluster;" ::: "memory");
    }
    __syncthreads();

    if (wg == 0) {
        reg_dealloc<24>();
        if (tid == 0) {
            prefetch_tmap(&tm_xn);
            prefetch_tmap(&tm_wq);
            prefetch_tmap(&tm_k);
            prefetch_tmap(&tm_v);
            int stage = 0;
            uint32_t phase = 0;
            for (int tile = blockIdx.x; tile < NUM_AT_TILES; tile += gridDim.x) {
                const int h = tile >> 4, qb = tile & 15;
                for (int kc = 0; kc < 4; kc++) {
                    mbar_wait(smem_u32(&sm.empty_k[stage]), phase ^ 1);
                    mbar_expect_tx(smem_u32(&sm.full_k[stage]), TILE_BYTES);
                    tma_load_3d(smem_u32(sm.k[stage]), &tm_xn, smem_u32(&sm.full_k[stage]), 0, qb * 128, kc * 2);
                    mbar_wait(smem_u32(&sm.empty_v[stage]), phase ^ 1);
                    mbar_expect_tx(smem_u32(&sm.full_v[stage]), TILE_BYTES);
                    tma_load_3d(smem_u32(sm.v[stage]), &tm_wq, smem_u32(&sm.full_v[stage]), 0, kc * 128, h * 2);
                    if (++stage == AT_STAGES) { stage = 0; phase ^= 1; }
                }
                for (int j = 0; j < 16; j++) {
                    mbar_wait(smem_u32(&sm.empty_k[stage]), phase ^ 1);
                    mbar_expect_tx(smem_u32(&sm.full_k[stage]), TILE_BYTES);
                    tma_load_3d(smem_u32(sm.k[stage]), &tm_k, smem_u32(&sm.full_k[stage]), 0, h * SEQ + j * 128, 0);
                    mbar_wait(smem_u32(&sm.empty_v[stage]), phase ^ 1);
                    mbar_expect_tx(smem_u32(&sm.full_v[stage]), TILE_BYTES);
                    tma_load_3d(smem_u32(sm.v[stage]), &tm_v, smem_u32(&sm.full_v[stage]), 0, h * SEQ + j * 128, 0);
                    if (++stage == AT_STAGES) { stage = 0; phase ^= 1; }
                }
            }
        }
    } else {
        reg_alloc<240>();
        const int cw = wg - 1;
        const int lane = tid & 31;
        const int warp_in_wg = (tid >> 5) & 3;
        const float c = 1.4426950408889634f;
        const uint32_t SCALE_HI2 = 0x3DB53DB5u, SCALE_LO2 = 0x371E371Eu;
        constexpr int BAR_SCHED0 = 1, BAR_EPI0 = 3;

        if (cw == 1) named_arrive(BAR_SCHED0 + 0, 256);

        int stage = 0;
        uint32_t phase = 0;
        float S[64], O[64];
        uint32_t P[32];

        for (int tile = blockIdx.x; tile < NUM_AT_TILES; tile += gridDim.x) {
            const int h = tile >> 4, qb = tile & 15;
#pragma unroll 1
            for (int kc = 0; kc < 4; kc++) {
                mbar_wait(smem_u32(&sm.full_k[stage]), phase);
                mbar_wait(smem_u32(&sm.full_v[stage]), phase);
                const uint64_t da = make_desc(smem_u32(sm.k[stage]) + cw * 64 * 128, 16, 1024);
                const uint64_t db = make_desc(smem_u32(sm.v[stage]), 16384, 1024);
                wgmma_fence();
#pragma unroll
                for (int kk = 0; kk < 8; kk++) {
                    wgmma_ss_n128<1>(S, da + (uint64_t)(((kk >> 2) * 16384 + (kk & 3) * 32) >> 4),
                                     db + (uint64_t)((kk * 2048) >> 4), (kc | kk) != 0);
                }
                wgmma_commit();
                wgmma_wait<0>();
                if (lane == 0) {
                    mbar_arrive(smem_u32(&sm.empty_k[stage]));
                    mbar_arrive(smem_u32(&sm.empty_v[stage]));
                }
                if (++stage == AT_STAGES) { stage = 0; phase ^= 1; }
            }
            const uint32_t obase = smem_u32(sm.o) + cw * 16384;
            if ((tid & 127) == 0) tma_wait_read0();
            named_sync(BAR_EPI0 + cw, 128);
            {
                const int row = warp_in_wg * 16 + ((lane >> 3) & 1) * 8 + (lane & 7);
#pragma unroll
                for (int i = 0; i < 16; i += 2) {
                    const int cc = i + (lane >> 4);
                    const uint32_t addr = obase + (cc >> 3) * 8192 + row * 128 + (((cc & 7) ^ (row & 7)) << 4);
                    stmatrix_x4(addr, pack_bf16(S[4 * i], S[4 * i + 1]), pack_bf16(S[4 * i + 2], S[4 * i + 3]),
                                pack_bf16(S[4 * i + 4], S[4 * i + 5]), pack_bf16(S[4 * i + 6], S[4 * i + 7]));
                }
            }
            fence_proxy_async();
            named_sync(BAR_EPI0 + cw, 128);
            const uint64_t dq = make_desc(obase, 16, 1024);
#pragma unroll
            for (int i = 0; i < 64; i++) O[i] = 0.f;

            float m0 = -INFINITY, m1 = -INFINITY, l0 = 0.f, l1 = 0.f, a0 = 0.f, a1 = 0.f;

            {
                mbar_wait(smem_u32(&sm.full_k[stage]), phase);
                const uint64_t dk = make_desc(smem_u32(sm.k[stage]), 16, 1024);
                named_sync(BAR_SCHED0 + cw, 256);
                wgmma_fence();
#pragma unroll
                for (int kk = 0; kk < 8; kk++)
                    wgmma_ss_n128<0>(S, dq + (uint64_t)(((kk >> 2) * 8192 + (kk & 3) * 32) >> 4),
                                     dk + (uint64_t)(((kk >> 2) * 16384 + (kk & 3) * 32) >> 4), kk != 0);
                wgmma_commit();
                named_arrive(BAR_SCHED0 + (cw ^ 1), 256);
                wgmma_wait<0>();
                if (lane == 0) mbar_arrive(smem_u32(&sm.empty_k[stage]));
            }
            int vstage = stage;
            uint32_t vphase = phase;
            if (++stage == AT_STAGES) { stage = 0; phase ^= 1; }

            auto softmax = [&]() {
                uint32_t T[32];
#pragma unroll
                for (int i = 0; i < 32; i++) {
                    const uint32_t sb = pack_bf16(S[2 * i], S[2 * i + 1]);
                    T[i] = fma_bf16x2(sb, SCALE_HI2, mul_bf16x2(sb, SCALE_LO2));
                }
                uint32_t y0 = max_bf16x2(T[0], T[2]), y1 = max_bf16x2(T[1], T[3]);
#pragma unroll
                for (int i = 2; i < 16; i++) {
                    y0 = max_bf16x2(y0, T[2 * i]);
                    y1 = max_bf16x2(y1, T[2 * i + 1]);
                }
                float x0 = fmaxf(m0, fmaxf(bf16lo(y0), bf16hi(y0)));
                float x1 = fmaxf(m1, fmaxf(bf16lo(y1), bf16hi(y1)));
                x0 = fmaxf(x0, __shfl_xor_sync(0xffffffffu, x0, 1));
                x1 = fmaxf(x1, __shfl_xor_sync(0xffffffffu, x1, 1));
                x0 = fmaxf(x0, __shfl_xor_sync(0xffffffffu, x0, 2));
                x1 = fmaxf(x1, __shfl_xor_sync(0xffffffffu, x1, 2));
                a0 = ex2((m0 - x0) * c);
                a1 = ex2((m1 - x1) * c);
                m0 = x0;
                m1 = x1;
                const float n0 = -x0 * c, n1 = -x1 * c;
                float s0 = 0.f, s1 = 0.f;
#pragma unroll
                for (int i = 0; i < 16; i++) {
                    S[4 * i] = ex2(fmaf(bf16lo(T[2 * i]), c, n0));
                    S[4 * i + 1] = ex2(fmaf(bf16hi(T[2 * i]), c, n0));
                    S[4 * i + 2] = ex2(fmaf(bf16lo(T[2 * i + 1]), c, n1));
                    S[4 * i + 3] = ex2(fmaf(bf16hi(T[2 * i + 1]), c, n1));
                    s0 += S[4 * i] + S[4 * i + 1];
                    s1 += S[4 * i + 2] + S[4 * i + 3];
                }
                l0 = l0 * a0 + s0;
                l1 = l1 * a1 + s1;
                while (s0 + s1 < 0.f) s0 = g_dummy;
            };
            softmax();
#pragma unroll
            for (int i = 0; i < 32; i++) P[i] = pack_bf16(S[2 * i], S[2 * i + 1]);

#pragma unroll 1
            for (int j = 1; j < 16; j++) {
                mbar_wait(smem_u32(&sm.full_k[stage]), phase);
                const uint64_t dk = make_desc(smem_u32(sm.k[stage]), 16, 1024);
                const uint64_t dv = make_desc(smem_u32(sm.v[vstage]), 16384, 1024);
                named_sync(BAR_SCHED0 + cw, 256);
                wgmma_fence();
#pragma unroll
                for (int kk = 0; kk < 8; kk++)
                    wgmma_ss_n128<0>(S, dq + (uint64_t)(((kk >> 2) * 8192 + (kk & 3) * 32) >> 4),
                                     dk + (uint64_t)(((kk >> 2) * 16384 + (kk & 3) * 32) >> 4), kk != 0);
                wgmma_commit();
#pragma unroll
                for (int i = 0; i < 16; i++) {
                    O[4 * i] *= a0;
                    O[4 * i + 1] *= a0;
                    O[4 * i + 2] *= a1;
                    O[4 * i + 3] *= a1;
                }
                mbar_wait(smem_u32(&sm.full_v[vstage]), vphase);
                wgmma_fence();
#pragma unroll
                for (int kk = 0; kk < 8; kk++)
                    wgmma_rs_n128<1>(O, P[4 * kk], P[4 * kk + 1], P[4 * kk + 2], P[4 * kk + 3],
                                     dv + (uint64_t)((kk * 2048) >> 4), 1);
                wgmma_commit();
                named_arrive(BAR_SCHED0 + (cw ^ 1), 256);
                wgmma_wait<1>();
                if (lane == 0) mbar_arrive(smem_u32(&sm.empty_k[stage]));
                softmax();
                wgmma_wait<0>();
                if (lane == 0) mbar_arrive(smem_u32(&sm.empty_v[vstage]));
#pragma unroll
                for (int i = 0; i < 32; i++) P[i] = pack_bf16(S[2 * i], S[2 * i + 1]);
                vstage = stage;
                vphase = phase;
                if (++stage == AT_STAGES) { stage = 0; phase ^= 1; }
            }
            {
#pragma unroll
                for (int i = 0; i < 16; i++) {
                    O[4 * i] *= a0;
                    O[4 * i + 1] *= a0;
                    O[4 * i + 2] *= a1;
                    O[4 * i + 3] *= a1;
                }
                const uint64_t dv = make_desc(smem_u32(sm.v[vstage]), 16384, 1024);
                mbar_wait(smem_u32(&sm.full_v[vstage]), vphase);
                wgmma_fence();
#pragma unroll
                for (int kk = 0; kk < 8; kk++)
                    wgmma_rs_n128<1>(O, P[4 * kk], P[4 * kk + 1], P[4 * kk + 2], P[4 * kk + 3],
                                     dv + (uint64_t)((kk * 2048) >> 4), 1);
                wgmma_commit();
                wgmma_wait<0>();
                if (lane == 0) mbar_arrive(smem_u32(&sm.empty_v[vstage]));
            }
            l0 += __shfl_xor_sync(0xffffffffu, l0, 1);
            l1 += __shfl_xor_sync(0xffffffffu, l1, 1);
            l0 += __shfl_xor_sync(0xffffffffu, l0, 2);
            l1 += __shfl_xor_sync(0xffffffffu, l1, 2);
            const float i0 = 1.0f / l0, i1 = 1.0f / l1;
            named_sync(BAR_EPI0 + cw, 128);
            {
                const int row = warp_in_wg * 16 + ((lane >> 3) & 1) * 8 + (lane & 7);
#pragma unroll
                for (int i = 0; i < 16; i += 2) {
                    const int cc = i + (lane >> 4);
                    const uint32_t addr = obase + (cc >> 3) * 8192 + row * 128 + (((cc & 7) ^ (row & 7)) << 4);
                    stmatrix_x4(addr, pack_bf16(O[4 * i] * i0, O[4 * i + 1] * i0), pack_bf16(O[4 * i + 2] * i1, O[4 * i + 3] * i1),
                                pack_bf16(O[4 * i + 4] * i0, O[4 * i + 5] * i0), pack_bf16(O[4 * i + 6] * i1, O[4 * i + 7] * i1));
                }
            }
            fence_proxy_async();
            named_sync(BAR_EPI0 + cw, 128);
            if ((tid & 127) == 0) {
                tma_store_3d(&tm_o, obase, 0, qb * 128 + cw * 64, h * 2);
                tma_commit();
            }
        }
        if ((tid & 127) == 0) tma_wait_all0();
    }
}

constexpr int G_STAGES = 4;
struct __align__(1024) GemmSmem {
    uint8_t a[G_STAGES][128 * 64 * 2];
    uint8_t b[G_STAGES][64 * 128 * 2];
    uint64_t full[G_STAGES], empty[G_STAGES];
};

__device__ __forceinline__ void gemm_producer(GemmSmem& sm, const CUtensorMap* ta, const CUtensorMap* tb, int m0, int n0,
                                              int ktiles, int& stage, uint32_t& phase) {
    for (int kt = 0; kt < ktiles; kt++) {
        mbar_wait(smem_u32(&sm.empty[stage]), phase ^ 1);
        mbar_expect_tx(smem_u32(&sm.full[stage]), 32768);
        tma_load_3d(smem_u32(sm.a[stage]), ta, smem_u32(&sm.full[stage]), 0, m0, kt);
        tma_load_3d(smem_u32(sm.b[stage]), tb, smem_u32(&sm.full[stage]), 0, kt * 64, n0 >> 6);
        if (++stage == G_STAGES) { stage = 0; phase ^= 1; }
    }
}

__device__ __forceinline__ void gemm_consumer(GemmSmem& sm, float (&acc)[64], int cw, int lane, int ktiles, int& stage,
                                              uint32_t& phase) {
    int prev = -1;
#pragma unroll 1
    for (int kt = 0; kt < ktiles; kt++) {
        mbar_wait(smem_u32(&sm.full[stage]), phase);
        const uint64_t da = make_desc(smem_u32(sm.a[stage]) + cw * 64 * 128, 16, 1024);
        const uint64_t db = make_desc(smem_u32(sm.b[stage]), 8192, 1024);
        wgmma_fence();
#pragma unroll
        for (int kk = 0; kk < 4; kk++)
            wgmma_ss_n128<1>(acc, da + (uint64_t)((kk * 32) >> 4), db + (uint64_t)((kk * 2048) >> 4), (kt | kk) != 0);
        wgmma_commit();
        wgmma_wait<1>();
        if (prev >= 0 && lane == 0) mbar_arrive(smem_u32(&sm.empty[prev]));
        prev = stage;
        if (++stage == G_STAGES) { stage = 0; phase ^= 1; }
    }
    wgmma_wait<0>();
    if (lane == 0) mbar_arrive(smem_u32(&sm.empty[prev]));
}

__global__ void __launch_bounds__(384, 1)
ffn1_kernel(const __grid_constant__ CUtensorMap tm_a, const __grid_constant__ CUtensorMap tm_b) {
    extern __shared__ uint8_t smem_raw[];
    GemmSmem& sm = *reinterpret_cast<GemmSmem*>((reinterpret_cast<uintptr_t>(smem_raw) + 1023) & ~uintptr_t(1023));
    const int tid = threadIdx.x, wg = tid >> 7;
    const int m0 = blockIdx.y * 128, n0 = blockIdx.x * 128;
    if (tid == 0) {
        for (int s = 0; s < G_STAGES; s++) {
            mbar_init(smem_u32(&sm.full[s]), 1);
            mbar_init(smem_u32(&sm.empty[s]), 8);
        }
        asm volatile("fence.mbarrier_init.release.cluster;" ::: "memory");
    }
    __syncthreads();
    int stage = 0;
    uint32_t phase = 0;
    if (wg == 0) {
        if (tid == 0) gemm_producer(sm, &tm_a, &tm_b, m0, n0, DM / 64, stage, phase);
    } else {
        const int cw = wg - 1, lane = tid & 31, warp_in_wg = (tid >> 5) & 3;
        float acc[64];
        gemm_consumer(sm, acc, cw, lane, DM / 64, stage, phase);
        const int r0 = m0 + cw * 64 + warp_in_wg * 16 + (lane >> 2);
#pragma unroll
        for (int i = 0; i < 16; i++) {
            const int col = n0 + i * 8 + (lane & 3) * 2;
            float v0 = silu_f(bf16_round(acc[4 * i])), v1 = silu_f(bf16_round(acc[4 * i + 1]));
            float v2 = silu_f(bf16_round(acc[4 * i + 2])), v3 = silu_f(bf16_round(acc[4 * i + 3]));
            *reinterpret_cast<uint32_t*>(g_h + (size_t)r0 * FF + col) = pack_bf16(v0, v1);
            *reinterpret_cast<uint32_t*>(g_h + (size_t)(r0 + 8) * FF + col) = pack_bf16(v2, v3);
        }
    }
}

__global__ void __launch_bounds__(384, 1)
final_kernel(const __grid_constant__ CUtensorMap tm_o, const __grid_constant__ CUtensorMap tm_wo,
             const __grid_constant__ CUtensorMap tm_h, const __grid_constant__ CUtensorMap tm_w2,
             const bf16* __restrict__ x, bf16* __restrict__ out) {
    extern __shared__ uint8_t smem_raw[];
    GemmSmem& sm = *reinterpret_cast<GemmSmem*>((reinterpret_cast<uintptr_t>(smem_raw) + 1023) & ~uintptr_t(1023));
    const int tid = threadIdx.x, wg = tid >> 7;
    const int m0 = blockIdx.y * 128, n0 = blockIdx.x * 128;
    if (tid == 0) {
        for (int s = 0; s < G_STAGES; s++) {
            mbar_init(smem_u32(&sm.full[s]), 1);
            mbar_init(smem_u32(&sm.empty[s]), 8);
        }
        asm volatile("fence.mbarrier_init.release.cluster;" ::: "memory");
    }
    __syncthreads();
    int stage = 0;
    uint32_t phase = 0;
    if (wg == 0) {
        if (tid == 0) {
            gemm_producer(sm, &tm_h, &tm_w2, m0, n0, FF / 64, stage, phase);
            gemm_producer(sm, &tm_o, &tm_wo, m0, n0, NH * DH / 64, stage, phase);
        }
    } else {
        const int cw = wg - 1, lane = tid & 31, warp_in_wg = (tid >> 5) & 3;
        float accf[64], accs[64];
        gemm_consumer(sm, accf, cw, lane, FF / 64, stage, phase);
        gemm_consumer(sm, accs, cw, lane, NH * DH / 64, stage, phase);
        const int r0 = m0 + cw * 64 + warp_in_wg * 16 + (lane >> 2);
#pragma unroll
        for (int i = 0; i < 16; i++) {
            const int col = n0 + i * 8 + (lane & 3) * 2;
#pragma unroll
            for (int hh = 0; hh < 2; hh++) {
                const int r = r0 + hh * 8;
                const __nv_bfloat162 xv = *reinterpret_cast<const __nv_bfloat162*>(x + (size_t)r * DM + col);
                float g0 = bf16_round(silu_f(bf16_round(accf[4 * i + 2 * hh])));
                float g1 = bf16_round(silu_f(bf16_round(accf[4 * i + 2 * hh + 1])));
                float s0 = bf16_round(accs[4 * i + 2 * hh]), s1 = bf16_round(accs[4 * i + 2 * hh + 1]);
                float o0 = __bfloat162float(xv.x) + bf16_round(s0 * g0);
                float o1 = __bfloat162float(xv.y) + bf16_round(s1 * g1);
                *reinterpret_cast<uint32_t*>(out + (size_t)r * DM + col) = pack_bf16(o0, o1);
            }
        }
    }
}

typedef CUresult (*EncodeFn)(CUtensorMap*, CUtensorMapDataType, cuuint32_t, void*, const cuuint64_t*, const cuuint64_t*,
                             const cuuint32_t*, const cuuint32_t*, CUtensorMapInterleave, CUtensorMapSwizzle,
                             CUtensorMapL2promotion, CUtensorMapFloatOOBfill);

static CUtensorMap make_map(EncodeFn fn, const void* ptr, uint64_t rows, uint64_t cols, uint32_t box_rows, uint32_t box_blk) {
    CUtensorMap m;
    cuuint64_t dims[3] = {64, rows, cols / 64};
    cuuint64_t strides[2] = {cols * 2, 128};
    cuuint32_t box[3] = {64, box_rows, box_blk};
    cuuint32_t es[3] = {1, 1, 1};
    fn(&m, CU_TENSOR_MAP_DATA_TYPE_BFLOAT16, 3, const_cast<void*>(ptr), dims, strides, box, es, CU_TENSOR_MAP_INTERLEAVE_NONE,
       CU_TENSOR_MAP_SWIZZLE_128B, CU_TENSOR_MAP_L2_PROMOTION_L2_256B, CU_TENSOR_MAP_FLOAT_OOB_FILL_NONE);
    return m;
}

extern "C" void kernel_launch(void* const* d_in, const int* in_sizes, int n_in, void* d_out, int out_size) {
    const bf16* x = (const bf16*)d_in[0];
    const bf16* kc = (const bf16*)d_in[1];
    const bf16* vc = (const bf16*)d_in[2];
    const bf16* wq = (const bf16*)d_in[3];
    const bf16* wo = (const bf16*)d_in[4];
    const bf16* w1 = (const bf16*)d_in[6];
    const bf16* w2 = (const bf16*)d_in[7];
    bf16* out = (bf16*)d_out;

    static EncodeFn fn = nullptr;
    static void *p_xn = nullptr, *p_h = nullptr, *p_o = nullptr;
    if (!fn) {
        void* f = nullptr;
        cudaDriverEntryPointQueryResult st;
        cudaGetDriverEntryPoint("cuTensorMapEncodeTiled", &f, cudaEnableDefault, &st);
        fn = (EncodeFn)f;
        cudaGetSymbolAddress(&p_xn, g_xn);
        cudaGetSymbolAddress(&p_h, g_h);
        cudaGetSymbolAddress(&p_o, g_o);
        cudaFuncSetAttribute(attn_kernel, cudaFuncAttributeMaxDynamicSharedMemorySize, (int)sizeof(AttnSmem) + 1024);
        cudaFuncSetAttribute(ffn1_kernel, cudaFuncAttributeMaxDynamicSharedMemorySize, (int)sizeof(GemmSmem) + 1024);
        cudaFuncSetAttribute(final_kernel, cudaFuncAttributeMaxDynamicSharedMemorySize, (int)sizeof(GemmSmem) + 1024);
    }
    CUtensorMap tm_xn_at = make_map(fn, p_xn, SEQ, DM, 128, 2);
    CUtensorMap tm_wq = make_map(fn, wq, DM, NH * DH, 128, 2);
    CUtensorMap tm_k = make_map(fn, kc, NH * SEQ, DH, 128, 2);
    CUtensorMap tm_v = make_map(fn, vc, NH * SEQ, DH, 128, 2);
    CUtensorMap tm_o_st = make_map(fn, p_o, SEQ, NH * DH, 64, 2);
    CUtensorMap tm_xn_g = make_map(fn, p_xn, SEQ, DM, 128, 1);
    CUtensorMap tm_w1 = make_map(fn, w1, DM, FF, 64, 2);
    CUtensorMap tm_o_g = make_map(fn, p_o, SEQ, NH * DH, 128, 1);
    CUtensorMap tm_wo = make_map(fn, wo, NH * DH, DM, 64, 2);
    CUtensorMap tm_h_g = make_map(fn, p_h, SEQ, FF, 128, 1);
    CUtensorMap tm_w2 = make_map(fn, w2, FF, DM, 64, 2);

    ln_kernel<<<SEQ / 8, 256>>>(x);
    ffn1_kernel<<<dim3(FF / 128, SEQ / 128), 384, sizeof(GemmSmem) + 1024>>>(tm_xn_g, tm_w1);
    attn_kernel<<<132, 384, sizeof(AttnSmem) + 1024>>>(tm_xn_at, tm_wq, tm_k, tm_v, tm_o_st);
    final_kernel<<<dim3(DM / 128, SEQ / 128), 384, sizeof(GemmSmem) + 1024>>>(tm_o_g, tm_wo, tm_h_g, tm_w2, x, out);
}
```

```cpp
#include <cuda_runtime.h>
#include <cuda_bf16.h>
#include <cuda.h>
#include <stdint.h>

typedef __nv_bfloat16 bf16;

constexpr int SEQ = 2048, DM = 512, NH = 32, DH = 128, FF = 1792;

__device__ __align__(1024) bf16 g_xn[SEQ * DM];
__device__ __align__(1024) bf16 g_h[SEQ * FF];
__device__ __align__(1024) bf16 g_o[SEQ * NH * DH];
__device__ __align__(1024) bf16 g_g[SEQ * DM];
__device__ unsigned int g_hcnt[SEQ / 128];
__device__ volatile float g_dummy;

__device__ __forceinline__ uint32_t smem_u32(const void* p) { return (uint32_t)__cvta_generic_to_shared(p); }

__device__ __forceinline__ void mbar_init(uint32_t bar, uint32_t count) {
    asm volatile("mbarrier.init.shared::cta.b64 [%0], %1;" ::"r"(bar), "r"(count) : "memory");
}
__device__ __forceinline__ void mbar_expect_tx(uint32_t bar, uint32_t bytes) {
    asm volatile("mbarrier.arrive.expect_tx.shared::cta.b64 _, [%0], %1;" ::"r"(bar), "r"(bytes) : "memory");
}
__device__ __forceinline__ void mbar_arrive(uint32_t bar) {
    asm volatile("mbarrier.arrive.shared::cta.b64 _, [%0];" ::"r"(bar) : "memory");
}
__device__ __forceinline__ bool mbar_try_wait(uint32_t bar, uint32_t parity) {
    uint32_t ok;
    asm volatile(
        "{\n.reg .pred p;\n"
        "mbarrier.try_wait.parity.shared::cta.b64 p, [%1], %2;\n"
        "selp.u32 %0, 1, 0, p;\n}\n"
        : "=r"(ok)
        : "r"(bar), "r"(parity)
        : "memory");
    return ok != 0;
}
__device__ __forceinline__ void mbar_wait(uint32_t bar, uint32_t parity) {
    asm volatile(
        "{\n.reg .pred P1;\n.reg .u32 n;\nmov.u32 n, 0;\n"
        "LAB_WAIT:\n"
        "mbarrier.try_wait.parity.shared::cta.b64 P1, [%0], %1;\n"
        "@P1 bra DONE;\n"
        "add.u32 n, n, 1;\n"
        "setp.lt.u32 P1, n, 4194304;\n"
        "@P1 bra LAB_WAIT;\n"
        "trap;\n"
        "DONE:\n}\n" ::"r"(bar), "r"(parity)
        : "memory");
}
__device__ __forceinline__ void tma_load_3d(uint32_t dst, const CUtensorMap* map, uint32_t bar, int c0, int c1, int c2) {
    asm volatile(
        "cp.async.bulk.tensor.3d.shared::cluster.global.mbarrier::complete_tx::bytes [%0], [%1, {%3, %4, %5}], [%2];"
        ::"r"(dst), "l"((uint64_t)map), "r"(bar), "r"(c0), "r"(c1), "r"(c2)
        : "memory");
}
__device__ __forceinline__ void tma_store_3d(const CUtensorMap* map, uint32_t src, int c0, int c1, int c2) {
    asm volatile("cp.async.bulk.tensor.3d.global.shared::cta.bulk_group [%0, {%2, %3, %4}], [%1];"
                 ::"l"((uint64_t)map), "r"(src), "r"(c0), "r"(c1), "r"(c2)
                 : "memory");
}
__device__ __forceinline__ void tma_commit() { asm volatile("cp.async.bulk.commit_group;" ::: "memory"); }
__device__ __forceinline__ void tma_wait_read0() { asm volatile("cp.async.bulk.wait_group.read 0;" ::: "memory"); }
__device__ __forceinline__ void tma_wait_all0() { asm volatile("cp.async.bulk.wait_group 0;" ::: "memory"); }
__device__ __forceinline__ void fence_proxy_async() { asm volatile("fence.proxy.async.shared::cta;" ::: "memory"); }
__device__ __forceinline__ void prefetch_tmap(const CUtensorMap* map) {
    asm volatile("prefetch.tensormap [%0];" ::"l"((uint64_t)map) : "memory");
}
__device__ __forceinline__ void named_sync(int id, int n) { asm volatile("bar.sync %0, %1;" ::"r"(id), "r"(n) : "memory"); }
__device__ __forceinline__ void named_arrive(int id, int n) { asm volatile("bar.arrive %0, %1;" ::"r"(id), "r"(n) : "memory"); }

__device__ __forceinline__ void wgmma_fence() { asm volatile("wgmma.fence.sync.aligned;" ::: "memory"); }
__device__ __forceinline__ void wgmma_commit() { asm volatile("wgmma.commit_group.sync.aligned;" ::: "memory"); }
template <int N>
__device__ __forceinline__ void wgmma_wait() { asm volatile("wgmma.wait_group.sync.aligned %0;" ::"n"(N) : "memory"); }

template <int R>
__device__ __forceinline__ void reg_alloc() { asm volatile("setmaxnreg.inc.sync.aligned.u32 %0;" ::"n"(R)); }
template <int R>
__device__ __forceinline__ void reg_dealloc() { asm volatile("setmaxnreg.dec.sync.aligned.u32 %0;" ::"n"(R)); }

__device__ __forceinline__ uint64_t make_desc(uint32_t saddr, uint32_t lbo_bytes, uint32_t sbo_bytes) {
    uint64_t d = 0;
    d |= (uint64_t)((saddr & 0x3FFFF) >> 4);
    d |= (uint64_t)((lbo_bytes >> 4) & 0x3FFF) << 16;
    d |= (uint64_t)((sbo_bytes >> 4) & 0x3FFF) << 32;
    d |= (uint64_t)1 << 62;
    return d;
}

__device__ __forceinline__ float ex2(float x) {
    float y;
    asm volatile("ex2.approx.ftz.f32 %0, %1;" : "=f"(y) : "f"(x));
    return y;
}
__device__ __forceinline__ uint32_t pack_bf16(float lo, float hi) {
    uint32_t r;
    asm("cvt.rn.bf16x2.f32 %0, %1, %2;" : "=r"(r) : "f"(hi), "f"(lo));
    return r;
}
__device__ __forceinline__ uint32_t mul_bf16x2(uint32_t a, uint32_t b) {
    uint32_t r;
    asm("mul.rn.bf16x2 %0, %1, %2;" : "=r"(r) : "r"(a), "r"(b));
    return r;
}
__device__ __forceinline__ uint32_t fma_bf16x2(uint32_t a, uint32_t b, uint32_t c) {
    uint32_t r;
    asm("fma.rn.bf16x2 %0, %1, %2, %3;" : "=r"(r) : "r"(a), "r"(b), "r"(c));
    return r;
}
__device__ __forceinline__ uint32_t max_bf16x2(uint32_t a, uint32_t b) {
    uint32_t r;
    asm("max.bf16x2 %0, %1, %2;" : "=r"(r) : "r"(a), "r"(b));
    return r;
}
__device__ __forceinline__ float bf16lo(uint32_t v) { return __uint_as_float(v << 16); }
__device__ __forceinline__ float bf16hi(uint32_t v) { return __uint_as_float(v & 0xffff0000u); }
__device__ __forceinline__ float bf16_round(float x) { return __bfloat162float(__float2bfloat16_rn(x)); }
__device__ __forceinline__ float silu_f(float x) { return x / (1.0f + __expf(-x)); }

__device__ __forceinline__ void stmatrix_x4(uint32_t addr, uint32_t r0, uint32_t r1, uint32_t r2, uint32_t r3) {
    asm volatile("stmatrix.sync.aligned.m8n8.x4.shared.b16 [%0], {%1, %2, %3, %4};"
                 ::"r"(addr), "r"(r0), "r"(r1), "r"(r2), "r"(r3)
                 : "memory");
}

#define ACC64(d) \
    "+f"(d[0]), "+f"(d[1]), "+f"(d[2]), "+f"(d[3]), "+f"(d[4]), "+f"(d[5]), "+f"(d[6]), "+f"(d[7]), \
    "+f"(d[8]), "+f"(d[9]), "+f"(d[10]), "+f"(d[11]), "+f"(d[12]), "+f"(d[13]), "+f"(d[14]), "+f"(d[15]), \
    "+f"(d[16]), "+f"(d[17]), "+f"(d[18]), "+f"(d[19]), "+f"(d[20]), "+f"(d[21]), "+f"(d[22]), "+f"(d[23]), \
    "+f"(d[24]), "+f"(d[25]), "+f"(d[26]), "+f"(d[27]), "+f"(d[28]), "+f"(d[29]), "+f"(d[30]), "+f"(d[31]), \
    "+f"(d[32]), "+f"(d[33]), "+f"(d[34]), "+f"(d[35]), "+f"(d[36]), "+f"(d[37]), "+f"(d[38]), "+f"(d[39]), \
    "+f"(d[40]), "+f"(d[41]), "+f"(d[42]), "+f"(d[43]), "+f"(d[44]), "+f"(d[45]), "+f"(d[46]), "+f"(d[47]), \
    "+f"(d[48]), "+f"(d[49]), "+f"(d[50]), "+f"(d[51]), "+f"(d[52]), "+f"(d[53]), "+f"(d[54]), "+f"(d[55]), \
    "+f"(d[56]), "+f"(d[57]), "+f"(d[58]), "+f"(d[59]), "+f"(d[60]), "+f"(d[61]), "+f"(d[62]), "+f"(d[63])

#define ACC64_STR \
    "{%0, %1, %2, %3, %4, %5, %6, %7, %8, %9, %10, %11, %12, %13, %14, %15, " \
    "%16, %17, %18, %19, %20, %21, %22, %23, %24, %25, %26, %27, %28, %29, %30, %31, " \
    "%32, %33, %34, %35, %36, %37, %38, %39, %40, %41, %42, %43, %44, %45, %46, %47, " \
    "%48, %49, %50, %51, %52, %53, %54, %55, %56, %57, %58, %59, %60, %61, %62, %63}"

template <int TB>
__device__ __forceinline__ void wgmma_ss_n128(float (&d)[64], uint64_t da, uint64_t db, int scale_d) {
    asm volatile(
        "{\n.reg .pred p;\nsetp.ne.b32 p, %66, 0;\n"
        "wgmma.mma_async.sync.aligned.m64n128k16.f32.bf16.bf16 " ACC64_STR ", %64, %65, p, 1, 1, 0, %67;\n}\n"
        : ACC64(d)
        : "l"(da), "l"(db), "r"(scale_d), "n"(TB));
}
template <int TB>
__device__ __forceinline__ void wgmma_rs_n128(float (&d)[64], uint32_t a0, uint32_t a1, uint32_t a2, uint32_t a3,
                                              uint64_t db, int scale_d) {
    asm volatile(
        "{\n.reg .pred p;\nsetp.ne.b32 p, %69, 0;\n"
        "wgmma.mma_async.sync.aligned.m64n128k16.f32.bf16.bf16 " ACC64_STR ", {%64, %65, %66, %67}, %68, p, 1, 1, %70;\n}\n"
        : ACC64(d)
        : "r"(a0), "r"(a1), "r"(a2), "r"(a3), "l"(db), "r"(scale_d), "n"(TB));
}

__global__ void __launch_bounds__(256) ln_kernel(const bf16* __restrict__ x) {
    int warp = threadIdx.x >> 5, lane = threadIdx.x & 31;
    int row = blockIdx.x * 8 + warp;
    if (blockIdx.x == 0 && threadIdx.x < SEQ / 128) g_hcnt[threadIdx.x] = 0;
    const uint4* src = reinterpret_cast<const uint4*>(x + (size_t)row * DM);
    uint4 v[2];
    v[0] = src[lane];
    v[1] = src[lane + 32];
    float f[16];
#pragma unroll
    for (int i = 0; i < 2; i++) {
        const __nv_bfloat162* p = reinterpret_cast<const __nv_bfloat162*>(&v[i]);
#pragma unroll
        for (int j = 0; j < 4; j++) {
            float2 t = __bfloat1622float2(p[j]);
            f[i * 8 + j * 2] = t.x;
            f[i * 8 + j * 2 + 1] = t.y;
        }
    }
    float s = 0.f;
#pragma unroll
    for (int i = 0; i < 16; i++) s += f[i];
#pragma unroll
    for (int o = 16; o > 0; o >>= 1) s += __shfl_xor_sync(0xffffffffu, s, o);
    float mean = s * (1.0f / DM);
    float q = 0.f;
#pragma unroll
    for (int i = 0; i < 16; i++) {
        float d = f[i] - mean;
        q += d * d;
    }
#pragma unroll
    for (int o = 16; o > 0; o >>= 1) q += __shfl_xor_sync(0xffffffffu, q, o);
    float var_b = bf16_round(q * (1.0f / DM));
    float mean_b = bf16_round(mean);
    float den = bf16_round(sqrtf(bf16_round(var_b + 1e-5f)));
    uint4 o[2];
#pragma unroll
    for (int i = 0; i < 2; i++) {
        uint32_t* p = reinterpret_cast<uint32_t*>(&o[i]);
#pragma unroll
        for (int j = 0; j < 4; j++) {
            float a = bf16_round(f[i * 8 + j * 2] - mean_b) / den;
            float b = bf16_round(f[i * 8 + j * 2 + 1] - mean_b) / den;
            p[j] = pack_bf16(a, b);
        }
    }
    uint4* dst = reinterpret_cast<uint4*>(g_xn + (size_t)row * DM);
    dst[lane] = o[0];
    dst[lane + 32] = o[1];
}

constexpr int AT_STAGES = 3;
constexpr int TILE_BYTES = 128 * 128 * 2;
struct __align__(1024) AttnSmem {
    uint8_t k[AT_STAGES][TILE_BYTES];
    uint8_t v[AT_STAGES][TILE_BYTES];
    uint8_t o[TILE_BYTES];
    uint64_t full_k[AT_STAGES], full_v[AT_STAGES], empty_k[AT_STAGES], empty_v[AT_STAGES];
};

constexpr int NUM_CTAS = 132;
constexpr int MAX_ITEMS = 12;
enum { T_ATT = 0, T_F1 = 1, T_F2 = 2 };
struct Sched {
    uint16_t item[NUM_CTAS][MAX_ITEMS];
    uint8_t count[NUM_CTAS];
};

__global__ void __launch_bounds__(384, 1)
attn_kernel(const __grid_constant__ CUtensorMap tm_xn, const __grid_constant__ CUtensorMap tm_wq,
            const __grid_constant__ CUtensorMap tm_k, const __grid_constant__ CUtensorMap tm_v,
            const __grid_constant__ CUtensorMap tm_o, const __grid_constant__ CUtensorMap tm_w1,
            const __grid_constant__ CUtensorMap tm_hst, const __grid_constant__ CUtensorMap tm_hld,
            const __grid_constant__ CUtensorMap tm_w2, const __grid_constant__ CUtensorMap tm_gst,
            const __grid_constant__ Sched sched) {
    extern __shared__ uint8_t smem_raw[];
    AttnSmem& sm = *reinterpret_cast<AttnSmem*>((reinterpret_cast<uintptr_t>(smem_raw) + 1023) & ~uintptr_t(1023));
    const int tid = threadIdx.x;
    const int wg = tid >> 7;
    const int n_items = sched.count[blockIdx.x];

    if (tid == 0) {
#pragma unroll
        for (int s = 0; s < AT_STAGES; s++) {
            mbar_init(smem_u32(&sm.full_k[s]), 1);
            mbar_init(smem_u32(&sm.full_v[s]), 1);
            mbar_init(smem_u32(&sm.empty_k[s]), 8);
            mbar_init(smem_u32(&sm.empty_v[s]), 8);
        }
        asm volatile("fence.mbarrier_init.release.cluster;" ::: "memory");
    }
    __syncthreads();

    if (wg == 0) {
        reg_dealloc<24>();
        if (tid == 0) {
            int stage = 0;
            uint32_t phase = 0;
            for (int it = 0; it < n_items; it++) {
                const int item = sched.item[blockIdx.x][it];
                const int type = item >> 12, a = (item >> 4) & 0xff, b = item & 15;
                const CUtensorMap* ta = (type == T_F2) ? &tm_hld : &tm_xn;
                const CUtensorMap* tb = (type == T_ATT) ? &tm_wq : (type == T_F1 ? &tm_w1 : &tm_w2);
                const int nch = (type == T_F2) ? FF / 128 : DM / 128;
                if (type == T_F2) {
                    unsigned int v, spins = 0;
                    do {
                        asm volatile("ld.acquire.gpu.global.u32 %0, [%1];" : "=r"(v) : "l"(&g_hcnt[b]) : "memory");
                    } while (v < 2 * (FF / 128) && ++spins < (1u << 24));
                    asm volatile("fence.proxy.async;" ::: "memory");
                }
                for (int kc = 0; kc < nch; kc++) {
                    mbar_wait(smem_u32(&sm.empty_k[stage]), phase ^ 1);
                    mbar_expect_tx(smem_u32(&sm.full_k[stage]), TILE_BYTES);
                    tma_load_3d(smem_u32(sm.k[stage]), ta, smem_u32(&sm.full_k[stage]), 0, b * 128, kc * 2);
                    mbar_wait(smem_u32(&sm.empty_v[stage]), phase ^ 1);
                    mbar_expect_tx(smem_u32(&sm.full_v[stage]), TILE_BYTES);
                    tma_load_3d(smem_u32(sm.v[stage]), tb, smem_u32(&sm.full_v[stage]), 0, kc * 128, a * 2);
                    if (++stage == AT_STAGES) { stage = 0; phase ^= 1; }
                }
                if (type == T_ATT) {
                    for (int j = 0; j < 16; j++) {
                        mbar_wait(smem_u32(&sm.empty_k[stage]), phase ^ 1);
                        mbar_expect_tx(smem_u32(&sm.full_k[stage]), TILE_BYTES);
                        tma_load_3d(smem_u32(sm.k[stage]), &tm_k, smem_u32(&sm.full_k[stage]), 0, a * SEQ + j * 128, 0);
                        mbar_wait(smem_u32(&sm.empty_v[stage]), phase ^ 1);
                        mbar_expect_tx(smem_u32(&sm.full_v[stage]), TILE_BYTES);
                        tma_load_3d(smem_u32(sm.v[stage]), &tm_v, smem_u32(&sm.full_v[stage]), 0, a * SEQ + j * 128, 0);
                        if (++stage == AT_STAGES) { stage = 0; phase ^= 1; }
                    }
                }
            }
        }
    } else {
        reg_alloc<240>();
        const int cw = wg - 1;
        const int lane = tid & 31;
        const int warp_in_wg = (tid >> 5) & 3;
        const float c = 1.4426950408889634f;
        const uint32_t SCALE_HI2 = 0x3DB53DB5u, SCALE_LO2 = 0x371E371Eu;
        constexpr int BAR_SCHED0 = 1, BAR_EPI0 = 3;
        const uint32_t obase = smem_u32(sm.o) + cw * 16384;
        const int st_row = warp_in_wg * 16 + ((lane >> 3) & 1) * 8 + (lane & 7);

        if (cw == 1) named_arrive(BAR_SCHED0 + 0, 256);

        int stage = 0;
        uint32_t phase = 0;
        int pending_mb = -1;
        float S[64], O[64];
        uint32_t P[32];

        for (int it = 0; it < n_items; it++) {
            const int item = sched.item[blockIdx.x][it];
            const int type = item >> 12, ia = (item >> 4) & 0xff, ib = item & 15;
            const int nch = (type == T_F2) ? FF / 128 : DM / 128;
            {
                int prev = -1;
#pragma unroll 1
                for (int kc = 0; kc < nch; kc++) {
                    mbar_wait(smem_u32(&sm.full_k[stage]), phase);
                    mbar_wait(smem_u32(&sm.full_v[stage]), phase);
                    const uint64_t da = make_desc(smem_u32(sm.k[stage]) + cw * 64 * 128, 16, 1024);
                    const uint64_t db = make_desc(smem_u32(sm.v[stage]), 16384, 1024);
                    wgmma_fence();
#pragma unroll
                    for (int kk = 0; kk < 8; kk++) {
                        wgmma_ss_n128<1>(S, da + (uint64_t)(((kk >> 2) * 16384 + (kk & 3) * 32) >> 4),
                                         db + (uint64_t)((kk * 2048) >> 4), (kc | kk) != 0);
                    }
                    wgmma_commit();
                    wgmma_wait<1>();
                    if (prev >= 0 && lane == 0) {
                        mbar_arrive(smem_u32(&sm.empty_k[prev]));
                        mbar_arrive(smem_u32(&sm.empty_v[prev]));
                    }
                    prev = stage;
                    if (++stage == AT_STAGES) { stage = 0; phase ^= 1; }
                }
                wgmma_wait<0>();
                if (lane == 0) {
                    mbar_arrive(smem_u32(&sm.empty_k[prev]));
                    mbar_arrive(smem_u32(&sm.empty_v[prev]));
                }
            }
            if (type != T_ATT) {
#pragma unroll
                for (int i = 0; i < 64; i++) S[i] = silu_f(bf16_round(S[i]));
            }
            if ((tid & 127) == 0) {
                if (pending_mb >= 0) {
                    tma_wait_all0();
                    asm volatile("fence.proxy.async;" ::: "memory");
                    __threadfence();
                    atomicAdd(&g_hcnt[pending_mb], 1u);
                } else {
                    tma_wait_read0();
                }
            }
            pending_mb = -1;
            named_sync(BAR_EPI0 + cw, 128);
#pragma unroll
            for (int i = 0; i < 16; i += 2) {
                const int cc = i + (lane >> 4);
                const uint32_t addr = obase + (cc >> 3) * 8192 + st_row * 128 + (((cc & 7) ^ (st_row & 7)) << 4);
                stmatrix_x4(addr, pack_bf16(S[4 * i], S[4 * i + 1]), pack_bf16(S[4 * i + 2], S[4 * i + 3]),
                            pack_bf16(S[4 * i + 4], S[4 * i + 5]), pack_bf16(S[4 * i + 6], S[4 * i + 7]));
            }
            fence_proxy_async();
            named_sync(BAR_EPI0 + cw, 128);
            if (type != T_ATT) {
                if ((tid & 127) == 0) {
                    tma_store_3d(type == T_F1 ? &tm_hst : &tm_gst, obase, 0, ib * 128 + cw * 64, ia * 2);
                    tma_commit();
                }
                if (type == T_F1) pending_mb = ib;
                continue;
            }
            const uint64_t dq = make_desc(obase, 16, 1024);
#pragma unroll
            for (int i = 0; i < 64; i++) O[i] = 0.f;

            float m0 = -INFINITY, m1 = -INFINITY, l0 = 0.f, l1 = 0.f, a0 = 0.f, a1 = 0.f;

            {
                mbar_wait(smem_u32(&sm.full_k[stage]), phase);
                const uint64_t dk = make_desc(smem_u32(sm.k[stage]), 16, 1024);
                named_sync(BAR_SCHED0 + cw, 256);
                wgmma_fence();
#pragma unroll
                for (int kk = 0; kk < 8; kk++)
                    wgmma_ss_n128<0>(S, dq + (uint64_t)(((kk >> 2) * 8192 + (kk & 3) * 32) >> 4),
                                     dk + (uint64_t)(((kk >> 2) * 16384 + (kk & 3) * 32) >> 4), kk != 0);
                wgmma_commit();
                named_arrive(BAR_SCHED0 + (cw ^ 1), 256);
                wgmma_wait<0>();
                if (lane == 0) mbar_arrive(smem_u32(&sm.empty_k[stage]));
            }
            int vstage = stage;
            uint32_t vphase = phase;
            if (++stage == AT_STAGES) { stage = 0; phase ^= 1; }

            auto softmax = [&]() {
                uint32_t T[32];
#pragma unroll
                for (int i = 0; i < 32; i++) {
                    const uint32_t sb = pack_bf16(S[2 * i], S[2 * i + 1]);
                    T[i] = fma_bf16x2(sb, SCALE_HI2, mul_bf16x2(sb, SCALE_LO2));
                }
                uint32_t y0 = max_bf16x2(T[0], T[2]), y1 = max_bf16x2(T[1], T[3]);
#pragma unroll
                for (int i = 2; i < 16; i++) {
                    y0 = max_bf16x2(y0, T[2 * i]);
                    y1 = max_bf16x2(y1, T[2 * i + 1]);
                }
                float x0 = fmaxf(m0, fmaxf(bf16lo(y0), bf16hi(y0)));
                float x1 = fmaxf(m1, fmaxf(bf16lo(y1), bf16hi(y1)));
                x0 = fmaxf(x0, __shfl_xor_sync(0xffffffffu, x0, 1));
                x1 = fmaxf(x1, __shfl_xor_sync(0xffffffffu, x1, 1));
                x0 = fmaxf(x0, __shfl_xor_sync(0xffffffffu, x0, 2));
                x1 = fmaxf(x1, __shfl_xor_sync(0xffffffffu, x1, 2));
                a0 = ex2((m0 - x0) * c);
                a1 = ex2((m1 - x1) * c);
                m0 = x0;
                m1 = x1;
                const float n0 = -x0 * c, n1 = -x1 * c;
                float s0 = 0.f, s1 = 0.f;
#pragma unroll
                for (int i = 0; i < 16; i++) {
                    S[4 * i] = ex2(fmaf(bf16lo(T[2 * i]), c, n0));
                    S[4 * i + 1] = ex2(fmaf(bf16hi(T[2 * i]), c, n0));
                    S[4 * i + 2] = ex2(fmaf(bf16lo(T[2 * i + 1]), c, n1));
                    S[4 * i + 3] = ex2(fmaf(bf16hi(T[2 * i + 1]), c, n1));
                    s0 += S[4 * i] + S[4 * i + 1];
                    s1 += S[4 * i + 2] + S[4 * i + 3];
                }
                l0 = l0 * a0 + s0;
                l1 = l1 * a1 + s1;
                while (s0 + s1 < 0.f) s0 = g_dummy;
            };
            softmax();
#pragma unroll
            for (int i = 0; i < 32; i++) P[i] = pack_bf16(S[2 * i], S[2 * i + 1]);

#pragma unroll 1
            for (int j = 1; j < 16; j++) {
                mbar_wait(smem_u32(&sm.full_k[stage]), phase);
                const uint64_t dk = make_desc(smem_u32(sm.k[stage]), 16, 1024);
                const uint64_t dv = make_desc(smem_u32(sm.v[vstage]), 16384, 1024);
                named_sync(BAR_SCHED0 + cw, 256);
                wgmma_fence();
#pragma unroll
                for (int kk = 0; kk < 8; kk++)
                    wgmma_ss_n128<0>(S, dq + (uint64_t)(((kk >> 2) * 8192 + (kk & 3) * 32) >> 4),
                                     dk + (uint64_t)(((kk >> 2) * 16384 + (kk & 3) * 32) >> 4), kk != 0);
                wgmma_commit();
#pragma unroll
                for (int i = 0; i < 16; i++) {
                    O[4 * i] *= a0;
                    O[4 * i + 1] *= a0;
                    O[4 * i + 2] *= a1;
                    O[4 * i + 3] *= a1;
                }
                mbar_wait(smem_u32(&sm.full_v[vstage]), vphase);
                wgmma_fence();
#pragma unroll
                for (int kk = 0; kk < 8; kk++)
                    wgmma_rs_n128<1>(O, P[4 * kk], P[4 * kk + 1], P[4 * kk + 2], P[4 * kk + 3],
                                     dv + (uint64_t)((kk * 2048) >> 4), 1);
                wgmma_commit();
                named_arrive(BAR_SCHED0 + (cw ^ 1), 256);
                wgmma_wait<1>();
                if (lane == 0) mbar_arrive(smem_u32(&sm.empty_k[stage]));
                softmax();
                wgmma_wait<0>();
                if (lane == 0) mbar_arrive(smem_u32(&sm.empty_v[vstage]));
#pragma unroll
                for (int i = 0; i < 32; i++) P[i] = pack_bf16(S[2 * i], S[2 * i + 1]);
                vstage = stage;
                vphase = phase;
                if (++stage == AT_STAGES) { stage = 0; phase ^= 1; }
            }
            {
#pragma unroll
                for (int i = 0; i < 16; i++) {
                    O[4 * i] *= a0;
                    O[4 * i + 1] *= a0;
                    O[4 * i + 2] *= a1;
                    O[4 * i + 3] *= a1;
                }
                const uint64_t dv = make_desc(smem_u32(sm.v[vstage]), 16384, 1024);
                mbar_wait(smem_u32(&sm.full_v[vstage]), vphase);
                wgmma_fence();
#pragma unroll
                for (int kk = 0; kk < 8; kk++)
                    wgmma_rs_n128<1>(O, P[4 * kk], P[4 * kk + 1], P[4 * kk + 2], P[4 * kk + 3],
                                     dv + (uint64_t)((kk * 2048) >> 4), 1);
                wgmma_commit();
                wgmma_wait<0>();
                if (lane == 0) mbar_arrive(smem_u32(&sm.empty_v[vstage]));
            }
            l0 += __shfl_xor_sync(0xffffffffu, l0, 1);
            l1 += __shfl_xor_sync(0xffffffffu, l1, 1);
            l0 += __shfl_xor_sync(0xffffffffu, l0, 2);
            l1 += __shfl_xor_sync(0xffffffffu, l1, 2);
            const float i0 = 1.0f / l0, i1 = 1.0f / l1;
            named_sync(BAR_EPI0 + cw, 128);
#pragma unroll
            for (int i = 0; i < 16; i += 2) {
                const int cc = i + (lane >> 4);
                const uint32_t addr = obase + (cc >> 3) * 8192 + st_row * 128 + (((cc & 7) ^ (st_row & 7)) << 4);
                stmatrix_x4(addr, pack_bf16(O[4 * i] * i0, O[4 * i + 1] * i0), pack_bf16(O[4 * i + 2] * i1, O[4 * i + 3] * i1),
                            pack_bf16(O[4 * i + 4] * i0, O[4 * i + 5] * i0), pack_bf16(O[4 * i + 6] * i1, O[4 * i + 7] * i1));
            }
            fence_proxy_async();
            named_sync(BAR_EPI0 + cw, 128);
            if ((tid & 127) == 0) {
                tma_store_3d(&tm_o, obase, 0, ib * 128 + cw * 64, ia * 2);
                tma_commit();
            }
        }
        if ((tid & 127) == 0) {
            tma_wait_all0();
            if (pending_mb >= 0) {
                asm volatile("fence.proxy.async;" ::: "memory");
                __threadfence();
                atomicAdd(&g_hcnt[pending_mb], 1u);
            }
        }
    }
}

constexpr int OP_STAGES = 4;
constexpr int OP_KSPLIT = 4;
struct __align__(1024) OpSmem {
    uint8_t a[OP_STAGES][128 * 64 * 2];
    uint8_t b[OP_STAGES][64 * 256 * 2];
    uint64_t full[OP_STAGES], empty[OP_STAGES];
};

#define ACC8(d, o) "+f"(d[o]), "+f"(d[o + 1]), "+f"(d[o + 2]), "+f"(d[o + 3]), "+f"(d[o + 4]), "+f"(d[o + 5]), "+f"(d[o + 6]), "+f"(d[o + 7])
__device__ __forceinline__ void wgmma_ss_n256_tb(float (&d)[128], uint64_t da, uint64_t db, int scale_d) {
    asm volatile(
        "{\n.reg .pred p;\nsetp.ne.b32 p, %130, 0;\n"
        "wgmma.mma_async.sync.aligned.m64n256k16.f32.bf16.bf16 "
        "{%0, %1, %2, %3, %4, %5, %6, %7, %8, %9, %10, %11, %12, %13, %14, %15, "
        "%16, %17, %18, %19, %20, %21, %22, %23, %24, %25, %26, %27, %28, %29, %30, %31, "
        "%32, %33, %34, %35, %36, %37, %38, %39, %40, %41, %42, %43, %44, %45, %46, %47, "
        "%48, %49, %50, %51, %52, %53, %54, %55, %56, %57, %58, %59, %60, %61, %62, %63, "
        "%64, %65, %66, %67, %68, %69, %70, %71, %72, %73, %74, %75, %76, %77, %78, %79, "
        "%80, %81, %82, %83, %84, %85, %86, %87, %88, %89, %90, %91, %92, %93, %94, %95, "
        "%96, %97, %98, %99, %100, %101, %102, %103, %104, %105, %106, %107, %108, %109, %110, %111, "
        "%112, %113, %114, %115, %116, %117, %118, %119, %120, %121, %122, %123, %124, %125, %126, %127}, "
        "%128, %129, p, 1, 1, 0, 1;\n}\n"
        : ACC8(d, 0), ACC8(d, 8), ACC8(d, 16), ACC8(d, 24), ACC8(d, 32), ACC8(d, 40), ACC8(d, 48), ACC8(d, 56),
          ACC8(d, 64), ACC8(d, 72), ACC8(d, 80), ACC8(d, 88), ACC8(d, 96), ACC8(d, 104), ACC8(d, 112), ACC8(d, 120)
        : "l"(da), "l"(db), "r"(scale_d));
}
__device__ __forceinline__ void cluster_sync_all() {
    asm volatile("barrier.cluster.arrive.release.aligned;\nbarrier.cluster.wait.acquire.aligned;" ::: "memory");
}

__global__ void __cluster_dims__(OP_KSPLIT, 1, 1) __launch_bounds__(384, 1)
oproj_kernel(const __grid_constant__ CUtensorMap tm_o, const __grid_constant__ CUtensorMap tm_wo,
             const bf16* __restrict__ x, bf16* __restrict__ out) {
    extern __shared__ uint8_t smem_raw[];
    OpSmem& sm = *reinterpret_cast<OpSmem*>((reinterpret_cast<uintptr_t>(smem_raw) + 1023) & ~uintptr_t(1023));
    const int tid = threadIdx.x, wg = tid >> 7;
    const int kr = blockIdx.x;
    const int n0 = blockIdx.y * 256, m0 = blockIdx.z * 128;
    constexpr int KT = NH * DH / OP_KSPLIT / 64;
    if (tid == 0) {
        for (int s = 0; s < OP_STAGES; s++) {
            mbar_init(smem_u32(&sm.full[s]), 1);
            mbar_init(smem_u32(&sm.empty[s]), 8);
        }
        asm volatile("fence.mbarrier_init.release.cluster;" ::: "memory");
    }
    __syncthreads();
    float acc[128];
    const int cw = wg - 1, lane = tid & 31, warp_in_wg = (tid >> 5) & 3;
    if (wg == 0) {
        if (tid == 0) {
            int stage = 0;
            uint32_t phase = 0;
            for (int kt = 0; kt < KT; kt++) {
                const int kg = kr * KT + kt;
                mbar_wait(smem_u32(&sm.empty[stage]), phase ^ 1);
                mbar_expect_tx(smem_u32(&sm.full[stage]), 49152);
                tma_load_3d(smem_u32(sm.a[stage]), &tm_o, smem_u32(&sm.full[stage]), 0, m0, kg);
                tma_load_3d(smem_u32(sm.b[stage]), &tm_wo, smem_u32(&sm.full[stage]), 0, kg * 64, n0 >> 6);
                if (++stage == OP_STAGES) { stage = 0; phase ^= 1; }
            }
        }
    } else {
        int stage = 0, prev = -1;
        uint32_t phase = 0;
#pragma unroll 1
        for (int kt = 0; kt < KT; kt++) {
            mbar_wait(smem_u32(&sm.full[stage]), phase);
            const uint64_t da = make_desc(smem_u32(sm.a[stage]) + cw * 64 * 128, 16, 1024);
            const uint64_t db = make_desc(smem_u32(sm.b[stage]), 8192, 1024);
            wgmma_fence();
#pragma unroll
            for (int kk = 0; kk < 4; kk++)
                wgmma_ss_n256_tb(acc, da + (uint64_t)((kk * 32) >> 4), db + (uint64_t)((kk * 2048) >> 4), (kt | kk) != 0);
            wgmma_commit();
            wgmma_wait<1>();
            if (prev >= 0 && lane == 0) mbar_arrive(smem_u32(&sm.empty[prev]));
            prev = stage;
            if (++stage == OP_STAGES) { stage = 0; phase ^= 1; }
        }
        wgmma_wait<0>();
    }
    cluster_sync_all();
    const int ct = tid - 128;
    const uint32_t red_base = smem_u32(sm.a[0]);
    if (wg != 0) {
#pragma unroll
        for (int d = 0; d < OP_KSPLIT; d++) {
            if (d == kr) continue;
            const int slot = kr < d ? kr : kr - 1;
            uint32_t ra;
            asm volatile("mapa.shared::cluster.u32 %0, %1, %2;" : "=r"(ra) : "r"(red_base + (slot * 8 * 256 + ct) * 16), "r"(d));
#pragma unroll
            for (int j = 0; j < 8; j++) {
                asm volatile("st.shared::cluster.v4.f32 [%0], {%1, %2, %3, %4};"
                             ::"r"(ra + j * 256 * 16), "f"(acc[(8 * d + j) * 4]), "f"(acc[(8 * d + j) * 4 + 1]),
                               "f"(acc[(8 * d + j) * 4 + 2]), "f"(acc[(8 * d + j) * 4 + 3])
                             : "memory");
            }
        }
    }
    cluster_sync_all();
    if (wg != 0) {
        float r[32];
#pragma unroll
        for (int d = 0; d < OP_KSPLIT; d++) {
            if (d == kr) {
#pragma unroll
                for (int i = 0; i < 32; i++) r[i] = acc[32 * d + i];
            }
        }
#pragma unroll
        for (int slot = 0; slot < OP_KSPLIT - 1; slot++) {
#pragma unroll
            for (int j = 0; j < 8; j++) {
                float4 v;
                asm volatile("ld.shared.v4.f32 {%0, %1, %2, %3}, [%4];"
                             : "=f"(v.x), "=f"(v.y), "=f"(v.z), "=f"(v.w)
                             : "r"(red_base + ((slot * 8 + j) * 256 + ct) * 16));
                r[4 * j] += v.x;
                r[4 * j + 1] += v.y;
                r[4 * j + 2] += v.z;
                r[4 * j + 3] += v.w;
            }
        }
        const int r0 = m0 + cw * 64 + warp_in_wg * 16 + (lane >> 2);
#pragma unroll
        for (int j = 0; j < 8; j++) {
            const int col = n0 + kr * 64 + j * 8 + (lane & 3) * 2;
#pragma unroll
            for (int hh = 0; hh < 2; hh++) {
                const size_t off = (size_t)(r0 + hh * 8) * DM + col;
                const __nv_bfloat162 xv = *reinterpret_cast<const __nv_bfloat162*>(x + off);
                const __nv_bfloat162 gv = *reinterpret_cast<const __nv_bfloat162*>(g_g + off);
                const float s0 = bf16_round(r[4 * j + 2 * hh]), s1 = bf16_round(r[4 * j + 2 * hh + 1]);
                const float o0 = __bfloat162float(xv.x) + bf16_round(s0 * __bfloat162float(gv.x));
                const float o1 = __bfloat162float(xv.y) + bf16_round(s1 * __bfloat162float(gv.y));
                *reinterpret_cast<uint32_t*>(out + off) = pack_bf16(o0, o1);
            }
        }
    }
}

typedef CUresult (*EncodeFn)(CUtensorMap*, CUtensorMapDataType, cuuint32_t, void*, const cuuint64_t*, const cuuint64_t*,
                             const cuuint32_t*, const cuuint32_t*, CUtensorMapInterleave, CUtensorMapSwizzle,
                             CUtensorMapL2promotion, CUtensorMapFloatOOBfill);

static CUtensorMap make_map(EncodeFn fn, const void* ptr, uint64_t rows, uint64_t cols, uint32_t box_rows, uint32_t box_blk) {
    CUtensorMap m;
    cuuint64_t dims[3] = {64, rows, cols / 64};
    cuuint64_t strides[2] = {cols * 2, 128};
    cuuint32_t box[3] = {64, box_rows, box_blk};
    cuuint32_t es[3] = {1, 1, 1};
    fn(&m, CU_TENSOR_MAP_DATA_TYPE_BFLOAT16, 3, const_cast<void*>(ptr), dims, strides, box, es, CU_TENSOR_MAP_INTERLEAVE_NONE,
       CU_TENSOR_MAP_SWIZZLE_128B, CU_TENSOR_MAP_L2_PROMOTION_L2_256B, CU_TENSOR_MAP_FLOAT_OOB_FILL_NONE);
    return m;
}

extern "C" void kernel_launch(void* const* d_in, const int* in_sizes, int n_in, void* d_out, int out_size) {
    const bf16* x = (const bf16*)d_in[0];
    const bf16* kc = (const bf16*)d_in[1];
    const bf16* vc = (const bf16*)d_in[2];
    const bf16* wq = (const bf16*)d_in[3];
    const bf16* wo = (const bf16*)d_in[4];
    const bf16* w1 = (const bf16*)d_in[6];
    const bf16* w2 = (const bf16*)d_in[7];
    bf16* out = (bf16*)d_out;

    static EncodeFn fn = nullptr;
    static void *p_xn = nullptr, *p_h = nullptr, *p_o = nullptr, *p_g = nullptr;
    static Sched sched;
    if (!fn) {
        void* f = nullptr;
        cudaDriverEntryPointQueryResult st;
        cudaGetDriverEntryPoint("cuTensorMapEncodeTiled", &f, cudaEnableDefault, &st);
        fn = (EncodeFn)f;
        cudaGetSymbolAddress(&p_xn, g_xn);
        cudaGetSymbolAddress(&p_h, g_h);
        cudaGetSymbolAddress(&p_o, g_o);
        cudaGetSymbolAddress(&p_g, g_g);
        cudaFuncSetAttribute(attn_kernel, cudaFuncAttributeMaxDynamicSharedMemorySize, (int)sizeof(AttnSmem) + 1024);
        cudaFuncSetAttribute(oproj_kernel, cudaFuncAttributeMaxDynamicSharedMemorySize, (int)sizeof(OpSmem) + 1024);
        static uint16_t f1[NUM_CTAS][MAX_ITEMS], at[NUM_CTAS][MAX_ITEMS], f2[NUM_CTAS][MAX_ITEMS];
        static int n1[NUM_CTAS], na[NUM_CTAS], n2[NUM_CTAS];
        static double load[NUM_CTAS];
        const double C_ATT = 58.0, C_F1 = 6.5, C_F2 = 19.5;
        for (int i = 0; i < NUM_CTAS; i++) { n1[i] = na[i] = n2[i] = 0; load[i] = 0; }
        for (int t = 0; t < NH * 16; t++) {
            int cta = t % NUM_CTAS;
            at[cta][na[cta]++] = (uint16_t)((T_ATT << 12) | ((t >> 4) << 4) | (t & 15));
            load[cta] += C_ATT;
        }
        auto least = [&]() { int bi = 0; for (int i = 1; i < NUM_CTAS; i++) if (load[i] < load[bi]) bi = i; return bi; };
        for (int t = 0; t < 64; t++) {
            int cta = least();
            f2[cta][n2[cta]++] = (uint16_t)((T_F2 << 12) | ((t & 3) << 4) | (t >> 2));
            load[cta] += C_F2;
        }
        for (int t = 0; t < 224; t++) {
            int cta = least();
            f1[cta][n1[cta]++] = (uint16_t)((T_F1 << 12) | ((t % 14) << 4) | (t / 14));
            load[cta] += C_F1;
        }
        for (int i = 0; i < NUM_CTAS; i++) {
            int n = 0;
            for (int j = 0; j < n1[i]; j++) sched.item[i][n++] = f1[i][j];
            for (int j = 0; j < na[i]; j++) sched.item[i][n++] = at[i][j];
            for (int j = 0; j < n2[i]; j++) sched.item[i][n++] = f2[i][j];
            sched.count[i] = (uint8_t)n;
        }
    }
    CUtensorMap tm_xn_at = make_map(fn, p_xn, SEQ, DM, 128, 2);
    CUtensorMap tm_wq = make_map(fn, wq, DM, NH * DH, 128, 2);
    CUtensorMap tm_k = make_map(fn, kc, NH * SEQ, DH, 128, 2);
    CUtensorMap tm_v = make_map(fn, vc, NH * SEQ, DH, 128, 2);
    CUtensorMap tm_o_st = make_map(fn, p_o, SEQ, NH * DH, 64, 2);
    CUtensorMap tm_w1 = make_map(fn, w1, DM, FF, 128, 2);
    CUtensorMap tm_h_st = make_map(fn, p_h, SEQ, FF, 64, 2);
    CUtensorMap tm_h_ld = make_map(fn, p_h, SEQ, FF, 128, 2);
    CUtensorMap tm_w2 = make_map(fn, w2, FF, DM, 128, 2);
    CUtensorMap tm_g_st = make_map(fn, p_g, SEQ, DM, 64, 2);
    CUtensorMap tm_o_g = make_map(fn, p_o, SEQ, NH * DH, 128, 1);
    CUtensorMap tm_wo = make_map(fn, wo, NH * DH, DM, 64, 4);

    ln_kernel<<<SEQ / 8, 256>>>(x);
    attn_kernel<<<NUM_CTAS, 384, sizeof(AttnSmem) + 1024>>>(tm_xn_at, tm_wq, tm_k, tm_v, tm_o_st, tm_w1, tm_h_st, tm_h_ld,
                                                            tm_w2, tm_g_st, sched);
    oproj_kernel<<<dim3(OP_KSPLIT, DM / 256, SEQ / 128), 384, sizeof(OpSmem) + 1024>>>(tm_o_g, tm_wo, x, out);
}
```

```cpp
#include <cuda_runtime.h>
#include <cuda_bf16.h>
#include <cuda.h>
#include <stdint.h>

typedef __nv_bfloat16 bf16;

constexpr int SEQ = 2048, DM = 512, NH = 32, DH = 128, FF = 1792;

__device__ __align__(1024) bf16 g_xn[SEQ * DM];
__device__ __align__(1024) bf16 g_h[SEQ * FF];
__device__ __align__(1024) bf16 g_o[SEQ * NH * DH];
__device__ __align__(1024) bf16 g_g[SEQ * DM];
__device__ unsigned int g_hcnt[SEQ / 128];
__device__ float4 g_part[32 * 16 * 8 * 256];
__device__ unsigned int g_pcnt[128];
__device__ volatile float g_dummy;

__device__ __forceinline__ uint32_t smem_u32(const void* p) { return (uint32_t)__cvta_generic_to_shared(p); }

__device__ __forceinline__ void mbar_init(uint32_t bar, uint32_t count) {
    asm volatile("mbarrier.init.shared::cta.b64 [%0], %1;" ::"r"(bar), "r"(count) : "memory");
}
__device__ __forceinline__ void mbar_expect_tx(uint32_t bar, uint32_t bytes) {
    asm volatile("mbarrier.arrive.expect_tx.shared::cta.b64 _, [%0], %1;" ::"r"(bar), "r"(bytes) : "memory");
}
__device__ __forceinline__ void mbar_arrive(uint32_t bar) {
    asm volatile("mbarrier.arrive.shared::cta.b64 _, [%0];" ::"r"(bar) : "memory");
}
__device__ __forceinline__ bool mbar_try_wait(uint32_t bar, uint32_t parity) {
    uint32_t ok;
    asm volatile(
        "{\n.reg .pred p;\n"
        "mbarrier.try_wait.parity.shared::cta.b64 p, [%1], %2;\n"
        "selp.u32 %0, 1, 0, p;\n}\n"
        : "=r"(ok)
        : "r"(bar), "r"(parity)
        : "memory");
    return ok != 0;
}
__device__ __forceinline__ void mbar_wait(uint32_t bar, uint32_t parity) {
    asm volatile(
        "{\n.reg .pred P1;\n.reg .u32 n;\nmov.u32 n, 0;\n"
        "LAB_WAIT:\n"
        "mbarrier.try_wait.parity.shared::cta.b64 P1, [%0], %1;\n"
        "@P1 bra DONE;\n"
        "add.u32 n, n, 1;\n"
        "setp.lt.u32 P1, n, 4194304;\n"
        "@P1 bra LAB_WAIT;\n"
        "trap;\n"
        "DONE:\n}\n" ::"r"(bar), "r"(parity)
        : "memory");
}
__device__ __forceinline__ void tma_load_3d(uint32_t dst, const CUtensorMap* map, uint32_t bar, int c0, int c1, int c2) {
    asm volatile(
        "cp.async.bulk.tensor.3d.shared::cluster.global.mbarrier::complete_tx::bytes [%0], [%1, {%3, %4, %5}], [%2];"
        ::"r"(dst), "l"((uint64_t)map), "r"(bar), "r"(c0), "r"(c1), "r"(c2)
        : "memory");
}
__device__ __forceinline__ void tma_store_3d(const CUtensorMap* map, uint32_t src, int c0, int c1, int c2) {
    asm volatile("cp.async.bulk.tensor.3d.global.shared::cta.bulk_group [%0, {%2, %3, %4}], [%1];"
                 ::"l"((uint64_t)map), "r"(src), "r"(c0), "r"(c1), "r"(c2)
                 : "memory");
}
__device__ __forceinline__ void tma_commit() { asm volatile("cp.async.bulk.commit_group;" ::: "memory"); }
__device__ __forceinline__ void tma_wait_read0() { asm volatile("cp.async.bulk.wait_group.read 0;" ::: "memory"); }
__device__ __forceinline__ void tma_wait_all0() { asm volatile("cp.async.bulk.wait_group 0;" ::: "memory"); }
__device__ __forceinline__ void fence_proxy_async() { asm volatile("fence.proxy.async.shared::cta;" ::: "memory"); }
__device__ __forceinline__ void prefetch_tmap(const CUtensorMap* map) {
    asm volatile("prefetch.tensormap [%0];" ::"l"((uint64_t)map) : "memory");
}
__device__ __forceinline__ void named_sync(int id, int n) { asm volatile("bar.sync %0, %1;" ::"r"(id), "r"(n) : "memory"); }
__device__ __forceinline__ void named_arrive(int id, int n) { asm volatile("bar.arrive %0, %1;" ::"r"(id), "r"(n) : "memory"); }

__device__ __forceinline__ void wgmma_fence() { asm volatile("wgmma.fence.sync.aligned;" ::: "memory"); }
__device__ __forceinline__ void wgmma_commit() { asm volatile("wgmma.commit_group.sync.aligned;" ::: "memory"); }
template <int N>
__device__ __forceinline__ void wgmma_wait() { asm volatile("wgmma.wait_group.sync.aligned %0;" ::"n"(N) : "memory"); }

template <int R>
__device__ __forceinline__ void reg_alloc() { asm volatile("setmaxnreg.inc.sync.aligned.u32 %0;" ::"n"(R)); }
template <int R>
__device__ __forceinline__ void reg_dealloc() { asm volatile("setmaxnreg.dec.sync.aligned.u32 %0;" ::"n"(R)); }

__device__ __forceinline__ uint64_t make_desc(uint32_t saddr, uint32_t lbo_bytes, uint32_t sbo_bytes) {
    uint64_t d = 0;
    d |= (uint64_t)((saddr & 0x3FFFF) >> 4);
    d |= (uint64_t)((lbo_bytes >> 4) & 0x3FFF) << 16;
    d |= (uint64_t)((sbo_bytes >> 4) & 0x3FFF) << 32;
    d |= (uint64_t)1 << 62;
    return d;
}

__device__ __forceinline__ float ex2(float x) {
    float y;
    asm volatile("ex2.approx.ftz.f32 %0, %1;" : "=f"(y) : "f"(x));
    return y;
}
__device__ __forceinline__ uint32_t pack_bf16(float lo, float hi) {
    uint32_t r;
    asm("cvt.rn.bf16x2.f32 %0, %1, %2;" : "=r"(r) : "f"(hi), "f"(lo));
    return r;
}
__device__ __forceinline__ uint32_t mul_bf16x2(uint32_t a, uint32_t b) {
    uint32_t r;
    asm("mul.rn.bf16x2 %0, %1, %2;" : "=r"(r) : "r"(a), "r"(b));
    return r;
}
__device__ __forceinline__ uint32_t fma_bf16x2(uint32_t a, uint32_t b, uint32_t c) {
    uint32_t r;
    asm("fma.rn.bf16x2 %0, %1, %2, %3;" : "=r"(r) : "r"(a), "r"(b), "r"(c));
    return r;
}
__device__ __forceinline__ uint32_t max_bf16x2(uint32_t a, uint32_t b) {
    uint32_t r;
    asm("max.bf16x2 %0, %1, %2;" : "=r"(r) : "r"(a), "r"(b));
    return r;
}
__device__ __forceinline__ float bf16lo(uint32_t v) { return __uint_as_float(v << 16); }
__device__ __forceinline__ float bf16hi(uint32_t v) { return __uint_as_float(v & 0xffff0000u); }
__device__ __forceinline__ float bf16_round(float x) { return __bfloat162float(__float2bfloat16_rn(x)); }
__device__ __forceinline__ float silu_f(float x) { return __fdividef(x, 1.0f + __expf(-x)); }

__device__ __forceinline__ void stmatrix_x4(uint32_t addr, uint32_t r0, uint32_t r1, uint32_t r2, uint32_t r3) {
    asm volatile("stmatrix.sync.aligned.m8n8.x4.shared.b16 [%0], {%1, %2, %3, %4};"
                 ::"r"(addr), "r"(r0), "r"(r1), "r"(r2), "r"(r3)
                 : "memory");
}

#define ACC64(d) \
    "+f"(d[0]), "+f"(d[1]), "+f"(d[2]), "+f"(d[3]), "+f"(d[4]), "+f"(d[5]), "+f"(d[6]), "+f"(d[7]), \
    "+f"(d[8]), "+f"(d[9]), "+f"(d[10]), "+f"(d[11]), "+f"(d[12]), "+f"(d[13]), "+f"(d[14]), "+f"(d[15]), \
    "+f"(d[16]), "+f"(d[17]), "+f"(d[18]), "+f"(d[19]), "+f"(d[20]), "+f"(d[21]), "+f"(d[22]), "+f"(d[23]), \
    "+f"(d[24]), "+f"(d[25]), "+f"(d[26]), "+f"(d[27]), "+f"(d[28]), "+f"(d[29]), "+f"(d[30]), "+f"(d[31]), \
    "+f"(d[32]), "+f"(d[33]), "+f"(d[34]), "+f"(d[35]), "+f"(d[36]), "+f"(d[37]), "+f"(d[38]), "+f"(d[39]), \
    "+f"(d[40]), "+f"(d[41]), "+f"(d[42]), "+f"(d[43]), "+f"(d[44]), "+f"(d[45]), "+f"(d[46]), "+f"(d[47]), \
    "+f"(d[48]), "+f"(d[49]), "+f"(d[50]), "+f"(d[51]), "+f"(d[52]), "+f"(d[53]), "+f"(d[54]), "+f"(d[55]), \
    "+f"(d[56]), "+f"(d[57]), "+f"(d[58]), "+f"(d[59]), "+f"(d[60]), "+f"(d[61]), "+f"(d[62]), "+f"(d[63])

#define ACC64_STR \
    "{%0, %1, %2, %3, %4, %5, %6, %7, %8, %9, %10, %11, %12, %13, %14, %15, " \
    "%16, %17, %18, %19, %20, %21, %22, %23, %24, %25, %26, %27, %28, %29, %30, %31, " \
    "%32, %33, %34, %35, %36, %37, %38, %39, %40, %41, %42, %43, %44, %45, %46, %47, " \
    "%48, %49, %50, %51, %52, %53, %54, %55, %56, %57, %58, %59, %60, %61, %62, %63}"

template <int TB>
__device__ __forceinline__ void wgmma_ss_n128(float (&d)[64], uint64_t da, uint64_t db, int scale_d) {
    asm volatile(
        "{\n.reg .pred p;\nsetp.ne.b32 p, %66, 0;\n"
        "wgmma.mma_async.sync.aligned.m64n128k16.f32.bf16.bf16 " ACC64_STR ", %64, %65, p, 1, 1, 0, %67;\n}\n"
        : ACC64(d)
        : "l"(da), "l"(db), "r"(scale_d), "n"(TB));
}
template <int TB>
__device__ __forceinline__ void wgmma_rs_n128(float (&d)[64], uint32_t a0, uint32_t a1, uint32_t a2, uint32_t a3,
                                              uint64_t db, int scale_d) {
    asm volatile(
        "{\n.reg .pred p;\nsetp.ne.b32 p, %69, 0;\n"
        "wgmma.mma_async.sync.aligned.m64n128k16.f32.bf16.bf16 " ACC64_STR ", {%64, %65, %66, %67}, %68, p, 1, 1, %70;\n}\n"
        : ACC64(d)
        : "r"(a0), "r"(a1), "r"(a2), "r"(a3), "l"(db), "r"(scale_d), "n"(TB));
}

__global__ void __launch_bounds__(256) ln_kernel(const bf16* __restrict__ x) {
    int warp = threadIdx.x >> 5, lane = threadIdx.x & 31;
    int row = blockIdx.x * 8 + warp;
    if (blockIdx.x == 0 && threadIdx.x < SEQ / 128) g_hcnt[threadIdx.x] = 0;
    if (blockIdx.x == 1 && threadIdx.x < 128) g_pcnt[threadIdx.x] = 0;
    const uint4* src = reinterpret_cast<const uint4*>(x + (size_t)row * DM);
    uint4 v[2];
    v[0] = src[lane];
    v[1] = src[lane + 32];
    float f[16];
#pragma unroll
    for (int i = 0; i < 2; i++) {
        const __nv_bfloat162* p = reinterpret_cast<const __nv_bfloat162*>(&v[i]);
#pragma unroll
        for (int j = 0; j < 4; j++) {
            float2 t = __bfloat1622float2(p[j]);
            f[i * 8 + j * 2] = t.x;
            f[i * 8 + j * 2 + 1] = t.y;
        }
    }
    float s = 0.f;
#pragma unroll
    for (int i = 0; i < 16; i++) s += f[i];
#pragma unroll
    for (int o = 16; o > 0; o >>= 1) s += __shfl_xor_sync(0xffffffffu, s, o);
    float mean = s * (1.0f / DM);
    float q = 0.f;
#pragma unroll
    for (int i = 0; i < 16; i++) {
        float d = f[i] - mean;
        q += d * d;
    }
#pragma unroll
    for (int o = 16; o > 0; o >>= 1) q += __shfl_xor_sync(0xffffffffu, q, o);
    float var_b = bf16_round(q * (1.0f / DM));
    float mean_b = bf16_round(mean);
    float den = bf16_round(sqrtf(bf16_round(var_b + 1e-5f)));
    uint4 o[2];
#pragma unroll
    for (int i = 0; i < 2; i++) {
        uint32_t* p = reinterpret_cast<uint32_t*>(&o[i]);
#pragma unroll
        for (int j = 0; j < 4; j++) {
            float a = bf16_round(f[i * 8 + j * 2] - mean_b) / den;
            float b = bf16_round(f[i * 8 + j * 2 + 1] - mean_b) / den;
            p[j] = pack_bf16(a, b);
        }
    }
    uint4* dst = reinterpret_cast<uint4*>(g_xn + (size_t)row * DM);
    dst[lane] = o[0];
    dst[lane + 32] = o[1];
}

constexpr int AT_STAGES = 3;
constexpr int TILE_BYTES = 128 * 128 * 2;
struct __align__(1024) AttnSmem {
    uint8_t k[AT_STAGES][TILE_BYTES];
    uint8_t v[AT_STAGES][TILE_BYTES];
    uint8_t o[TILE_BYTES];
    uint64_t full_k[AT_STAGES], full_v[AT_STAGES], empty_k[AT_STAGES], empty_v[AT_STAGES];
};

constexpr int NUM_CTAS = 132;
constexpr int MAX_ITEMS = 12;
enum { T_ATT = 0, T_F1 = 1, T_F2 = 2 };
struct Sched {
    uint16_t item[NUM_CTAS][MAX_ITEMS];
    uint8_t count[NUM_CTAS];
};

__global__ void __launch_bounds__(384, 1)
attn_kernel(const __grid_constant__ CUtensorMap tm_xn, const __grid_constant__ CUtensorMap tm_wq,
            const __grid_constant__ CUtensorMap tm_k, const __grid_constant__ CUtensorMap tm_v,
            const __grid_constant__ CUtensorMap tm_o, const __grid_constant__ CUtensorMap tm_w1,
            const __grid_constant__ CUtensorMap tm_hst, const __grid_constant__ CUtensorMap tm_hld,
            const __grid_constant__ CUtensorMap tm_w2, const __grid_constant__ CUtensorMap tm_gst,
            const __grid_constant__ Sched sched) {
    extern __shared__ uint8_t smem_raw[];
    AttnSmem& sm = *reinterpret_cast<AttnSmem*>((reinterpret_cast<uintptr_t>(smem_raw) + 1023) & ~uintptr_t(1023));
    const int tid = threadIdx.x;
    const int wg = tid >> 7;
    const int n_items = sched.count[blockIdx.x];

    if (tid == 0) {
#pragma unroll
        for (int s = 0; s < AT_STAGES; s++) {
            mbar_init(smem_u32(&sm.full_k[s]), 1);
            mbar_init(smem_u32(&sm.full_v[s]), 1);
            mbar_init(smem_u32(&sm.empty_k[s]), 8);
            mbar_init(smem_u32(&sm.empty_v[s]), 8);
        }
        asm volatile("fence.mbarrier_init.release.cluster;" ::: "memory");
    }
    __syncthreads();

    if (wg == 0) {
        reg_dealloc<24>();
        if (tid == 0) {
            int stage = 0;
            uint32_t phase = 0;
            for (int it = 0; it < n_items; it++) {
                const int item = sched.item[blockIdx.x][it];
                const int type = item >> 12, a = (item >> 4) & 0xff, b = item & 15;
                const CUtensorMap* ta = (type == T_F2) ? &tm_hld : &tm_xn;
                const CUtensorMap* tb = (type == T_ATT) ? &tm_wq : (type == T_F1 ? &tm_w1 : &tm_w2);
                const int nch = (type == T_F2) ? FF / 128 : DM / 128;
                if (type == T_F2) {
                    unsigned int v, spins = 0;
                    do {
                        asm volatile("ld.acquire.gpu.global.u32 %0, [%1];" : "=r"(v) : "l"(&g_hcnt[b]) : "memory");
                    } while (v < 2 * (FF / 128) && ++spins < (1u << 24));
                    asm volatile("fence.proxy.async;" ::: "memory");
                }
                for (int kc = 0; kc < nch; kc++) {
                    mbar_wait(smem_u32(&sm.empty_k[stage]), phase ^ 1);
                    mbar_expect_tx(smem_u32(&sm.full_k[stage]), TILE_BYTES);
                    tma_load_3d(smem_u32(sm.k[stage]), ta, smem_u32(&sm.full_k[stage]), 0, b * 128, kc * 2);
                    mbar_wait(smem_u32(&sm.empty_v[stage]), phase ^ 1);
                    mbar_expect_tx(smem_u32(&sm.full_v[stage]), TILE_BYTES);
                    tma_load_3d(smem_u32(sm.v[stage]), tb, smem_u32(&sm.full_v[stage]), 0, kc * 128, a * 2);
                    if (++stage == AT_STAGES) { stage = 0; phase ^= 1; }
                }
                if (type == T_ATT) {
                    for (int j = 0; j < 16; j++) {
                        mbar_wait(smem_u32(&sm.empty_k[stage]), phase ^ 1);
                        mbar_expect_tx(smem_u32(&sm.full_k[stage]), TILE_BYTES);
                        tma_load_3d(smem_u32(sm.k[stage]), &tm_k, smem_u32(&sm.full_k[stage]), 0, a * SEQ + j * 128, 0);
                        mbar_wait(smem_u32(&sm.empty_v[stage]), phase ^ 1);
                        mbar_expect_tx(smem_u32(&sm.full_v[stage]), TILE_BYTES);
                        tma_load_3d(smem_u32(sm.v[stage]), &tm_v, smem_u32(&sm.full_v[stage]), 0, a * SEQ + j * 128, 0);
                        if (++stage == AT_STAGES) { stage = 0; phase ^= 1; }
                    }
                }
            }
        }
    } else {
        reg_alloc<240>();
        const int cw = wg - 1;
        const int lane = tid & 31;
        const int warp_in_wg = (tid >> 5) & 3;
        const float c = 1.4426950408889634f;
        const uint32_t SCALE_HI2 = 0x3DB53DB5u, SCALE_LO2 = 0x371E371Eu;
        constexpr int BAR_SCHED0 = 1, BAR_EPI0 = 3;
        const uint32_t obase = smem_u32(sm.o) + cw * 16384;
        const int st_row = warp_in_wg * 16 + ((lane >> 3) & 1) * 8 + (lane & 7);

        if (cw == 1) named_arrive(BAR_SCHED0 + 0, 256);

        int stage = 0;
        uint32_t phase = 0;
        int pending_mb = -1;
        float S[64], O[64];
        uint32_t P[32];

        for (int it = 0; it < n_items; it++) {
            const int item = sched.item[blockIdx.x][it];
            const int type = item >> 12, ia = (item >> 4) & 0xff, ib = item & 15;
            const int nch = (type == T_F2) ? FF / 128 : DM / 128;
            {
                int prev = -1;
#pragma unroll 1
                for (int kc = 0; kc < nch; kc++) {
                    mbar_wait(smem_u32(&sm.full_k[stage]), phase);
                    mbar_wait(smem_u32(&sm.full_v[stage]), phase);
                    const uint64_t da = make_desc(smem_u32(sm.k[stage]) + cw * 64 * 128, 16, 1024);
                    const uint64_t db = make_desc(smem_u32(sm.v[stage]), 16384, 1024);
                    wgmma_fence();
#pragma unroll
                    for (int kk = 0; kk < 8; kk++) {
                        wgmma_ss_n128<1>(S, da + (uint64_t)(((kk >> 2) * 16384 + (kk & 3) * 32) >> 4),
                                         db + (uint64_t)((kk * 2048) >> 4), (kc | kk) != 0);
                    }
                    wgmma_commit();
                    wgmma_wait<1>();
                    if (prev >= 0 && lane == 0) {
                        mbar_arrive(smem_u32(&sm.empty_k[prev]));
                        mbar_arrive(smem_u32(&sm.empty_v[prev]));
                    }
                    prev = stage;
                    if (++stage == AT_STAGES) { stage = 0; phase ^= 1; }
                }
                wgmma_wait<0>();
                if (lane == 0) {
                    mbar_arrive(smem_u32(&sm.empty_k[prev]));
                    mbar_arrive(smem_u32(&sm.empty_v[prev]));
                }
            }
            if (type != T_ATT) {
#pragma unroll
                for (int i = 0; i < 64; i++) S[i] = silu_f(bf16_round(S[i]));
            }
            if ((tid & 127) == 0) {
                if (pending_mb >= 0) {
                    tma_wait_all0();
                    asm volatile("fence.proxy.async;" ::: "memory");
                    __threadfence();
                    atomicAdd(&g_hcnt[pending_mb], 1u);
                } else {
                    tma_wait_read0();
                }
            }
            pending_mb = -1;
            named_sync(BAR_EPI0 + cw, 128);
#pragma unroll
            for (int i = 0; i < 16; i += 2) {
                const int cc = i + (lane >> 4);
                const uint32_t addr = obase + (cc >> 3) * 8192 + st_row * 128 + (((cc & 7) ^ (st_row & 7)) << 4);
                stmatrix_x4(addr, pack_bf16(S[4 * i], S[4 * i + 1]), pack_bf16(S[4 * i + 2], S[4 * i + 3]),
                            pack_bf16(S[4 * i + 4], S[4 * i + 5]), pack_bf16(S[4 * i + 6], S[4 * i + 7]));
            }
            fence_proxy_async();
            named_sync(BAR_EPI0 + cw, 128);
            if (type != T_ATT) {
                if ((tid & 127) == 0) {
                    tma_store_3d(type == T_F1 ? &tm_hst : &tm_gst, obase, 0, ib * 128 + cw * 64, ia * 2);
                    tma_commit();
                }
                if (type == T_F1) pending_mb = ib;
                continue;
            }
            const uint64_t dq = make_desc(obase, 16, 1024);
#pragma unroll
            for (int i = 0; i < 64; i++) O[i] = 0.f;

            float m0 = -INFINITY, m1 = -INFINITY, l0 = 0.f, l1 = 0.f, a0 = 0.f, a1 = 0.f;

            {
                mbar_wait(smem_u32(&sm.full_k[stage]), phase);
                const uint64_t dk = make_desc(smem_u32(sm.k[stage]), 16, 1024);
                named_sync(BAR_SCHED0 + cw, 256);
                wgmma_fence();
#pragma unroll
                for (int kk = 0; kk < 8; kk++)
                    wgmma_ss_n128<0>(S, dq + (uint64_t)(((kk >> 2) * 8192 + (kk & 3) * 32) >> 4),
                                     dk + (uint64_t)(((kk >> 2) * 16384 + (kk & 3) * 32) >> 4), kk != 0);
                wgmma_commit();
                named_arrive(BAR_SCHED0 + (cw ^ 1), 256);
                wgmma_wait<0>();
                if (lane == 0) mbar_arrive(smem_u32(&sm.empty_k[stage]));
            }
            int vstage = stage;
            uint32_t vphase = phase;
            if (++stage == AT_STAGES) { stage = 0; phase ^= 1; }

            auto softmax = [&]() {
                uint32_t T[32];
#pragma unroll
                for (int i = 0; i < 32; i++) {
                    const uint32_t sb = pack_bf16(S[2 * i], S[2 * i + 1]);
                    T[i] = fma_bf16x2(sb, SCALE_HI2, mul_bf16x2(sb, SCALE_LO2));
                }
                uint32_t y0 = max_bf16x2(T[0], T[2]), y1 = max_bf16x2(T[1], T[3]);
#pragma unroll
                for (int i = 2; i < 16; i++) {
                    y0 = max_bf16x2(y0, T[2 * i]);
                    y1 = max_bf16x2(y1, T[2 * i + 1]);
                }
                float x0 = fmaxf(m0, fmaxf(bf16lo(y0), bf16hi(y0)));
                float x1 = fmaxf(m1, fmaxf(bf16lo(y1), bf16hi(y1)));
                x0 = fmaxf(x0, __shfl_xor_sync(0xffffffffu, x0, 1));
                x1 = fmaxf(x1, __shfl_xor_sync(0xffffffffu, x1, 1));
                x0 = fmaxf(x0, __shfl_xor_sync(0xffffffffu, x0, 2));
                x1 = fmaxf(x1, __shfl_xor_sync(0xffffffffu, x1, 2));
                a0 = ex2((m0 - x0) * c);
                a1 = ex2((m1 - x1) * c);
                m0 = x0;
                m1 = x1;
                const float n0 = -x0 * c, n1 = -x1 * c;
                float s0 = 0.f, s1 = 0.f;
#pragma unroll
                for (int i = 0; i < 16; i++) {
                    S[4 * i] = ex2(fmaf(bf16lo(T[2 * i]), c, n0));
                    S[4 * i + 1] = ex2(fmaf(bf16hi(T[2 * i]), c, n0));
                    S[4 * i + 2] = ex2(fmaf(bf16lo(T[2 * i + 1]), c, n1));
                    S[4 * i + 3] = ex2(fmaf(bf16hi(T[2 * i + 1]), c, n1));
                    s0 += S[4 * i] + S[4 * i + 1];
                    s1 += S[4 * i + 2] + S[4 * i + 3];
                }
                l0 = l0 * a0 + s0;
                l1 = l1 * a1 + s1;
                while (s0 + s1 < 0.f) s0 = g_dummy;
            };
            softmax();
#pragma unroll
            for (int i = 0; i < 32; i++) P[i] = pack_bf16(S[2 * i], S[2 * i + 1]);

#pragma unroll 1
            for (int j = 1; j < 16; j++) {
                mbar_wait(smem_u32(&sm.full_k[stage]), phase);
                const uint64_t dk = make_desc(smem_u32(sm.k[stage]), 16, 1024);
                const uint64_t dv = make_desc(smem_u32(sm.v[vstage]), 16384, 1024);
                named_sync(BAR_SCHED0 + cw, 256);
                wgmma_fence();
#pragma unroll
                for (int kk = 0; kk < 8; kk++)
                    wgmma_ss_n128<0>(S, dq + (uint64_t)(((kk >> 2) * 8192 + (kk & 3) * 32) >> 4),
                                     dk + (uint64_t)(((kk >> 2) * 16384 + (kk & 3) * 32) >> 4), kk != 0);
                wgmma_commit();
#pragma unroll
                for (int i = 0; i < 16; i++) {
                    O[4 * i] *= a0;
                    O[4 * i + 1] *= a0;
                    O[4 * i + 2] *= a1;
                    O[4 * i + 3] *= a1;
                }
                mbar_wait(smem_u32(&sm.full_v[vstage]), vphase);
                wgmma_fence();
#pragma unroll
                for (int kk = 0; kk < 8; kk++)
                    wgmma_rs_n128<1>(O, P[4 * kk], P[4 * kk + 1], P[4 * kk + 2], P[4 * kk + 3],
                                     dv + (uint64_t)((kk * 2048) >> 4), 1);
                wgmma_commit();
                named_arrive(BAR_SCHED0 + (cw ^ 1), 256);
                wgmma_wait<1>();
                if (lane == 0) mbar_arrive(smem_u32(&sm.empty_k[stage]));
                softmax();
                wgmma_wait<0>();
                if (lane == 0) mbar_arrive(smem_u32(&sm.empty_v[vstage]));
#pragma unroll
                for (int i = 0; i < 32; i++) P[i] = pack_bf16(S[2 * i], S[2 * i + 1]);
                vstage = stage;
                vphase = phase;
                if (++stage == AT_STAGES) { stage = 0; phase ^= 1; }
            }
            {
#pragma unroll
                for (int i = 0; i < 16; i++) {
                    O[4 * i] *= a0;
                    O[4 * i + 1] *= a0;
                    O[4 * i + 2] *= a1;
                    O[4 * i + 3] *= a1;
                }
                const uint64_t dv = make_desc(smem_u32(sm.v[vstage]), 16384, 1024);
                mbar_wait(smem_u32(&sm.full_v[vstage]), vphase);
                wgmma_fence();
#pragma unroll
                for (int kk = 0; kk < 8; kk++)
                    wgmma_rs_n128<1>(O, P[4 * kk], P[4 * kk + 1], P[4 * kk + 2], P[4 * kk + 3],
                                     dv + (uint64_t)((kk * 2048) >> 4), 1);
                wgmma_commit();
                wgmma_wait<0>();
                if (lane == 0) mbar_arrive(smem_u32(&sm.empty_v[vstage]));
            }
            l0 += __shfl_xor_sync(0xffffffffu, l0, 1);
            l1 += __shfl_xor_sync(0xffffffffu, l1, 1);
            l0 += __shfl_xor_sync(0xffffffffu, l0, 2);
            l1 += __shfl_xor_sync(0xffffffffu, l1, 2);
            const float i0 = 1.0f / l0, i1 = 1.0f / l1;
            named_sync(BAR_EPI0 + cw, 128);
#pragma unroll
            for (int i = 0; i < 16; i += 2) {
                const int cc = i + (lane >> 4);
                const uint32_t addr = obase + (cc >> 3) * 8192 + st_row * 128 + (((cc & 7) ^ (st_row & 7)) << 4);
                stmatrix_x4(addr, pack_bf16(O[4 * i] * i0, O[4 * i + 1] * i0), pack_bf16(O[4 * i + 2] * i1, O[4 * i + 3] * i1),
                            pack_bf16(O[4 * i + 4] * i0, O[4 * i + 5] * i0), pack_bf16(O[4 * i + 6] * i1, O[4 * i + 7] * i1));
            }
            fence_proxy_async();
            named_sync(BAR_EPI0 + cw, 128);
            if ((tid & 127) == 0) {
                tma_store_3d(&tm_o, obase, 0, ib * 128 + cw * 64, ia * 2);
                tma_commit();
            }
        }
        if ((tid & 127) == 0) {
            tma_wait_all0();
            if (pending_mb >= 0) {
                asm volatile("fence.proxy.async;" ::: "memory");
                __threadfence();
                atomicAdd(&g_hcnt[pending_mb], 1u);
            }
        }
    }
}

constexpr int OP_STAGES = 4;
constexpr int OP_KSPLIT = 4;
struct __align__(1024) OpSmem {
    uint8_t a[OP_STAGES][128 * 64 * 2];
    uint8_t b[OP_STAGES][64 * 256 * 2];
    uint64_t full[OP_STAGES], empty[OP_STAGES];
};

#define ACC8(d, o) "+f"(d[o]), "+f"(d[o + 1]), "+f"(d[o + 2]), "+f"(d[o + 3]), "+f"(d[o + 4]), "+f"(d[o + 5]), "+f"(d[o + 6]), "+f"(d[o + 7])
__device__ __forceinline__ void wgmma_ss_n256_tb(float (&d)[128], uint64_t da, uint64_t db, int scale_d) {
    asm volatile(
        "{\n.reg .pred p;\nsetp.ne.b32 p, %130, 0;\n"
        "wgmma.mma_async.sync.aligned.m64n256k16.f32.bf16.bf16 "
        "{%0, %1, %2, %3, %4, %5, %6, %7, %8, %9, %10, %11, %12, %13, %14, %15, "
        "%16, %17, %18, %19, %20, %21, %22, %23, %24, %25, %26, %27, %28, %29, %30, %31, "
        "%32, %33, %34, %35, %36, %37, %38, %39, %40, %41, %42, %43, %44, %45, %46, %47, "
        "%48, %49, %50, %51, %52, %53, %54, %55, %56, %57, %58, %59, %60, %61, %62, %63, "
        "%64, %65, %66, %67, %68, %69, %70, %71, %72, %73, %74, %75, %76, %77, %78, %79, "
        "%80, %81, %82, %83, %84, %85, %86, %87, %88, %89, %90, %91, %92, %93, %94, %95, "
        "%96, %97, %98, %99, %100, %101, %102, %103, %104, %105, %106, %107, %108, %109, %110, %111, "
        "%112, %113, %114, %115, %116, %117, %118, %119, %120, %121, %122, %123, %124, %125, %126, %127}, "
        "%128, %129, p, 1, 1, 0, 1;\n}\n"
        : ACC8(d, 0), ACC8(d, 8), ACC8(d, 16), ACC8(d, 24), ACC8(d, 32), ACC8(d, 40), ACC8(d, 48), ACC8(d, 56),
          ACC8(d, 64), ACC8(d, 72), ACC8(d, 80), ACC8(d, 88), ACC8(d, 96), ACC8(d, 104), ACC8(d, 112), ACC8(d, 120)
        : "l"(da), "l"(db), "r"(scale_d));
}
__device__ __forceinline__ void cluster_sync_all() {
    asm volatile("barrier.cluster.arrive.release.aligned;\nbarrier.cluster.wait.acquire.aligned;" ::: "memory");
}

__global__ void __launch_bounds__(384, 1)
oproj_kernel(const __grid_constant__ CUtensorMap tm_o, const __grid_constant__ CUtensorMap tm_wo,
             const bf16* __restrict__ x, bf16* __restrict__ out) {
    extern __shared__ uint8_t smem_raw[];
    OpSmem& sm = *reinterpret_cast<OpSmem*>((reinterpret_cast<uintptr_t>(smem_raw) + 1023) & ~uintptr_t(1023));
    const int tid = threadIdx.x, wg = tid >> 7;
    const int kr = blockIdx.x;
    const int n0 = blockIdx.y * 256, m0 = blockIdx.z * 128;
    const int tile = blockIdx.y + 2 * blockIdx.z;
    constexpr int KT = NH * DH / OP_KSPLIT / 64;
    if (tid == 0) {
        for (int s = 0; s < OP_STAGES; s++) {
            mbar_init(smem_u32(&sm.full[s]), 1);
            mbar_init(smem_u32(&sm.empty[s]), 8);
        }
        asm volatile("fence.mbarrier_init.release.cluster;" ::: "memory");
    }
    __syncthreads();
    if (wg == 0) {
        reg_dealloc<40>();
        if (tid == 0) {
            int stage = 0;
            uint32_t phase = 0;
            for (int kt = 0; kt < KT; kt++) {
                const int kg = kr * KT + kt;
                mbar_wait(smem_u32(&sm.empty[stage]), phase ^ 1);
                mbar_expect_tx(smem_u32(&sm.full[stage]), 49152);
                tma_load_3d(smem_u32(sm.a[stage]), &tm_o, smem_u32(&sm.full[stage]), 0, m0, kg);
                tma_load_3d(smem_u32(sm.b[stage]), &tm_wo, smem_u32(&sm.full[stage]), 0, kg * 64, n0 >> 6);
                if (++stage == OP_STAGES) { stage = 0; phase ^= 1; }
            }
        }
    } else {
        reg_alloc<232>();
        const int cw = wg - 1, lane = tid & 31, warp_in_wg = (tid >> 5) & 3;
        const int ct = tid - 128;
        float acc[128];
        const int r0 = m0 + cw * 64 + warp_in_wg * 16 + (lane >> 2);
        uint32_t xv[16], gv[16];
#pragma unroll
        for (int j = 0; j < 8; j++) {
#pragma unroll
            for (int hh = 0; hh < 2; hh++) {
                const size_t off = (size_t)(r0 + hh * 8) * DM + n0 + kr * 64 + j * 8 + (lane & 3) * 2;
                xv[2 * j + hh] = *reinterpret_cast<const uint32_t*>(x + off);
                gv[2 * j + hh] = *reinterpret_cast<const uint32_t*>(g_g + off);
            }
        }
        int stage = 0, prev = -1;
        uint32_t phase = 0;
#pragma unroll 1
        for (int kt = 0; kt < KT; kt++) {
            mbar_wait(smem_u32(&sm.full[stage]), phase);
            const uint64_t da = make_desc(smem_u32(sm.a[stage]) + cw * 64 * 128, 16, 1024);
            const uint64_t db = make_desc(smem_u32(sm.b[stage]), 8192, 1024);
            wgmma_fence();
#pragma unroll
            for (int kk = 0; kk < 4; kk++)
                wgmma_ss_n256_tb(acc, da + (uint64_t)((kk * 32) >> 4), db + (uint64_t)((kk * 2048) >> 4), (kt | kk) != 0);
            wgmma_commit();
            wgmma_wait<1>();
            if (prev >= 0 && lane == 0) mbar_arrive(smem_u32(&sm.empty[prev]));
            prev = stage;
            if (++stage == OP_STAGES) { stage = 0; phase ^= 1; }
        }
        wgmma_wait<0>();
        float4* part = g_part + (size_t)tile * (OP_KSPLIT * OP_KSPLIT * 8 * 256);
#pragma unroll
        for (int d = 0; d < OP_KSPLIT; d++) {
            if (d == kr) continue;
#pragma unroll
            for (int j = 0; j < 8; j++)
                __stcg(part + ((d * OP_KSPLIT + kr) * 8 + j) * 256 + ct,
                       make_float4(acc[(8 * d + j) * 4], acc[(8 * d + j) * 4 + 1], acc[(8 * d + j) * 4 + 2], acc[(8 * d + j) * 4 + 3]));
        }
        __threadfence();
        named_sync(1, 256);
        if (ct < OP_KSPLIT && ct != kr)
            asm volatile("red.release.gpu.global.add.u32 [%0], 1;" ::"l"(&g_pcnt[tile * OP_KSPLIT + ct]) : "memory");
        float r[32];
#pragma unroll
        for (int d = 0; d < OP_KSPLIT; d++) {
            if (d == kr) {
#pragma unroll
                for (int i = 0; i < 32; i++) r[i] = acc[32 * d + i];
            }
        }
        if (ct == 0) {
            unsigned int v, spins = 0;
            do {
                asm volatile("ld.acquire.gpu.global.u32 %0, [%1];" : "=r"(v) : "l"(&g_pcnt[tile * OP_KSPLIT + kr]) : "memory");
            } while (v < OP_KSPLIT - 1 && ++spins < (1u << 24));
        }
        named_sync(1, 256);
#pragma unroll
        for (int sr = 0; sr < OP_KSPLIT; sr++) {
            if (sr == kr) continue;
#pragma unroll
            for (int j = 0; j < 8; j++) {
                const float4 v = __ldcg(part + ((kr * OP_KSPLIT + sr) * 8 + j) * 256 + ct);
                r[4 * j] += v.x;
                r[4 * j + 1] += v.y;
                r[4 * j + 2] += v.z;
                r[4 * j + 3] += v.w;
            }
        }
#pragma unroll
        for (int j = 0; j < 8; j++) {
#pragma unroll
            for (int hh = 0; hh < 2; hh++) {
                const size_t off = (size_t)(r0 + hh * 8) * DM + n0 + kr * 64 + j * 8 + (lane & 3) * 2;
                const float s0 = bf16_round(r[4 * j + 2 * hh]), s1 = bf16_round(r[4 * j + 2 * hh + 1]);
                const float o0 = bf16lo(xv[2 * j + hh]) + bf16_round(s0 * bf16lo(gv[2 * j + hh]));
                const float o1 = bf16hi(xv[2 * j + hh]) + bf16_round(s1 * bf16hi(gv[2 * j + hh]));
                *reinterpret_cast<uint32_t*>(out + off) = pack_bf16(o0, o1);
            }
        }
    }
}

typedef CUresult (*EncodeFn)(CUtensorMap*, CUtensorMapDataType, cuuint32_t, void*, const cuuint64_t*, const cuuint64_t*,
                             const cuuint32_t*, const cuuint32_t*, CUtensorMapInterleave, CUtensorMapSwizzle,
                             CUtensorMapL2promotion, CUtensorMapFloatOOBfill);

static CUtensorMap make_map(EncodeFn fn, const void* ptr, uint64_t rows, uint64_t cols, uint32_t box_rows, uint32_t box_blk) {
    CUtensorMap m;
    cuuint64_t dims[3] = {64, rows, cols / 64};
    cuuint64_t strides[2] = {cols * 2, 128};
    cuuint32_t box[3] = {64, box_rows, box_blk};
    cuuint32_t es[3] = {1, 1, 1};
    fn(&m, CU_TENSOR_MAP_DATA_TYPE_BFLOAT16, 3, const_cast<void*>(ptr), dims, strides, box, es, CU_TENSOR_MAP_INTERLEAVE_NONE,
       CU_TENSOR_MAP_SWIZZLE_128B, CU_TENSOR_MAP_L2_PROMOTION_L2_256B, CU_TENSOR_MAP_FLOAT_OOB_FILL_NONE);
    return m;
}

extern "C" void kernel_launch(void* const* d_in, const int* in_sizes, int n_in, void* d_out, int out_size) {
    const bf16* x = (const bf16*)d_in[0];
    const bf16* kc = (const bf16*)d_in[1];
    const bf16* vc = (const bf16*)d_in[2];
    const bf16* wq = (const bf16*)d_in[3];
    const bf16* wo = (const bf16*)d_in[4];
    const bf16* w1 = (const bf16*)d_in[6];
    const bf16* w2 = (const bf16*)d_in[7];
    bf16* out = (bf16*)d_out;

    static EncodeFn fn = nullptr;
    static void *p_xn = nullptr, *p_h = nullptr, *p_o = nullptr, *p_g = nullptr;
    static Sched sched;
    if (!fn) {
        void* f = nullptr;
        cudaDriverEntryPointQueryResult st;
        cudaGetDriverEntryPoint("cuTensorMapEncodeTiled", &f, cudaEnableDefault, &st);
        fn = (EncodeFn)f;
        cudaGetSymbolAddress(&p_xn, g_xn);
        cudaGetSymbolAddress(&p_h, g_h);
        cudaGetSymbolAddress(&p_o, g_o);
        cudaGetSymbolAddress(&p_g, g_g);
        cudaFuncSetAttribute(attn_kernel, cudaFuncAttributeMaxDynamicSharedMemorySize, (int)sizeof(AttnSmem) + 1024);
        cudaFuncSetAttribute(oproj_kernel, cudaFuncAttributeMaxDynamicSharedMemorySize, (int)sizeof(OpSmem) + 1024);
        static uint16_t f1[NUM_CTAS][MAX_ITEMS], at[NUM_CTAS][MAX_ITEMS], f2[NUM_CTAS][MAX_ITEMS];
        static int n1[NUM_CTAS], na[NUM_CTAS], n2[NUM_CTAS];
        static double load[NUM_CTAS];
        const double C_ATT = 58.0, C_F1 = 6.5, C_F2 = 19.5;
        for (int i = 0; i < NUM_CTAS; i++) { n1[i] = na[i] = n2[i] = 0; load[i] = 0; }
        for (int t = 0; t < NH * 16; t++) {
            int cta = t % NUM_CTAS;
            at[cta][na[cta]++] = (uint16_t)((T_ATT << 12) | ((t >> 4) << 4) | (t & 15));
            load[cta] += C_ATT;
        }
        auto least = [&]() { int bi = 0; for (int i = 1; i < NUM_CTAS; i++) if (load[i] < load[bi]) bi = i; return bi; };
        for (int t = 0; t < 64; t++) {
            int cta = least();
            f2[cta][n2[cta]++] = (uint16_t)((T_F2 << 12) | ((t & 3) << 4) | (t >> 2));
            load[cta] += C_F2;
        }
        for (int t = 0; t < 224; t++) {
            int cta = least();
            f1[cta][n1[cta]++] = (uint16_t)((T_F1 << 12) | ((t % 14) << 4) | (t / 14));
            load[cta] += C_F1;
        }
        for (int i = 0; i < NUM_CTAS; i++) {
            int n = 0;
            for (int j = 0; j < n1[i]; j++) sched.item[i][n++] = f1[i][j];
            for (int j = 0; j < na[i]; j++) sched.item[i][n++] = at[i][j];
            for (int j = 0; j < n2[i]; j++) sched.item[i][n++] = f2[i][j];
            sched.count[i] = (uint8_t)n;
        }
    }
    CUtensorMap tm_xn_at = make_map(fn, p_xn, SEQ, DM, 128, 2);
    CUtensorMap tm_wq = make_map(fn, wq, DM, NH * DH, 128, 2);
    CUtensorMap tm_k = make_map(fn, kc, NH * SEQ, DH, 128, 2);
    CUtensorMap tm_v = make_map(fn, vc, NH * SEQ, DH, 128, 2);
    CUtensorMap tm_o_st = make_map(fn, p_o, SEQ, NH * DH, 64, 2);
    CUtensorMap tm_w1 = make_map(fn, w1, DM, FF, 128, 2);
    CUtensorMap tm_h_st = make_map(fn, p_h, SEQ, FF, 64, 2);
    CUtensorMap tm_h_ld = make_map(fn, p_h, SEQ, FF, 128, 2);
    CUtensorMap tm_w2 = make_map(fn, w2, FF, DM, 128, 2);
    CUtensorMap tm_g_st = make_map(fn, p_g, SEQ, DM, 64, 2);
    CUtensorMap tm_o_g = make_map(fn, p_o, SEQ, NH * DH, 128, 1);
    CUtensorMap tm_wo = make_map(fn, wo, NH * DH, DM, 64, 4);

    ln_kernel<<<SEQ / 8, 256>>>(x);
    attn_kernel<<<NUM_CTAS, 384, sizeof(AttnSmem) + 1024>>>(tm_xn_at, tm_wq, tm_k, tm_v, tm_o_st, tm_w1, tm_h_st, tm_h_ld,
                                                            tm_w2, tm_g_st, sched);
    oproj_kernel<<<dim3(OP_KSPLIT, DM / 256, SEQ / 128), 384, sizeof(OpSmem) + 1024>>>(tm_o_g, tm_wo, x, out);
}
```

```cpp
#include <cuda_runtime.h>
#include <cuda_bf16.h>
#include <cuda.h>
#include <stdint.h>

typedef __nv_bfloat16 bf16;

constexpr int SEQ = 2048, DM = 512, NH = 32, DH = 128, FF = 1792;

__device__ __align__(1024) bf16 g_xn[SEQ * DM];
__device__ __align__(1024) bf16 g_h[SEQ * FF];
__device__ __align__(1024) bf16 g_o[SEQ * NH * DH];
__device__ __align__(1024) bf16 g_g[SEQ * DM];
__device__ unsigned int g_hcnt[SEQ / 128];
__device__ float4 g_part[32 * 16 * 8 * 256];
__device__ unsigned int g_pcnt[128];
__device__ volatile float g_dummy;

__device__ __forceinline__ uint32_t smem_u32(const void* p) { return (uint32_t)__cvta_generic_to_shared(p); }

__device__ __forceinline__ void mbar_init(uint32_t bar, uint32_t count) {
    asm volatile("mbarrier.init.shared::cta.b64 [%0], %1;" ::"r"(bar), "r"(count) : "memory");
}
__device__ __forceinline__ void mbar_expect_tx(uint32_t bar, uint32_t bytes) {
    asm volatile("mbarrier.arrive.expect_tx.shared::cta.b64 _, [%0], %1;" ::"r"(bar), "r"(bytes) : "memory");
}
__device__ __forceinline__ void mbar_arrive(uint32_t bar) {
    asm volatile("mbarrier.arrive.shared::cta.b64 _, [%0];" ::"r"(bar) : "memory");
}
__device__ __forceinline__ bool mbar_try_wait(uint32_t bar, uint32_t parity) {
    uint32_t ok;
    asm volatile(
        "{\n.reg .pred p;\n"
        "mbarrier.try_wait.parity.shared::cta.b64 p, [%1], %2;\n"
        "selp.u32 %0, 1, 0, p;\n}\n"
        : "=r"(ok)
        : "r"(bar), "r"(parity)
        : "memory");
    return ok != 0;
}
__device__ __forceinline__ void mbar_wait(uint32_t bar, uint32_t parity) {
    asm volatile(
        "{\n.reg .pred P1;\n.reg .u32 n;\nmov.u32 n, 0;\n"
        "LAB_WAIT:\n"
        "mbarrier.try_wait.parity.shared::cta.b64 P1, [%0], %1;\n"
        "@P1 bra DONE;\n"
        "add.u32 n, n, 1;\n"
        "setp.lt.u32 P1, n, 4194304;\n"
        "@P1 bra LAB_WAIT;\n"
        "trap;\n"
        "DONE:\n}\n" ::"r"(bar), "r"(parity)
        : "memory");
}
__device__ __forceinline__ void tma_load_3d(uint32_t dst, const CUtensorMap* map, uint32_t bar, int c0, int c1, int c2) {
    asm volatile(
        "cp.async.bulk.tensor.3d.shared::cluster.global.mbarrier::complete_tx::bytes [%0], [%1, {%3, %4, %5}], [%2];"
        ::"r"(dst), "l"((uint64_t)map), "r"(bar), "r"(c0), "r"(c1), "r"(c2)
        : "memory");
}
__device__ __forceinline__ void tma_store_3d(const CUtensorMap* map, uint32_t src, int c0, int c1, int c2) {
    asm volatile("cp.async.bulk.tensor.3d.global.shared::cta.bulk_group [%0, {%2, %3, %4}], [%1];"
                 ::"l"((uint64_t)map), "r"(src), "r"(c0), "r"(c1), "r"(c2)
                 : "memory");
}
__device__ __forceinline__ void tma_commit() { asm volatile("cp.async.bulk.commit_group;" ::: "memory"); }
__device__ __forceinline__ void tma_wait_read0() { asm volatile("cp.async.bulk.wait_group.read 0;" ::: "memory"); }
__device__ __forceinline__ void tma_wait_all0() { asm volatile("cp.async.bulk.wait_group 0;" ::: "memory"); }
__device__ __forceinline__ void fence_proxy_async() { asm volatile("fence.proxy.async.shared::cta;" ::: "memory"); }
__device__ __forceinline__ void prefetch_tmap(const CUtensorMap* map) {
    asm volatile("prefetch.tensormap [%0];" ::"l"((uint64_t)map) : "memory");
}
__device__ __forceinline__ void named_sync(int id, int n) { asm volatile("bar.sync %0, %1;" ::"r"(id), "r"(n) : "memory"); }
__device__ __forceinline__ void named_arrive(int id, int n) { asm volatile("bar.arrive %0, %1;" ::"r"(id), "r"(n) : "memory"); }

__device__ __forceinline__ void wgmma_fence() { asm volatile("wgmma.fence.sync.aligned;" ::: "memory"); }
__device__ __forceinline__ void wgmma_commit() { asm volatile("wgmma.commit_group.sync.aligned;" ::: "memory"); }
template <int N>
__device__ __forceinline__ void wgmma_wait() { asm volatile("wgmma.wait_group.sync.aligned %0;" ::"n"(N) : "memory"); }

template <int R>
__device__ __forceinline__ void reg_alloc() { asm volatile("setmaxnreg.inc.sync.aligned.u32 %0;" ::"n"(R)); }
template <int R>
__device__ __forceinline__ void reg_dealloc() { asm volatile("setmaxnreg.dec.sync.aligned.u32 %0;" ::"n"(R)); }

__device__ __forceinline__ uint64_t make_desc(uint32_t saddr, uint32_t lbo_bytes, uint32_t sbo_bytes) {
    uint64_t d = 0;
    d |= (uint64_t)((saddr & 0x3FFFF) >> 4);
    d |= (uint64_t)((lbo_bytes >> 4) & 0x3FFF) << 16;
    d |= (uint64_t)((sbo_bytes >> 4) & 0x3FFF) << 32;
    d |= (uint64_t)1 << 62;
    return d;
}

__device__ __forceinline__ float ex2(float x) {
    float y;
    asm volatile("ex2.approx.ftz.f32 %0, %1;" : "=f"(y) : "f"(x));
    return y;
}
__device__ __forceinline__ uint32_t pack_bf16(float lo, float hi) {
    uint32_t r;
    asm("cvt.rn.bf16x2.f32 %0, %1, %2;" : "=r"(r) : "f"(hi), "f"(lo));
    return r;
}
__device__ __forceinline__ uint32_t mul_bf16x2(uint32_t a, uint32_t b) {
    uint32_t r;
    asm("mul.rn.bf16x2 %0, %1, %2;" : "=r"(r) : "r"(a), "r"(b));
    return r;
}
__device__ __forceinline__ uint32_t fma_bf16x2(uint32_t a, uint32_t b, uint32_t c) {
    uint32_t r;
    asm("fma.rn.bf16x2 %0, %1, %2, %3;" : "=r"(r) : "r"(a), "r"(b), "r"(c));
    return r;
}
__device__ __forceinline__ uint32_t max_bf16x2(uint32_t a, uint32_t b) {
    uint32_t r;
    asm("max.bf16x2 %0, %1, %2;" : "=r"(r) : "r"(a), "r"(b));
    return r;
}
__device__ __forceinline__ float bf16lo(uint32_t v) { return __uint_as_float(v << 16); }
__device__ __forceinline__ float bf16hi(uint32_t v) { return __uint_as_float(v & 0xffff0000u); }
__device__ __forceinline__ float bf16_round(float x) { return __bfloat162float(__float2bfloat16_rn(x)); }
__device__ __forceinline__ float silu_f(float x) { return __fdividef(x, 1.0f + __expf(-x)); }

__device__ __forceinline__ void stmatrix_x4(uint32_t addr, uint32_t r0, uint32_t r1, uint32_t r2, uint32_t r3) {
    asm volatile("stmatrix.sync.aligned.m8n8.x4.shared.b16 [%0], {%1, %2, %3, %4};"
                 ::"r"(addr), "r"(r0), "r"(r1), "r"(r2), "r"(r3)
                 : "memory");
}

#define ACC64(d) \
    "+f"(d[0]), "+f"(d[1]), "+f"(d[2]), "+f"(d[3]), "+f"(d[4]), "+f"(d[5]), "+f"(d[6]), "+f"(d[7]), \
    "+f"(d[8]), "+f"(d[9]), "+f"(d[10]), "+f"(d[11]), "+f"(d[12]), "+f"(d[13]), "+f"(d[14]), "+f"(d[15]), \
    "+f"(d[16]), "+f"(d[17]), "+f"(d[18]), "+f"(d[19]), "+f"(d[20]), "+f"(d[21]), "+f"(d[22]), "+f"(d[23]), \
    "+f"(d[24]), "+f"(d[25]), "+f"(d[26]), "+f"(d[27]), "+f"(d[28]), "+f"(d[29]), "+f"(d[30]), "+f"(d[31]), \
    "+f"(d[32]), "+f"(d[33]), "+f"(d[34]), "+f"(d[35]), "+f"(d[36]), "+f"(d[37]), "+f"(d[38]), "+f"(d[39]), \
    "+f"(d[40]), "+f"(d[41]), "+f"(d[42]), "+f"(d[43]), "+f"(d[44]), "+f"(d[45]), "+f"(d[46]), "+f"(d[47]), \
    "+f"(d[48]), "+f"(d[49]), "+f"(d[50]), "+f"(d[51]), "+f"(d[52]), "+f"(d[53]), "+f"(d[54]), "+f"(d[55]), \
    "+f"(d[56]), "+f"(d[57]), "+f"(d[58]), "+f"(d[59]), "+f"(d[60]), "+f"(d[61]), "+f"(d[62]), "+f"(d[63])

#define ACC64_STR \
    "{%0, %1, %2, %3, %4, %5, %6, %7, %8, %9, %10, %11, %12, %13, %14, %15, " \
    "%16, %17, %18, %19, %20, %21, %22, %23, %24, %25, %26, %27, %28, %29, %30, %31, " \
    "%32, %33, %34, %35, %36, %37, %38, %39, %40, %41, %42, %43, %44, %45, %46, %47, " \
    "%48, %49, %50, %51, %52, %53, %54, %55, %56, %57, %58, %59, %60, %61, %62, %63}"

template <int TB>
__device__ __forceinline__ void wgmma_ss_n128(float (&d)[64], uint64_t da, uint64_t db, int scale_d) {
    asm volatile(
        "{\n.reg .pred p;\nsetp.ne.b32 p, %66, 0;\n"
        "wgmma.mma_async.sync.aligned.m64n128k16.f32.bf16.bf16 " ACC64_STR ", %64, %65, p, 1, 1, 0, %67;\n}\n"
        : ACC64(d)
        : "l"(da), "l"(db), "r"(scale_d), "n"(TB));
}
template <int TB>
__device__ __forceinline__ void wgmma_rs_n128(float (&d)[64], uint32_t a0, uint32_t a1, uint32_t a2, uint32_t a3,
                                              uint64_t db, int scale_d) {
    asm volatile(
        "{\n.reg .pred p;\nsetp.ne.b32 p, %69, 0;\n"
        "wgmma.mma_async.sync.aligned.m64n128k16.f32.bf16.bf16 " ACC64_STR ", {%64, %65, %66, %67}, %68, p, 1, 1, %70;\n}\n"
        : ACC64(d)
        : "r"(a0), "r"(a1), "r"(a2), "r"(a3), "l"(db), "r"(scale_d), "n"(TB));
}

__device__ __forceinline__ void wgmma_rs_n136_tb(float (&d)[68], uint32_t a0, uint32_t a1, uint32_t a2, uint32_t a3, uint64_t db) {
    asm volatile(
        "wgmma.mma_async.sync.aligned.m64n136k16.f32.bf16.bf16 "
        "{%0, %1, %2, %3, %4, %5, %6, %7, %8, %9, %10, %11, %12, %13, %14, %15, "
        "%16, %17, %18, %19, %20, %21, %22, %23, %24, %25, %26, %27, %28, %29, %30, %31, "
        "%32, %33, %34, %35, %36, %37, %38, %39, %40, %41, %42, %43, %44, %45, %46, %47, "
        "%48, %49, %50, %51, %52, %53, %54, %55, %56, %57, %58, %59, %60, %61, %62, %63, "
        "%64, %65, %66, %67}, {%68, %69, %70, %71}, %72, 1, 1, 1, 1;\n"
        : ACC64(d), "+f"(d[64]), "+f"(d[65]), "+f"(d[66]), "+f"(d[67])
        : "r"(a0), "r"(a1), "r"(a2), "r"(a3), "l"(db));
}

__global__ void __launch_bounds__(256) ln_kernel(const bf16* __restrict__ x) {
    int warp = threadIdx.x >> 5, lane = threadIdx.x & 31;
    int row = blockIdx.x * 8 + warp;
    if (blockIdx.x == 0 && threadIdx.x < SEQ / 128) g_hcnt[threadIdx.x] = 0;
    if (blockIdx.x == 1 && threadIdx.x < 128) g_pcnt[threadIdx.x] = 0;
    const uint4* src = reinterpret_cast<const uint4*>(x + (size_t)row * DM);
    uint4 v[2];
    v[0] = src[lane];
    v[1] = src[lane + 32];
    float f[16];
#pragma unroll
    for (int i = 0; i < 2; i++) {
        const __nv_bfloat162* p = reinterpret_cast<const __nv_bfloat162*>(&v[i]);
#pragma unroll
        for (int j = 0; j < 4; j++) {
            float2 t = __bfloat1622float2(p[j]);
            f[i * 8 + j * 2] = t.x;
            f[i * 8 + j * 2 + 1] = t.y;
        }
    }
    float s = 0.f;
#pragma unroll
    for (int i = 0; i < 16; i++) s += f[i];
#pragma unroll
    for (int o = 16; o > 0; o >>= 1) s += __shfl_xor_sync(0xffffffffu, s, o);
    float mean = s * (1.0f / DM);
    float q = 0.f;
#pragma unroll
    for (int i = 0; i < 16; i++) {
        float d = f[i] - mean;
        q += d * d;
    }
#pragma unroll
    for (int o = 16; o > 0; o >>= 1) q += __shfl_xor_sync(0xffffffffu, q, o);
    float var_b = bf16_round(q * (1.0f / DM));
    float mean_b = bf16_round(mean);
    float den = bf16_round(sqrtf(bf16_round(var_b + 1e-5f)));
    uint4 o[2];
#pragma unroll
    for (int i = 0; i < 2; i++) {
        uint32_t* p = reinterpret_cast<uint32_t*>(&o[i]);
#pragma unroll
        for (int j = 0; j < 4; j++) {
            float a = bf16_round(f[i * 8 + j * 2] - mean_b) / den;
            float b = bf16_round(f[i * 8 + j * 2 + 1] - mean_b) / den;
            p[j] = pack_bf16(a, b);
        }
    }
    uint4* dst = reinterpret_cast<uint4*>(g_xn + (size_t)row * DM);
    dst[lane] = o[0];
    dst[lane + 32] = o[1];
}

constexpr int TILE_BYTES = 128 * 128 * 2;
constexpr int VSLOT_BYTES = TILE_BYTES + 16384;
struct __align__(1024) AttnSmem {
    uint8_t k[2][TILE_BYTES];
    uint8_t v[2][VSLOT_BYTES];
    uint8_t o[TILE_BYTES];
    uint64_t full_k[2], full_v[2], empty_k[2], empty_v[2];
};

constexpr int NUM_CTAS = 132;
constexpr int MAX_ITEMS = 12;
enum { T_ATT = 0, T_F1 = 1, T_F2 = 2 };
struct Sched {
    uint16_t item[NUM_CTAS][MAX_ITEMS];
    uint8_t count[NUM_CTAS];
};

__global__ void __launch_bounds__(384, 1)
attn_kernel(const __grid_constant__ CUtensorMap tm_xn, const __grid_constant__ CUtensorMap tm_wq,
            const __grid_constant__ CUtensorMap tm_k, const __grid_constant__ CUtensorMap tm_v,
            const __grid_constant__ CUtensorMap tm_o, const __grid_constant__ CUtensorMap tm_w1,
            const __grid_constant__ CUtensorMap tm_hst, const __grid_constant__ CUtensorMap tm_hld,
            const __grid_constant__ CUtensorMap tm_w2, const __grid_constant__ CUtensorMap tm_gst,
            const __grid_constant__ Sched sched) {
    extern __shared__ uint8_t smem_raw[];
    AttnSmem& sm = *reinterpret_cast<AttnSmem*>((reinterpret_cast<uintptr_t>(smem_raw) + 1023) & ~uintptr_t(1023));
    const int tid = threadIdx.x;
    const int wg = tid >> 7;
    const int n_items = sched.count[blockIdx.x];

    if (tid == 0) {
#pragma unroll
        for (int s = 0; s < 2; s++) {
            mbar_init(smem_u32(&sm.full_k[s]), 1);
            mbar_init(smem_u32(&sm.full_v[s]), 1);
            mbar_init(smem_u32(&sm.empty_k[s]), 8);
            mbar_init(smem_u32(&sm.empty_v[s]), 8);
        }
        asm volatile("fence.mbarrier_init.release.cluster;" ::: "memory");
    }
    for (int i = tid; i < 2 * 1024; i += 384) {
        *reinterpret_cast<uint4*>(sm.v[i >> 10] + TILE_BYTES + (i & 1023) * 16) =
            make_uint4(0x3F803F80u, 0x3F803F80u, 0x3F803F80u, 0x3F803F80u);
    }
    fence_proxy_async();
    __syncthreads();

    const uint32_t fk0 = smem_u32(&sm.full_k[0]), fv0 = smem_u32(&sm.full_v[0]);
    const uint32_t ek0 = smem_u32(&sm.empty_k[0]), ev0 = smem_u32(&sm.empty_v[0]);
    const uint32_t kb0 = smem_u32(sm.k[0]), vb0 = smem_u32(sm.v[0]);

    if (wg == 0) {
        reg_dealloc<24>();
        if (tid == 0) {
            uint32_t n = 0;
            for (int it = 0; it < n_items; it++) {
                const int item = sched.item[blockIdx.x][it];
                const int type = item >> 12, a = (item >> 4) & 0xff, b = item & 15;
                const CUtensorMap* ta = (type == T_F2) ? &tm_hld : &tm_xn;
                const CUtensorMap* tb = (type == T_ATT) ? &tm_wq : (type == T_F1 ? &tm_w1 : &tm_w2);
                const int nch = (type == T_F2) ? FF / 128 : DM / 128;
                if (type == T_F2) {
                    unsigned int v, spins = 0;
                    do {
                        asm volatile("ld.acquire.gpu.global.u32 %0, [%1];" : "=r"(v) : "l"(&g_hcnt[b]) : "memory");
                    } while (v < 2 * (FF / 128) && ++spins < (1u << 24));
                    asm volatile("fence.proxy.async;" ::: "memory");
                }
                for (int kc = 0; kc < nch; kc++, n++) {
                    const uint32_t st = n & 1, ph = ((n >> 1) & 1) ^ 1;
                    mbar_wait(ek0 + st * 8, ph);
                    mbar_expect_tx(fk0 + st * 8, TILE_BYTES);
                    tma_load_3d(kb0 + st * TILE_BYTES, ta, fk0 + st * 8, 0, b * 128, kc * 2);
                    mbar_wait(ev0 + st * 8, ph);
                    mbar_expect_tx(fv0 + st * 8, TILE_BYTES);
                    tma_load_3d(vb0 + st * VSLOT_BYTES, tb, fv0 + st * 8, 0, kc * 128, a * 2);
                }
                if (type == T_ATT) {
                    for (int j = 0; j < 16; j++, n++) {
                        const uint32_t st = n & 1, ph = ((n >> 1) & 1) ^ 1;
                        mbar_wait(ek0 + st * 8, ph);
                        mbar_expect_tx(fk0 + st * 8, TILE_BYTES);
                        tma_load_3d(kb0 + st * TILE_BYTES, &tm_k, fk0 + st * 8, 0, a * SEQ + j * 128, 0);
                        mbar_wait(ev0 + st * 8, ph);
                        mbar_expect_tx(fv0 + st * 8, TILE_BYTES);
                        tma_load_3d(vb0 + st * VSLOT_BYTES, &tm_v, fv0 + st * 8, 0, a * SEQ + j * 128, 0);
                    }
                }
            }
        }
    } else {
        reg_alloc<240>();
        const int cw = wg - 1;
        const int lane = tid & 31;
        const int warp_in_wg = (tid >> 5) & 3;
        const float c = 1.4426950408889634f;
        const uint32_t SCALE_HI2 = 0x3DB53DB5u, SCALE_LO2 = 0x371E371Eu;
        const float TAU = 11.0f;
        constexpr int BAR_SCHED0 = 1, BAR_EPI0 = 3;
        const uint32_t obase = smem_u32(sm.o) + cw * 16384;
        const int st_row = warp_in_wg * 16 + ((lane >> 3) & 1) * 8 + (lane & 7);
        const uint64_t dA = make_desc(kb0 + cw * 64 * 128, 16, 1024);
        const uint64_t dK = make_desc(kb0, 16, 1024);
        const uint64_t dV = make_desc(vb0, 16384, 1024);
        const uint64_t dq = make_desc(obase, 16, 1024);
        constexpr uint64_t KST = TILE_BYTES >> 4, VST = VSLOT_BYTES >> 4;

        if (cw == 1) named_arrive(BAR_SCHED0 + 0, 256);

        uint32_t ph = 0;
        int pending_mb = -1;
        float S[64], O[68];
        uint32_t P[32];

        for (int it = 0; it < n_items; it++) {
            const int item = sched.item[blockIdx.x][it];
            const int type = item >> 12, ia = (item >> 4) & 0xff, ib = item & 15;
            const int nch2 = (type == T_F2) ? FF / 256 : DM / 256;
#pragma unroll 1
            for (int k2 = 0; k2 < nch2; k2++) {
#pragma unroll
                for (int st = 0; st < 2; st++) {
                    mbar_wait(fk0 + st * 8, ph);
                    mbar_wait(fv0 + st * 8, ph);
                    wgmma_fence();
#pragma unroll
                    for (int kk = 0; kk < 8; kk++) {
                        wgmma_ss_n128<1>(S, dA + st * KST + (uint64_t)(((kk >> 2) * 16384 + (kk & 3) * 32) >> 4),
                                         dV + st * VST + (uint64_t)((kk * 2048) >> 4), (k2 | st | kk) != 0);
                    }
                    wgmma_commit();
                    wgmma_wait<1>();
                    if ((k2 | st) != 0 && lane == 0) {
                        mbar_arrive(ek0 + (st ^ 1) * 8);
                        mbar_arrive(ev0 + (st ^ 1) * 8);
                    }
                }
                ph ^= 1;
            }
            wgmma_wait<0>();
            if (lane == 0) {
                mbar_arrive(ek0 + 8);
                mbar_arrive(ev0 + 8);
            }
            if (type != T_ATT) {
#pragma unroll
                for (int i = 0; i < 64; i++) S[i] = silu_f(bf16_round(S[i]));
            }
            if ((tid & 127) == 0) {
                if (pending_mb >= 0) {
                    tma_wait_all0();
                    asm volatile("fence.proxy.async;" ::: "memory");
                    __threadfence();
                    atomicAdd(&g_hcnt[pending_mb], 1u);
                } else {
                    tma_wait_read0();
                }
            }
            pending_mb = -1;
            named_sync(BAR_EPI0 + cw, 128);
#pragma unroll
            for (int i = 0; i < 16; i += 2) {
                const int cc = i + (lane >> 4);
                const uint32_t addr = obase + (cc >> 3) * 8192 + st_row * 128 + (((cc & 7) ^ (st_row & 7)) << 4);
                stmatrix_x4(addr, pack_bf16(S[4 * i], S[4 * i + 1]), pack_bf16(S[4 * i + 2], S[4 * i + 3]),
                            pack_bf16(S[4 * i + 4], S[4 * i + 5]), pack_bf16(S[4 * i + 6], S[4 * i + 7]));
            }
            fence_proxy_async();
            named_sync(BAR_EPI0 + cw, 128);
            if (type != T_ATT) {
                if ((tid & 127) == 0) {
                    tma_store_3d(type == T_F1 ? &tm_hst : &tm_gst, obase, 0, ib * 128 + cw * 64, ia * 2);
                    tma_commit();
                }
                if (type == T_F1) pending_mb = ib;
                continue;
            }
#pragma unroll
            for (int i = 0; i < 68; i++) O[i] = 0.f;

            float r0 = -INFINITY, r1 = -INFINITY, a0 = 1.f, a1 = 1.f;
            bool resc = false;

            auto issue_qk = [&](int st) {
                mbar_wait(fk0 + st * 8, ph);
                named_sync(BAR_SCHED0 + cw, 256);
                wgmma_fence();
#pragma unroll
                for (int kk = 0; kk < 8; kk++)
                    wgmma_ss_n128<0>(S, dq + (uint64_t)(((kk >> 2) * 8192 + (kk & 3) * 32) >> 4),
                                     dK + st * KST + (uint64_t)(((kk >> 2) * 16384 + (kk & 3) * 32) >> 4), kk != 0);
                wgmma_commit();
            };
            auto issue_pv = [&](int st, uint32_t vph) {
                if (resc) {
#pragma unroll
                    for (int i = 0; i < 17; i++) {
                        O[4 * i] *= a0;
                        O[4 * i + 1] *= a0;
                        O[4 * i + 2] *= a1;
                        O[4 * i + 3] *= a1;
                    }
                }
                mbar_wait(fv0 + st * 8, vph);
                wgmma_fence();
#pragma unroll
                for (int kk = 0; kk < 8; kk++)
                    wgmma_rs_n136_tb(O, P[4 * kk], P[4 * kk + 1], P[4 * kk + 2], P[4 * kk + 3],
                                     dV + st * VST + (uint64_t)((kk * 2048) >> 4));
                wgmma_commit();
            };
            auto softmax = [&]() {
                uint32_t T[32];
#pragma unroll
                for (int i = 0; i < 32; i++) {
                    const uint32_t sb = pack_bf16(S[2 * i], S[2 * i + 1]);
                    T[i] = fma_bf16x2(sb, SCALE_HI2, mul_bf16x2(sb, SCALE_LO2));
                }
                uint32_t y0 = max_bf16x2(T[0], T[2]), y1 = max_bf16x2(T[1], T[3]);
#pragma unroll
                for (int i = 2; i < 16; i++) {
                    y0 = max_bf16x2(y0, T[2 * i]);
                    y1 = max_bf16x2(y1, T[2 * i + 1]);
                }
                float x0 = fmaxf(bf16lo(y0), bf16hi(y0));
                float x1 = fmaxf(bf16lo(y1), bf16hi(y1));
                x0 = fmaxf(x0, __shfl_xor_sync(0xffffffffu, x0, 1));
                x1 = fmaxf(x1, __shfl_xor_sync(0xffffffffu, x1, 1));
                x0 = fmaxf(x0, __shfl_xor_sync(0xffffffffu, x0, 2));
                x1 = fmaxf(x1, __shfl_xor_sync(0xffffffffu, x1, 2));
                resc = __any_sync(0xffffffffu, (x0 - r0 > TAU) || (x1 - r1 > TAU));
                if (resc) {
                    x0 = fmaxf(x0, r0);
                    x1 = fmaxf(x1, r1);
                    a0 = ex2((r0 - x0) * c);
                    a1 = ex2((r1 - x1) * c);
                    r0 = x0;
                    r1 = x1;
                }
                const float n0 = -r0 * c, n1 = -r1 * c;
#pragma unroll
                for (int i = 0; i < 16; i++) {
                    S[4 * i] = ex2(fmaf(bf16lo(T[2 * i]), c, n0));
                    S[4 * i + 1] = ex2(fmaf(bf16hi(T[2 * i]), c, n0));
                    S[4 * i + 2] = ex2(fmaf(bf16lo(T[2 * i + 1]), c, n1));
                    S[4 * i + 3] = ex2(fmaf(bf16hi(T[2 * i + 1]), c, n1));
                }
                while (S[63] + S[61] < 0.f) S[63] = g_dummy;
            };
            auto pack_p = [&]() {
#pragma unroll
                for (int i = 0; i < 32; i++) P[i] = pack_bf16(S[2 * i], S[2 * i + 1]);
            };
            auto step = [&](int st, uint32_t vph) {
                issue_qk(st);
                issue_pv(st ^ 1, vph);
                named_arrive(BAR_SCHED0 + (cw ^ 1), 256);
                wgmma_wait<1>();
                if (lane == 0) mbar_arrive(ek0 + st * 8);
                softmax();
                wgmma_wait<0>();
                if (lane == 0) mbar_arrive(ev0 + (st ^ 1) * 8);
                pack_p();
            };

            issue_qk(0);
            named_arrive(BAR_SCHED0 + (cw ^ 1), 256);
            wgmma_wait<0>();
            if (lane == 0) mbar_arrive(ek0);
            softmax();
            resc = false;
            pack_p();
#pragma unroll 1
            for (int j2 = 0; j2 < 7; j2++) {
                step(1, ph);
                ph ^= 1;
                step(0, ph ^ 1);
            }
            step(1, ph);
            issue_pv(1, ph);
            wgmma_wait<0>();
            if (lane == 0) mbar_arrive(ev0 + 8);
            ph ^= 1;
            const float i0 = 1.0f / O[64], i1 = 1.0f / O[66];
            named_sync(BAR_EPI0 + cw, 128);
#pragma unroll
            for (int i = 0; i < 16; i += 2) {
                const int cc = i + (lane >> 4);
                const uint32_t addr = obase + (cc >> 3) * 8192 + st_row * 128 + (((cc & 7) ^ (st_row & 7)) << 4);
                stmatrix_x4(addr, pack_bf16(O[4 * i] * i0, O[4 * i + 1] * i0), pack_bf16(O[4 * i + 2] * i1, O[4 * i + 3] * i1),
                            pack_bf16(O[4 * i + 4] * i0, O[4 * i + 5] * i0), pack_bf16(O[4 * i + 6] * i1, O[4 * i + 7] * i1));
            }
            fence_proxy_async();
            named_sync(BAR_EPI0 + cw, 128);
            if ((tid & 127) == 0) {
                tma_store_3d(&tm_o, obase, 0, ib * 128 + cw * 64, ia * 2);
                tma_commit();
            }
        }
        if ((tid & 127) == 0) {
            tma_wait_all0();
            if (pending_mb >= 0) {
                asm volatile("fence.proxy.async;" ::: "memory");
                __threadfence();
                atomicAdd(&g_hcnt[pending_mb], 1u);
            }
        }
    }
}

constexpr int OP_STAGES = 4;
constexpr int OP_KSPLIT = 4;
struct __align__(1024) OpSmem {
    uint8_t a[OP_STAGES][128 * 64 * 2];
    uint8_t b[OP_STAGES][64 * 256 * 2];
    uint64_t full[OP_STAGES], empty[OP_STAGES];
};

#define ACC8(d, o) "+f"(d[o]), "+f"(d[o + 1]), "+f"(d[o + 2]), "+f"(d[o + 3]), "+f"(d[o + 4]), "+f"(d[o + 5]), "+f"(d[o + 6]), "+f"(d[o + 7])
__device__ __forceinline__ void wgmma_ss_n256_tb(float (&d)[128], uint64_t da, uint64_t db, int scale_d) {
    asm volatile(
        "{\n.reg .pred p;\nsetp.ne.b32 p, %130, 0;\n"
        "wgmma.mma_async.sync.aligned.m64n256k16.f32.bf16.bf16 "
        "{%0, %1, %2, %3, %4, %5, %6, %7, %8, %9, %10, %11, %12, %13, %14, %15, "
        "%16, %17, %18, %19, %20, %21, %22, %23, %24, %25, %26, %27, %28, %29, %30, %31, "
        "%32, %33, %34, %35, %36, %37, %38, %39, %40, %41, %42, %43, %44, %45, %46, %47, "
        "%48, %49, %50, %51, %52, %53, %54, %55, %56, %57, %58, %59, %60, %61, %62, %63, "
        "%64, %65, %66, %67, %68, %69, %70, %71, %72, %73, %74, %75, %76, %77, %78, %79, "
        "%80, %81, %82, %83, %84, %85, %86, %87, %88, %89, %90, %91, %92, %93, %94, %95, "
        "%96, %97, %98, %99, %100, %101, %102, %103, %104, %105, %106, %107, %108, %109, %110, %111, "
        "%112, %113, %114, %115, %116, %117, %118, %119, %120, %121, %122, %123, %124, %125, %126, %127}, "
        "%128, %129, p, 1, 1, 0, 1;\n}\n"
        : ACC8(d, 0), ACC8(d, 8), ACC8(d, 16), ACC8(d, 24), ACC8(d, 32), ACC8(d, 40), ACC8(d, 48), ACC8(d, 56),
          ACC8(d, 64), ACC8(d, 72), ACC8(d, 80), ACC8(d, 88), ACC8(d, 96), ACC8(d, 104), ACC8(d, 112), ACC8(d, 120)
        : "l"(da), "l"(db), "r"(scale_d));
}
__device__ __forceinline__ void cluster_sync_all() {
    asm volatile("barrier.cluster.arrive.release.aligned;\nbarrier.cluster.wait.acquire.aligned;" ::: "memory");
}

__global__ void __launch_bounds__(384, 1)
oproj_kernel(const __grid_constant__ CUtensorMap tm_o, const __grid_constant__ CUtensorMap tm_wo,
             const bf16* __restrict__ x, bf16* __restrict__ out) {
    extern __shared__ uint8_t smem_raw[];
    OpSmem& sm = *reinterpret_cast<OpSmem*>((reinterpret_cast<uintptr_t>(smem_raw) + 1023) & ~uintptr_t(1023));
    const int tid = threadIdx.x, wg = tid >> 7;
    const int kr = blockIdx.x;
    const int n0 = blockIdx.y * 256, m0 = blockIdx.z * 128;
    const int tile = blockIdx.y + 2 * blockIdx.z;
    constexpr int KT = NH * DH / OP_KSPLIT / 64;
    if (tid == 0) {
        for (int s = 0; s < OP_STAGES; s++) {
            mbar_init(smem_u32(&sm.full[s]), 1);
            mbar_init(smem_u32(&sm.empty[s]), 8);
        }
        asm volatile("fence.mbarrier_init.release.cluster;" ::: "memory");
    }
    __syncthreads();
    if (wg == 0) {
        reg_dealloc<40>();
        if (tid == 0) {
            int stage = 0;
            uint32_t phase = 0;
            for (int kt = 0; kt < KT; kt++) {
                const int kg = kr * KT + kt;
                mbar_wait(smem_u32(&sm.empty[stage]), phase ^ 1);
                mbar_expect_tx(smem_u32(&sm.full[stage]), 49152);
                tma_load_3d(smem_u32(sm.a[stage]), &tm_o, smem_u32(&sm.full[stage]), 0, m0, kg);
                tma_load_3d(smem_u32(sm.b[stage]), &tm_wo, smem_u32(&sm.full[stage]), 0, kg * 64, n0 >> 6);
                if (++stage == OP_STAGES) { stage = 0; phase ^= 1; }
            }
        }
    } else {
        reg_alloc<232>();
        const int cw = wg - 1, lane = tid & 31, warp_in_wg = (tid >> 5) & 3;
        const int ct = tid - 128;
        float acc[128];
        const int r0 = m0 + cw * 64 + warp_in_wg * 16 + (lane >> 2);
        uint32_t xv[16], gv[16];
#pragma unroll
        for (int j = 0; j < 8; j++) {
#pragma unroll
            for (int hh = 0; hh < 2; hh++) {
                const size_t off = (size_t)(r0 + hh * 8) * DM + n0 + kr * 64 + j * 8 + (lane & 3) * 2;
                xv[2 * j + hh] = *reinterpret_cast<const uint32_t*>(x + off);
                gv[2 * j + hh] = *reinterpret_cast<const uint32_t*>(g_g + off);
            }
        }
        int stage = 0, prev = -1;
        uint32_t phase = 0;
#pragma unroll 1
        for (int kt = 0; kt < KT; kt++) {
            mbar_wait(smem_u32(&sm.full[stage]), phase);
            const uint64_t da = make_desc(smem_u32(sm.a[stage]) + cw * 64 * 128, 16, 1024);
            const uint64_t db = make_desc(smem_u32(sm.b[stage]), 8192, 1024);
            wgmma_fence();
#pragma unroll
            for (int kk = 0; kk < 4; kk++)
                wgmma_ss_n256_tb(acc, da + (uint64_t)((kk * 32) >> 4), db + (uint64_t)((kk * 2048) >> 4), (kt | kk) != 0);
            wgmma_commit();
            wgmma_wait<1>();
            if (prev >= 0 && lane == 0) mbar_arrive(smem_u32(&sm.empty[prev]));
            prev = stage;
            if (++stage == OP_STAGES) { stage = 0; phase ^= 1; }
        }
        wgmma_wait<0>();
        float4* part = g_part + (size_t)tile * (OP_KSPLIT * OP_KSPLIT * 8 * 256);
#pragma unroll
        for (int d = 0; d < OP_KSPLIT; d++) {
            if (d == kr) continue;
#pragma unroll
            for (int j = 0; j < 8; j++)
                __stcg(part + ((d * OP_KSPLIT + kr) * 8 + j) * 256 + ct,
                       make_float4(acc[(8 * d + j) * 4], acc[(8 * d + j) * 4 + 1], acc[(8 * d + j) * 4 + 2], acc[(8 * d + j) * 4 + 3]));
        }
        __threadfence();
        named_sync(1, 256);
        if (ct < OP_KSPLIT && ct != kr)
            asm volatile("red.release.gpu.global.add.u32 [%0], 1;" ::"l"(&g_pcnt[tile * OP_KSPLIT + ct]) : "memory");
        float r[32];
#pragma unroll
        for (int d = 0; d < OP_KSPLIT; d++) {
            if (d == kr) {
#pragma unroll
                for (int i = 0; i < 32; i++) r[i] = acc[32 * d + i];
            }
        }
        if (ct == 0) {
            unsigned int v, spins = 0;
            do {
                asm volatile("ld.acquire.gpu.global.u32 %0, [%1];" : "=r"(v) : "l"(&g_pcnt[tile * OP_KSPLIT + kr]) : "memory");
            } while (v < OP_KSPLIT - 1 && ++spins < (1u << 24));
        }
        named_sync(1, 256);
#pragma unroll
        for (int sr = 0; sr < OP_KSPLIT; sr++) {
            if (sr == kr) continue;
#pragma unroll
            for (int j = 0; j < 8; j++) {
                const float4 v = __ldcg(part + ((kr * OP_KSPLIT + sr) * 8 + j) * 256 + ct);
                r[4 * j] += v.x;
                r[4 * j + 1] += v.y;
                r[4 * j + 2] += v.z;
                r[4 * j + 3] += v.w;
            }
        }
#pragma unroll
        for (int j = 0; j < 8; j++) {
#pragma unroll
            for (int hh = 0; hh < 2; hh++) {
                const size_t off = (size_t)(r0 + hh * 8) * DM + n0 + kr * 64 + j * 8 + (lane & 3) * 2;
                const float s0 = bf16_round(r[4 * j + 2 * hh]), s1 = bf16_round(r[4 * j + 2 * hh + 1]);
                const float o0 = bf16lo(xv[2 * j + hh]) + bf16_round(s0 * bf16lo(gv[2 * j + hh]));
                const float o1 = bf16hi(xv[2 * j + hh]) + bf16_round(s1 * bf16hi(gv[2 * j + hh]));
                *reinterpret_cast<uint32_t*>(out + off) = pack_bf16(o0, o1);
            }
        }
    }
}

typedef CUresult (*EncodeFn)(CUtensorMap*, CUtensorMapDataType, cuuint32_t, void*, const cuuint64_t*, const cuuint64_t*,
                             const cuuint32_t*, const cuuint32_t*, CUtensorMapInterleave, CUtensorMapSwizzle,
                             CUtensorMapL2promotion, CUtensorMapFloatOOBfill);

static CUtensorMap make_map(EncodeFn fn, const void* ptr, uint64_t rows, uint64_t cols, uint32_t box_rows, uint32_t box_blk) {
    CUtensorMap m;
    cuuint64_t dims[3] = {64, rows, cols / 64};
    cuuint64_t strides[2] = {cols * 2, 128};
    cuuint32_t box[3] = {64, box_rows, box_blk};
    cuuint32_t es[3] = {1, 1, 1};
    fn(&m, CU_TENSOR_MAP_DATA_TYPE_BFLOAT16, 3, const_cast<void*>(ptr), dims, strides, box, es, CU_TENSOR_MAP_INTERLEAVE_NONE,
       CU_TENSOR_MAP_SWIZZLE_128B, CU_TENSOR_MAP_L2_PROMOTION_L2_256B, CU_TENSOR_MAP_FLOAT_OOB_FILL_NONE);
    return m;
}

extern "C" void kernel_launch(void* const* d_in, const int* in_sizes, int n_in, void* d_out, int out_size) {
    const bf16* x = (const bf16*)d_in[0];
    const bf16* kc = (const bf16*)d_in[1];
    const bf16* vc = (const bf16*)d_in[2];
    const bf16* wq = (const bf16*)d_in[3];
    const bf16* wo = (const bf16*)d_in[4];
    const bf16* w1 = (const bf16*)d_in[6];
    const bf16* w2 = (const bf16*)d_in[7];
    bf16* out = (bf16*)d_out;

    static EncodeFn fn = nullptr;
    static void *p_xn = nullptr, *p_h = nullptr, *p_o = nullptr, *p_g = nullptr;
    static Sched sched;
    if (!fn) {
        void* f = nullptr;
        cudaDriverEntryPointQueryResult st;
        cudaGetDriverEntryPoint("cuTensorMapEncodeTiled", &f, cudaEnableDefault, &st);
        fn = (EncodeFn)f;
        cudaGetSymbolAddress(&p_xn, g_xn);
        cudaGetSymbolAddress(&p_h, g_h);
        cudaGetSymbolAddress(&p_o, g_o);
        cudaGetSymbolAddress(&p_g, g_g);
        cudaFuncSetAttribute(attn_kernel, cudaFuncAttributeMaxDynamicSharedMemorySize, (int)sizeof(AttnSmem) + 1024);
        cudaFuncSetAttribute(oproj_kernel, cudaFuncAttributeMaxDynamicSharedMemorySize, (int)sizeof(OpSmem) + 1024);
        static uint16_t f1[NUM_CTAS][MAX_ITEMS], at[NUM_CTAS][MAX_ITEMS], f2[NUM_CTAS][MAX_ITEMS];
        static int n1[NUM_CTAS], na[NUM_CTAS], n2[NUM_CTAS];
        static double load[NUM_CTAS];
        const double C_ATT = 58.0, C_F1 = 6.5, C_F2 = 19.5;
        for (int i = 0; i < NUM_CTAS; i++) { n1[i] = na[i] = n2[i] = 0; load[i] = 0; }
        for (int t = 0; t < NH * 16; t++) {
            int cta = t % NUM_CTAS;
            at[cta][na[cta]++] = (uint16_t)((T_ATT << 12) | ((t >> 4) << 4) | (t & 15));
            load[cta] += C_ATT;
        }
        auto least = [&]() { int bi = 0; for (int i = 1; i < NUM_CTAS; i++) if (load[i] < load[bi]) bi = i; return bi; };
        for (int t = 0; t < 64; t++) {
            int cta = least();
            f2[cta][n2[cta]++] = (uint16_t)((T_F2 << 12) | ((t & 3) << 4) | (t >> 2));
            load[cta] += C_F2;
        }
        for (int t = 0; t < 224; t++) {
            int cta = least();
            f1[cta][n1[cta]++] = (uint16_t)((T_F1 << 12) | ((t % 14) << 4) | (t / 14));
            load[cta] += C_F1;
        }
        for (int i = 0; i < NUM_CTAS; i++) {
            int n = 0;
            for (int j = 0; j < n1[i]; j++) sched.item[i][n++] = f1[i][j];
            for (int j = 0; j < na[i]; j++) sched.item[i][n++] = at[i][j];
            for (int j = 0; j < n2[i]; j++) sched.item[i][n++] = f2[i][j];
            sched.count[i] = (uint8_t)n;
        }
    }
    CUtensorMap tm_xn_at = make_map(fn, p_xn, SEQ, DM, 128, 2);
    CUtensorMap tm_wq = make_map(fn, wq, DM, NH * DH, 128, 2);
    CUtensorMap tm_k = make_map(fn, kc, NH * SEQ, DH, 128, 2);
    CUtensorMap tm_v = make_map(fn, vc, NH * SEQ, DH, 128, 2);
    CUtensorMap tm_o_st = make_map(fn, p_o, SEQ, NH * DH, 64, 2);
    CUtensorMap tm_w1 = make_map(fn, w1, DM, FF, 128, 2);
    CUtensorMap tm_h_st = make_map(fn, p_h, SEQ, FF, 64, 2);
    CUtensorMap tm_h_ld = make_map(fn, p_h, SEQ, FF, 128, 2);
    CUtensorMap tm_w2 = make_map(fn, w2, FF, DM, 128, 2);
    CUtensorMap tm_g_st = make_map(fn, p_g, SEQ, DM, 64, 2);
    CUtensorMap tm_o_g = make_map(fn, p_o, SEQ, NH * DH, 128, 1);
    CUtensorMap tm_wo = make_map(fn, wo, NH * DH, DM, 64, 4);

    ln_kernel<<<SEQ / 8, 256>>>(x);
    attn_kernel<<<NUM_CTAS, 384, sizeof(AttnSmem) + 1024>>>(tm_xn_at, tm_wq, tm_k, tm_v, tm_o_st, tm_w1, tm_h_st, tm_h_ld,
                                                            tm_w2, tm_g_st, sched);
    oproj_kernel<<<dim3(OP_KSPLIT, DM / 256, SEQ / 128), 384, sizeof(OpSmem) + 1024>>>(tm_o_g, tm_wo, x, out);
}
```

```cpp
#include <cuda_runtime.h>
#include <cuda_bf16.h>
#include <cuda.h>
#include <stdint.h>

typedef __nv_bfloat16 bf16;

constexpr int SEQ = 2048, DM = 512, NH = 32, DH = 128, FF = 1792;

__device__ __align__(1024) bf16 g_xn[SEQ * DM];
__device__ __align__(1024) bf16 g_h[SEQ * FF];
__device__ __align__(1024) bf16 g_o[SEQ * NH * DH];
__device__ __align__(1024) bf16 g_g[SEQ * DM];
__device__ unsigned int g_hcnt[SEQ / 128];
__device__ float4 g_part[32 * 16 * 8 * 256];
__device__ unsigned int g_pcnt[128];
__device__ volatile float g_dummy;

__device__ __forceinline__ uint32_t smem_u32(const void* p) { return (uint32_t)__cvta_generic_to_shared(p); }

__device__ __forceinline__ void mbar_init(uint32_t bar, uint32_t count) {
    asm volatile("mbarrier.init.shared::cta.b64 [%0], %1;" ::"r"(bar), "r"(count) : "memory");
}
__device__ __forceinline__ void mbar_expect_tx(uint32_t bar, uint32_t bytes) {
    asm volatile("mbarrier.arrive.expect_tx.shared::cta.b64 _, [%0], %1;" ::"r"(bar), "r"(bytes) : "memory");
}
__device__ __forceinline__ void mbar_arrive(uint32_t bar) {
    asm volatile("mbarrier.arrive.shared::cta.b64 _, [%0];" ::"r"(bar) : "memory");
}
__device__ __forceinline__ bool mbar_try_wait(uint32_t bar, uint32_t parity) {
    uint32_t ok;
    asm volatile(
        "{\n.reg .pred p;\n"
        "mbarrier.try_wait.parity.shared::cta.b64 p, [%1], %2;\n"
        "selp.u32 %0, 1, 0, p;\n}\n"
        : "=r"(ok)
        : "r"(bar), "r"(parity)
        : "memory");
    return ok != 0;
}
__device__ __forceinline__ void mbar_wait(uint32_t bar, uint32_t parity) {
    asm volatile(
        "{\n.reg .pred P1;\n.reg .u32 n;\nmov.u32 n, 0;\n"
        "LAB_WAIT:\n"
        "mbarrier.try_wait.parity.shared::cta.b64 P1, [%0], %1;\n"
        "@P1 bra DONE;\n"
        "add.u32 n, n, 1;\n"
        "setp.lt.u32 P1, n, 4194304;\n"
        "@P1 bra LAB_WAIT;\n"
        "trap;\n"
        "DONE:\n}\n" ::"r"(bar), "r"(parity)
        : "memory");
}
__device__ __forceinline__ void tma_load_3d(uint32_t dst, const CUtensorMap* map, uint32_t bar, int c0, int c1, int c2) {
    asm volatile(
        "cp.async.bulk.tensor.3d.shared::cluster.global.mbarrier::complete_tx::bytes [%0], [%1, {%3, %4, %5}], [%2];"
        ::"r"(dst), "l"((uint64_t)map), "r"(bar), "r"(c0), "r"(c1), "r"(c2)
        : "memory");
}
__device__ __forceinline__ void tma_load_3d_mc(uint32_t dst, const CUtensorMap* map, uint32_t bar, int c0, int c1, int c2,
                                               uint16_t mask) {
    asm volatile(
        "cp.async.bulk.tensor.3d.shared::cluster.global.mbarrier::complete_tx::bytes.multicast::cluster [%0], [%1, {%3, %4, %5}], [%2], %6;"
        ::"r"(dst), "l"((uint64_t)map), "r"(bar), "r"(c0), "r"(c1), "r"(c2), "h"(mask)
        : "memory");
}
__device__ __forceinline__ uint32_t mapa_u32(uint32_t addr, uint32_t rank) {
    uint32_t r;
    asm("mapa.shared::cluster.u32 %0, %1, %2;" : "=r"(r) : "r"(addr), "r"(rank));
    return r;
}
__device__ __forceinline__ void mbar_arrive_cluster(uint32_t bar) {
    asm volatile("mbarrier.arrive.release.cluster.shared::cluster.b64 _, [%0];" ::"r"(bar) : "memory");
}
__device__ __forceinline__ void cluster_sync_all() {
    asm volatile("barrier.cluster.arrive.release.aligned;\nbarrier.cluster.wait.acquire.aligned;" ::: "memory");
}
__device__ __forceinline__ void tma_store_3d(const CUtensorMap* map, uint32_t src, int c0, int c1, int c2) {
    asm volatile("cp.async.bulk.tensor.3d.global.shared::cta.bulk_group [%0, {%2, %3, %4}], [%1];"
                 ::"l"((uint64_t)map), "r"(src), "r"(c0), "r"(c1), "r"(c2)
                 : "memory");
}
__device__ __forceinline__ void tma_commit() { asm volatile("cp.async.bulk.commit_group;" ::: "memory"); }
__device__ __forceinline__ void tma_wait_read0() { asm volatile("cp.async.bulk.wait_group.read 0;" ::: "memory"); }
__device__ __forceinline__ void tma_wait_all0() { asm volatile("cp.async.bulk.wait_group 0;" ::: "memory"); }
__device__ __forceinline__ void fence_proxy_async() { asm volatile("fence.proxy.async.shared::cta;" ::: "memory"); }
__device__ __forceinline__ void prefetch_tmap(const CUtensorMap* map) {
    asm volatile("prefetch.tensormap [%0];" ::"l"((uint64_t)map) : "memory");
}
__device__ __forceinline__ void named_sync(int id, int n) { asm volatile("bar.sync %0, %1;" ::"r"(id), "r"(n) : "memory"); }
__device__ __forceinline__ void named_arrive(int id, int n) { asm volatile("bar.arrive %0, %1;" ::"r"(id), "r"(n) : "memory"); }

__device__ __forceinline__ void wgmma_fence() { asm volatile("wgmma.fence.sync.aligned;" ::: "memory"); }
__device__ __forceinline__ void wgmma_commit() { asm volatile("wgmma.commit_group.sync.aligned;" ::: "memory"); }
template <int N>
__device__ __forceinline__ void wgmma_wait() { asm volatile("wgmma.wait_group.sync.aligned %0;" ::"n"(N) : "memory"); }

template <int R>
__device__ __forceinline__ void reg_alloc() { asm volatile("setmaxnreg.inc.sync.aligned.u32 %0;" ::"n"(R)); }
template <int R>
__device__ __forceinline__ void reg_dealloc() { asm volatile("setmaxnreg.dec.sync.aligned.u32 %0;" ::"n"(R)); }

__device__ __forceinline__ uint64_t make_desc(uint32_t saddr, uint32_t lbo_bytes, uint32_t sbo_bytes) {
    uint64_t d = 0;
    d |= (uint64_t)((saddr & 0x3FFFF) >> 4);
    d |= (uint64_t)((lbo_bytes >> 4) & 0x3FFF) << 16;
    d |= (uint64_t)((sbo_bytes >> 4) & 0x3FFF) << 32;
    d |= (uint64_t)1 << 62;
    return d;
}

__device__ __forceinline__ float ex2(float x) {
    float y;
    asm volatile("ex2.approx.ftz.f32 %0, %1;" : "=f"(y) : "f"(x));
    return y;
}
__device__ __forceinline__ uint32_t pack_bf16(float lo, float hi) {
    uint32_t r;
    asm("cvt.rn.bf16x2.f32 %0, %1, %2;" : "=r"(r) : "f"(hi), "f"(lo));
    return r;
}
__device__ __forceinline__ uint32_t mul_bf16x2(uint32_t a, uint32_t b) {
    uint32_t r;
    asm("mul.rn.bf16x2 %0, %1, %2;" : "=r"(r) : "r"(a), "r"(b));
    return r;
}
__device__ __forceinline__ uint32_t fma_bf16x2(uint32_t a, uint32_t b, uint32_t c) {
    uint32_t r;
    asm("fma.rn.bf16x2 %0, %1, %2, %3;" : "=r"(r) : "r"(a), "r"(b), "r"(c));
    return r;
}
__device__ __forceinline__ uint32_t max_bf16x2(uint32_t a, uint32_t b) {
    uint32_t r;
    asm("max.bf16x2 %0, %1, %2;" : "=r"(r) : "r"(a), "r"(b));
    return r;
}
__device__ __forceinline__ float bf16lo(uint32_t v) { return __uint_as_float(v << 16); }
__device__ __forceinline__ float bf16hi(uint32_t v) { return __uint_as_float(v & 0xffff0000u); }
__device__ __forceinline__ float bf16_round(float x) { return __bfloat162float(__float2bfloat16_rn(x)); }
__device__ __forceinline__ float silu_f(float x) { return __fdividef(x, 1.0f + __expf(-x)); }

__device__ __forceinline__ void stmatrix_x4(uint32_t addr, uint32_t r0, uint32_t r1, uint32_t r2, uint32_t r3) {
    asm volatile("stmatrix.sync.aligned.m8n8.x4.shared.b16 [%0], {%1, %2, %3, %4};"
                 ::"r"(addr), "r"(r0), "r"(r1), "r"(r2), "r"(r3)
                 : "memory");
}

#define ACC64(d) \
    "+f"(d[0]), "+f"(d[1]), "+f"(d[2]), "+f"(d[3]), "+f"(d[4]), "+f"(d[5]), "+f"(d[6]), "+f"(d[7]), \
    "+f"(d[8]), "+f"(d[9]), "+f"(d[10]), "+f"(d[11]), "+f"(d[12]), "+f"(d[13]), "+f"(d[14]), "+f"(d[15]), \
    "+f"(d[16]), "+f"(d[17]), "+f"(d[18]), "+f"(d[19]), "+f"(d[20]), "+f"(d[21]), "+f"(d[22]), "+f"(d[23]), \
    "+f"(d[24]), "+f"(d[25]), "+f"(d[26]), "+f"(d[27]), "+f"(d[28]), "+f"(d[29]), "+f"(d[30]), "+f"(d[31]), \
    "+f"(d[32]), "+f"(d[33]), "+f"(d[34]), "+f"(d[35]), "+f"(d[36]), "+f"(d[37]), "+f"(d[38]), "+f"(d[39]), \
    "+f"(d[40]), "+f"(d[41]), "+f"(d[42]), "+f"(d[43]), "+f"(d[44]), "+f"(d[45]), "+f"(d[46]), "+f"(d[47]), \
    "+f"(d[48]), "+f"(d[49]), "+f"(d[50]), "+f"(d[51]), "+f"(d[52]), "+f"(d[53]), "+f"(d[54]), "+f"(d[55]), \
    "+f"(d[56]), "+f"(d[57]), "+f"(d[58]), "+f"(d[59]), "+f"(d[60]), "+f"(d[61]), "+f"(d[62]), "+f"(d[63])

#define ACC64_STR \
    "{%0, %1, %2, %3, %4, %5, %6, %7, %8, %9, %10, %11, %12, %13, %14, %15, " \
    "%16, %17, %18, %19, %20, %21, %22, %23, %24, %25, %26, %27, %28, %29, %30, %31, " \
    "%32, %33, %34, %35, %36, %37, %38, %39, %40, %41, %42, %43, %44, %45, %46, %47, " \
    "%48, %49, %50, %51, %52, %53, %54, %55, %56, %57, %58, %59, %60, %61, %62, %63}"

template <int TB>
__device__ __forceinline__ void wgmma_ss_n128(float (&d)[64], uint64_t da, uint64_t db, int scale_d) {
    asm volatile(
        "{\n.reg .pred p;\nsetp.ne.b32 p, %66, 0;\n"
        "wgmma.mma_async.sync.aligned.m64n128k16.f32.bf16.bf16 " ACC64_STR ", %64, %65, p, 1, 1, 0, %67;\n}\n"
        : ACC64(d)
        : "l"(da), "l"(db), "r"(scale_d), "n"(TB));
}
template <int TB>
__device__ __forceinline__ void wgmma_rs_n128(float (&d)[64], uint32_t a0, uint32_t a1, uint32_t a2, uint32_t a3,
                                              uint64_t db, int scale_d) {
    asm volatile(
        "{\n.reg .pred p;\nsetp.ne.b32 p, %69, 0;\n"
        "wgmma.mma_async.sync.aligned.m64n128k16.f32.bf16.bf16 " ACC64_STR ", {%64, %65, %66, %67}, %68, p, 1, 1, %70;\n}\n"
        : ACC64(d)
        : "r"(a0), "r"(a1), "r"(a2), "r"(a3), "l"(db), "r"(scale_d), "n"(TB));
}

__global__ void __launch_bounds__(256) ln_kernel(const bf16* __restrict__ x) {
    int warp = threadIdx.x >> 5, lane = threadIdx.x & 31;
    int row = blockIdx.x * 8 + warp;
    if (blockIdx.x == 0 && threadIdx.x < SEQ / 128) g_hcnt[threadIdx.x] = 0;
    if (blockIdx.x == 1 && threadIdx.x < 128) g_pcnt[threadIdx.x] = 0;
    const uint4* src = reinterpret_cast<const uint4*>(x + (size_t)row * DM);
    uint4 v[2];
    v[0] = src[lane];
    v[1] = src[lane + 32];
    float f[16];
#pragma unroll
    for (int i = 0; i < 2; i++) {
        const __nv_bfloat162* p = reinterpret_cast<const __nv_bfloat162*>(&v[i]);
#pragma unroll
        for (int j = 0; j < 4; j++) {
            float2 t = __bfloat1622float2(p[j]);
            f[i * 8 + j * 2] = t.x;
            f[i * 8 + j * 2 + 1] = t.y;
        }
    }
    float s = 0.f;
#pragma unroll
    for (int i = 0; i < 16; i++) s += f[i];
#pragma unroll
    for (int o = 16; o > 0; o >>= 1) s += __shfl_xor_sync(0xffffffffu, s, o);
    float mean = s * (1.0f / DM);
    float q = 0.f;
#pragma unroll
    for (int i = 0; i < 16; i++) {
        float d = f[i] - mean;
        q += d * d;
    }
#pragma unroll
    for (int o = 16; o > 0; o >>= 1) q += __shfl_xor_sync(0xffffffffu, q, o);
    float var_b = bf16_round(q * (1.0f / DM));
    float mean_b = bf16_round(mean);
    float den = bf16_round(sqrtf(bf16_round(var_b + 1e-5f)));
    uint4 o[2];
#pragma unroll
    for (int i = 0; i < 2; i++) {
        uint32_t* p = reinterpret_cast<uint32_t*>(&o[i]);
#pragma unroll
        for (int j = 0; j < 4; j++) {
            float a = bf16_round(f[i * 8 + j * 2] - mean_b) / den;
            float b = bf16_round(f[i * 8 + j * 2 + 1] - mean_b) / den;
            p[j] = pack_bf16(a, b);
        }
    }
    uint4* dst = reinterpret_cast<uint4*>(g_xn + (size_t)row * DM);
    dst[lane] = o[0];
    dst[lane + 32] = o[1];
}

constexpr int AT_STAGES = 3;
constexpr int TILE_BYTES = 128 * 128 * 2;
struct __align__(1024) AttnSmem {
    uint8_t k[AT_STAGES][TILE_BYTES];
    uint8_t v[AT_STAGES][TILE_BYTES];
    uint8_t o[TILE_BYTES];
    uint64_t full_k[AT_STAGES], full_v[AT_STAGES], empty_k[AT_STAGES], empty_v[AT_STAGES];
};

constexpr int NUM_CTAS = 66;
constexpr int MAX_ITEMS = 12;
enum { T_ATT = 0, T_F1 = 1, T_F2 = 2 };
struct Sched {
    uint16_t item[NUM_CTAS][MAX_ITEMS];
    uint8_t count[NUM_CTAS];
};

__global__ void __cluster_dims__(2, 1, 1) __launch_bounds__(384, 1)
attn_kernel(const __grid_constant__ CUtensorMap tm_xn, const __grid_constant__ CUtensorMap tm_wq,
            const __grid_constant__ CUtensorMap tm_k, const __grid_constant__ CUtensorMap tm_v,
            const __grid_constant__ CUtensorMap tm_o, const __grid_constant__ CUtensorMap tm_w1,
            const __grid_constant__ CUtensorMap tm_hst, const __grid_constant__ CUtensorMap tm_hld,
            const __grid_constant__ CUtensorMap tm_w2, const __grid_constant__ CUtensorMap tm_gst,
            const __grid_constant__ Sched sched) {
    extern __shared__ uint8_t smem_raw[];
    AttnSmem& sm = *reinterpret_cast<AttnSmem*>((reinterpret_cast<uintptr_t>(smem_raw) + 1023) & ~uintptr_t(1023));
    const int tid = threadIdx.x;
    const int wg = __shfl_sync(0xffffffffu, tid >> 7, 0);
    const int cid = blockIdx.x >> 1, rank = blockIdx.x & 1;
    const int n_items = sched.count[cid];

    if (tid == 0) {
#pragma unroll
        for (int s = 0; s < AT_STAGES; s++) {
            mbar_init(smem_u32(&sm.full_k[s]), 1);
            mbar_init(smem_u32(&sm.full_v[s]), 1);
            mbar_init(smem_u32(&sm.empty_k[s]), 16);
            mbar_init(smem_u32(&sm.empty_v[s]), 16);
        }
        asm volatile("fence.mbarrier_init.release.cluster;" ::: "memory");
    }
    cluster_sync_all();

    if (wg == 0) {
        reg_dealloc<24>();
        if (tid == 0) {
            int stage = 0;
            uint32_t phase = 0;
            for (int it = 0; it < n_items; it++) {
                const int item = sched.item[cid][it];
                const int type = item >> 12, a = (item >> 4) & 0xff, b = (item & 15) * 2 + rank;
                const CUtensorMap* ta = (type == T_F2) ? &tm_hld : &tm_xn;
                const CUtensorMap* tb = (type == T_ATT) ? &tm_wq : (type == T_F1 ? &tm_w1 : &tm_w2);
                const int nch = (type == T_F2) ? FF / 128 : DM / 128;
                if (type == T_F2) {
                    unsigned int v, spins = 0;
                    do {
                        asm volatile("ld.acquire.gpu.global.u32 %0, [%1];" : "=r"(v) : "l"(&g_hcnt[b]) : "memory");
                    } while (v < 2 * (FF / 128) && ++spins < (1u << 24));
                    asm volatile("fence.proxy.async;" ::: "memory");
                }
                for (int kc = 0; kc < nch; kc++) {
                    mbar_wait(smem_u32(&sm.empty_k[stage]), phase ^ 1);
                    mbar_expect_tx(smem_u32(&sm.full_k[stage]), TILE_BYTES);
                    tma_load_3d(smem_u32(sm.k[stage]), ta, smem_u32(&sm.full_k[stage]), 0, b * 128, kc * 2);
                    mbar_wait(smem_u32(&sm.empty_v[stage]), phase ^ 1);
                    mbar_expect_tx(smem_u32(&sm.full_v[stage]), TILE_BYTES);
                    tma_load_3d_mc(smem_u32(sm.v[stage]) + rank * 16384, tb, smem_u32(&sm.full_v[stage]), 0, kc * 128, a * 2 + rank, 3);
                    if (++stage == AT_STAGES) { stage = 0; phase ^= 1; }
                }
                if (type == T_ATT) {
                    for (int j = 0; j < 16; j++) {
                        mbar_wait(smem_u32(&sm.empty_k[stage]), phase ^ 1);
                        mbar_expect_tx(smem_u32(&sm.full_k[stage]), TILE_BYTES);
                        tma_load_3d_mc(smem_u32(sm.k[stage]) + rank * 16384, &tm_k, smem_u32(&sm.full_k[stage]), 0, a * SEQ + j * 128, rank, 3);
                        mbar_wait(smem_u32(&sm.empty_v[stage]), phase ^ 1);
                        mbar_expect_tx(smem_u32(&sm.full_v[stage]), TILE_BYTES);
                        tma_load_3d_mc(smem_u32(sm.v[stage]) + rank * 16384, &tm_v, smem_u32(&sm.full_v[stage]), 0, a * SEQ + j * 128, rank, 3);
                        if (++stage == AT_STAGES) { stage = 0; phase ^= 1; }
                    }
                }
            }
        }
    } else {
        reg_alloc<240>();
        const int cw = wg - 1;
        const int lane = tid & 31;
        const int warp_in_wg = (tid >> 5) & 3;
        const float c = 1.4426950408889634f;
        const uint32_t SCALE_HI2 = 0x3DB53DB5u, SCALE_LO2 = 0x371E371Eu;
        constexpr int BAR_SCHED0 = 1, BAR_EPI0 = 3;
        const uint32_t obase = smem_u32(sm.o) + cw * 16384;
        const int st_row = warp_in_wg * 16 + ((lane >> 3) & 1) * 8 + (lane & 7);
        const uint32_t rek = mapa_u32(smem_u32(&sm.empty_k[0]), lane & 1), rev = mapa_u32(smem_u32(&sm.empty_v[0]), lane & 1);

        if (cw == 1) named_arrive(BAR_SCHED0 + 0, 256);

        int stage = 0;
        uint32_t phase = 0;
        int pending_mb = -1;
        float S[64], O[64];
        uint32_t P[32];

        for (int it = 0; it < n_items; it++) {
            const int item = sched.item[cid][it];
            const int type = item >> 12, ia = (item >> 4) & 0xff, ib = (item & 15) * 2 + rank;
            const int nch = (type == T_F2) ? FF / 128 : DM / 128;
            {
                int prev = -1;
#pragma unroll 1
                for (int kc = 0; kc < nch; kc++) {
                    mbar_wait(smem_u32(&sm.full_k[stage]), phase);
                    mbar_wait(smem_u32(&sm.full_v[stage]), phase);
                    const uint64_t da = make_desc(smem_u32(sm.k[stage]) + cw * 64 * 128, 16, 1024);
                    const uint64_t db = make_desc(smem_u32(sm.v[stage]), 16384, 1024);
                    wgmma_fence();
#pragma unroll
                    for (int kk = 0; kk < 8; kk++) {
                        wgmma_ss_n128<1>(S, da + (uint64_t)(((kk >> 2) * 16384 + (kk & 3) * 32) >> 4),
                                         db + (uint64_t)((kk * 2048) >> 4), (kc | kk) != 0);
                    }
                    wgmma_commit();
                    wgmma_wait<1>();
                    if (prev >= 0 && lane < 2) {
                        mbar_arrive_cluster(rek + prev * 8);
                        mbar_arrive_cluster(rev + prev * 8);
                    }
                    prev = stage;
                    if (++stage == AT_STAGES) { stage = 0; phase ^= 1; }
                }
                wgmma_wait<0>();
                if (lane < 2) {
                    mbar_arrive_cluster(rek + prev * 8);
                    mbar_arrive_cluster(rev + prev * 8);
                }
            }
            if (type != T_ATT) {
#pragma unroll
                for (int i = 0; i < 64; i++) S[i] = silu_f(bf16_round(S[i]));
            }
            if ((tid & 127) == 0) {
                if (pending_mb >= 0) {
                    tma_wait_all0();
                    asm volatile("fence.proxy.async;" ::: "memory");
                    __threadfence();
                    atomicAdd(&g_hcnt[pending_mb], 1u);
                } else {
                    tma_wait_read0();
                }
            }
            pending_mb = -1;
            named_sync(BAR_EPI0 + cw, 128);
#pragma unroll
            for (int i = 0; i < 16; i += 2) {
                const int cc = i + (lane >> 4);
                const uint32_t addr = obase + (cc >> 3) * 8192 + st_row * 128 + (((cc & 7) ^ (st_row & 7)) << 4);
                stmatrix_x4(addr, pack_bf16(S[4 * i], S[4 * i + 1]), pack_bf16(S[4 * i + 2], S[4 * i + 3]),
                            pack_bf16(S[4 * i + 4], S[4 * i + 5]), pack_bf16(S[4 * i + 6], S[4 * i + 7]));
            }
            fence_proxy_async();
            named_sync(BAR_EPI0 + cw, 128);
            if (type != T_ATT) {
                if ((tid & 127) == 0) {
                    tma_store_3d(type == T_F1 ? &tm_hst : &tm_gst, obase, 0, ib * 128 + cw * 64, ia * 2);
                    tma_commit();
                }
                if (type == T_F1) pending_mb = ib;
                continue;
            }
            const uint64_t dq = make_desc(obase, 16, 1024);
#pragma unroll
            for (int i = 0; i < 64; i++) O[i] = 0.f;

            float m0 = -INFINITY, m1 = -INFINITY, l0 = 0.f, l1 = 0.f, a0 = 0.f, a1 = 0.f;
            bool resc = false;
            const float TAU = 11.0f;

            {
                mbar_wait(smem_u32(&sm.full_k[stage]), phase);
                const uint64_t dk = make_desc(smem_u32(sm.k[stage]), 16, 1024);
                named_sync(BAR_SCHED0 + cw, 256);
                wgmma_fence();
#pragma unroll
                for (int kk = 0; kk < 8; kk++)
                    wgmma_ss_n128<0>(S, dq + (uint64_t)(((kk >> 2) * 8192 + (kk & 3) * 32) >> 4),
                                     dk + (uint64_t)(((kk >> 2) * 16384 + (kk & 3) * 32) >> 4), kk != 0);
                wgmma_commit();
                named_arrive(BAR_SCHED0 + (cw ^ 1), 256);
                wgmma_wait<0>();
                if (lane < 2) mbar_arrive_cluster(rek + stage * 8);
            }
            int vstage = stage;
            uint32_t vphase = phase;
            if (++stage == AT_STAGES) { stage = 0; phase ^= 1; }

            auto softmax = [&]() {
                uint32_t T[32];
#pragma unroll
                for (int i = 0; i < 32; i++) {
                    const uint32_t sb = pack_bf16(S[2 * i], S[2 * i + 1]);
                    T[i] = fma_bf16x2(sb, SCALE_HI2, mul_bf16x2(sb, SCALE_LO2));
                }
                uint32_t y0 = max_bf16x2(T[0], T[2]), y1 = max_bf16x2(T[1], T[3]);
#pragma unroll
                for (int i = 2; i < 16; i++) {
                    y0 = max_bf16x2(y0, T[2 * i]);
                    y1 = max_bf16x2(y1, T[2 * i + 1]);
                }
                float x0 = fmaxf(bf16lo(y0), bf16hi(y0));
                float x1 = fmaxf(bf16lo(y1), bf16hi(y1));
                x0 = fmaxf(x0, __shfl_xor_sync(0xffffffffu, x0, 1));
                x1 = fmaxf(x1, __shfl_xor_sync(0xffffffffu, x1, 1));
                x0 = fmaxf(x0, __shfl_xor_sync(0xffffffffu, x0, 2));
                x1 = fmaxf(x1, __shfl_xor_sync(0xffffffffu, x1, 2));
                resc = __any_sync(0xffffffffu, (x0 - m0 > TAU) || (x1 - m1 > TAU));
                if (resc) {
                    x0 = fmaxf(x0, m0);
                    x1 = fmaxf(x1, m1);
                    a0 = ex2((m0 - x0) * c);
                    a1 = ex2((m1 - x1) * c);
                    m0 = x0;
                    m1 = x1;
                    l0 *= a0;
                    l1 *= a1;
                }
                const float n0 = -m0 * c, n1 = -m1 * c;
                float s0 = 0.f, s1 = 0.f;
#pragma unroll
                for (int i = 0; i < 16; i++) {
                    S[4 * i] = ex2(fmaf(bf16lo(T[2 * i]), c, n0));
                    S[4 * i + 1] = ex2(fmaf(bf16hi(T[2 * i]), c, n0));
                    S[4 * i + 2] = ex2(fmaf(bf16lo(T[2 * i + 1]), c, n1));
                    S[4 * i + 3] = ex2(fmaf(bf16hi(T[2 * i + 1]), c, n1));
                    s0 += S[4 * i] + S[4 * i + 1];
                    s1 += S[4 * i + 2] + S[4 * i + 3];
                }
                l0 += s0;
                l1 += s1;
                while (s0 + s1 < 0.f) s0 = g_dummy;
            };
            softmax();
#pragma unroll
            for (int i = 0; i < 32; i++) P[i] = pack_bf16(S[2 * i], S[2 * i + 1]);

#pragma unroll 1
            for (int j = 1; j < 16; j++) {
                mbar_wait(smem_u32(&sm.full_k[stage]), phase);
                const uint64_t dk = make_desc(smem_u32(sm.k[stage]), 16, 1024);
                const uint64_t dv = make_desc(smem_u32(sm.v[vstage]), 16384, 1024);
                named_sync(BAR_SCHED0 + cw, 256);
                wgmma_fence();
#pragma unroll
                for (int kk = 0; kk < 8; kk++)
                    wgmma_ss_n128<0>(S, dq + (uint64_t)(((kk >> 2) * 8192 + (kk & 3) * 32) >> 4),
                                     dk + (uint64_t)(((kk >> 2) * 16384 + (kk & 3) * 32) >> 4), kk != 0);
                wgmma_commit();
                if (resc) {
#pragma unroll
                    for (int i = 0; i < 16; i++) {
                        O[4 * i] *= a0;
                        O[4 * i + 1] *= a0;
                        O[4 * i + 2] *= a1;
                        O[4 * i + 3] *= a1;
                    }
                }
                mbar_wait(smem_u32(&sm.full_v[vstage]), vphase);
                wgmma_fence();
#pragma unroll
                for (int kk = 0; kk < 8; kk++)
                    wgmma_rs_n128<1>(O, P[4 * kk], P[4 * kk + 1], P[4 * kk + 2], P[4 * kk + 3],
                                     dv + (uint64_t)((kk * 2048) >> 4), 1);
                wgmma_commit();
                named_arrive(BAR_SCHED0 + (cw ^ 1), 256);
                wgmma_wait<1>();
                if (lane < 2) mbar_arrive_cluster(rek + stage * 8);
                softmax();
                wgmma_wait<0>();
                if (lane < 2) mbar_arrive_cluster(rev + vstage * 8);
#pragma unroll
                for (int i = 0; i < 32; i++) P[i] = pack_bf16(S[2 * i], S[2 * i + 1]);
                vstage = stage;
                vphase = phase;
                if (++stage == AT_STAGES) { stage = 0; phase ^= 1; }
            }
            {
                if (resc) {
#pragma unroll
                    for (int i = 0; i < 16; i++) {
                        O[4 * i] *= a0;
                        O[4 * i + 1] *= a0;
                        O[4 * i + 2] *= a1;
                        O[4 * i + 3] *= a1;
                    }
                }
                const uint64_t dv = make_desc(smem_u32(sm.v[vstage]), 16384, 1024);
                mbar_wait(smem_u32(&sm.full_v[vstage]), vphase);
                wgmma_fence();
#pragma unroll
                for (int kk = 0; kk < 8; kk++)
                    wgmma_rs_n128<1>(O, P[4 * kk], P[4 * kk + 1], P[4 * kk + 2], P[4 * kk + 3],
                                     dv + (uint64_t)((kk * 2048) >> 4), 1);
                wgmma_commit();
                wgmma_wait<0>();
                if (lane < 2) mbar_arrive_cluster(rev + vstage * 8);
            }
            l0 += __shfl_xor_sync(0xffffffffu, l0, 1);
            l1 += __shfl_xor_sync(0xffffffffu, l1, 1);
            l0 += __shfl_xor_sync(0xffffffffu, l0, 2);
            l1 += __shfl_xor_sync(0xffffffffu, l1, 2);
            const float i0 = 1.0f / l0, i1 = 1.0f / l1;
            named_sync(BAR_EPI0 + cw, 128);
#pragma unroll
            for (int i = 0; i < 16; i += 2) {
                const int cc = i + (lane >> 4);
                const uint32_t addr = obase + (cc >> 3) * 8192 + st_row * 128 + (((cc & 7) ^ (st_row & 7)) << 4);
                stmatrix_x4(addr, pack_bf16(O[4 * i] * i0, O[4 * i + 1] * i0), pack_bf16(O[4 * i + 2] * i1, O[4 * i + 3] * i1),
                            pack_bf16(O[4 * i + 4] * i0, O[4 * i + 5] * i0), pack_bf16(O[4 * i + 6] * i1, O[4 * i + 7] * i1));
            }
            fence_proxy_async();
            named_sync(BAR_EPI0 + cw, 128);
            if ((tid & 127) == 0) {
                tma_store_3d(&tm_o, obase, 0, ib * 128 + cw * 64, ia * 2);
                tma_commit();
            }
        }
        if ((tid & 127) == 0) {
            tma_wait_all0();
            if (pending_mb >= 0) {
                asm volatile("fence.proxy.async;" ::: "memory");
                __threadfence();
                atomicAdd(&g_hcnt[pending_mb], 1u);
            }
        }
    }
    cluster_sync_all();
}

constexpr int OP_STAGES = 4;
constexpr int OP_KSPLIT = 4;
struct __align__(1024) OpSmem {
    uint8_t a[OP_STAGES][128 * 64 * 2];
    uint8_t b[OP_STAGES][64 * 256 * 2];
    uint64_t full[OP_STAGES], empty[OP_STAGES];
};

#define ACC8(d, o) "+f"(d[o]), "+f"(d[o + 1]), "+f"(d[o + 2]), "+f"(d[o + 3]), "+f"(d[o + 4]), "+f"(d[o + 5]), "+f"(d[o + 6]), "+f"(d[o + 7])
__device__ __forceinline__ void wgmma_ss_n256_tb(float (&d)[128], uint64_t da, uint64_t db, int scale_d) {
    asm volatile(
        "{\n.reg .pred p;\nsetp.ne.b32 p, %130, 0;\n"
        "wgmma.mma_async.sync.aligned.m64n256k16.f32.bf16.bf16 "
        "{%0, %1, %2, %3, %4, %5, %6, %7, %8, %9, %10, %11, %12, %13, %14, %15, "
        "%16, %17, %18, %19, %20, %21, %22, %23, %24, %25, %26, %27, %28, %29, %30, %31, "
        "%32, %33, %34, %35, %36, %37, %38, %39, %40, %41, %42, %43, %44, %45, %46, %47, "
        "%48, %49, %50, %51, %52, %53, %54, %55, %56, %57, %58, %59, %60, %61, %62, %63, "
        "%64, %65, %66, %67, %68, %69, %70, %71, %72, %73, %74, %75, %76, %77, %78, %79, "
        "%80, %81, %82, %83, %84, %85, %86, %87, %88, %89, %90, %91, %92, %93, %94, %95, "
        "%96, %97, %98, %99, %100, %101, %102, %103, %104, %105, %106, %107, %108, %109, %110, %111, "
        "%112, %113, %114, %115, %116, %117, %118, %119, %120, %121, %122, %123, %124, %125, %126, %127}, "
        "%128, %129, p, 1, 1, 0, 1;\n}\n"
        : ACC8(d, 0), ACC8(d, 8), ACC8(d, 16), ACC8(d, 24), ACC8(d, 32), ACC8(d, 40), ACC8(d, 48), ACC8(d, 56),
          ACC8(d, 64), ACC8(d, 72), ACC8(d, 80), ACC8(d, 88), ACC8(d, 96), ACC8(d, 104), ACC8(d, 112), ACC8(d, 120)
        : "l"(da), "l"(db), "r"(scale_d));
}

__global__ void __launch_bounds__(384, 1)
oproj_kernel(const __grid_constant__ CUtensorMap tm_o, const __grid_constant__ CUtensorMap tm_wo,
             const bf16* __restrict__ x, bf16* __restrict__ out) {
    extern __shared__ uint8_t smem_raw[];
    OpSmem& sm = *reinterpret_cast<OpSmem*>((reinterpret_cast<uintptr_t>(smem_raw) + 1023) & ~uintptr_t(1023));
    const int tid = threadIdx.x, wg = tid >> 7;
    const int kr = blockIdx.x;
    const int n0 = blockIdx.y * 256, m0 = blockIdx.z * 128;
    const int tile = blockIdx.y + 2 * blockIdx.z;
    constexpr int KT = NH * DH / OP_KSPLIT / 64;
    if (tid == 0) {
        for (int s = 0; s < OP_STAGES; s++) {
            mbar_init(smem_u32(&sm.full[s]), 1);
            mbar_init(smem_u32(&sm.empty[s]), 8);
        }
        asm volatile("fence.mbarrier_init.release.cluster;" ::: "memory");
    }
    __syncthreads();
    if (wg == 0) {
        reg_dealloc<40>();
        if (tid == 0) {
            int stage = 0;
            uint32_t phase = 0;
            for (int kt = 0; kt < KT; kt++) {
                const int kg = kr * KT + kt;
                mbar_wait(smem_u32(&sm.empty[stage]), phase ^ 1);
                mbar_expect_tx(smem_u32(&sm.full[stage]), 49152);
                tma_load_3d(smem_u32(sm.a[stage]), &tm_o, smem_u32(&sm.full[stage]), 0, m0, kg);
                tma_load_3d(smem_u32(sm.b[stage]), &tm_wo, smem_u32(&sm.full[stage]), 0, kg * 64, n0 >> 6);
                if (++stage == OP_STAGES) { stage = 0; phase ^= 1; }
            }
        }
    } else {
        reg_alloc<232>();
        const int cw = wg - 1, lane = tid & 31, warp_in_wg = (tid >> 5) & 3;
        const int ct = tid - 128;
        float acc[128];
        const int r0 = m0 + cw * 64 + warp_in_wg * 16 + (lane >> 2);
        uint32_t xv[16], gv[16];
#pragma unroll
        for (int j = 0; j < 8; j++) {
#pragma unroll
            for (int hh = 0; hh < 2; hh++) {
                const size_t off = (size_t)(r0 + hh * 8) * DM + n0 + kr * 64 + j * 8 + (lane & 3) * 2;
                xv[2 * j + hh] = *reinterpret_cast<const uint32_t*>(x + off);
                gv[2 * j + hh] = *reinterpret_cast<const uint32_t*>(g_g + off);
            }
        }
        int stage = 0, prev = -1;
        uint32_t phase = 0;
#pragma unroll 1
        for (int kt = 0; kt < KT; kt++) {
            mbar_wait(smem_u32(&sm.full[stage]), phase);
            const uint64_t da = make_desc(smem_u32(sm.a[stage]) + cw * 64 * 128, 16, 1024);
            const uint64_t db = make_desc(smem_u32(sm.b[stage]), 8192, 1024);
            wgmma_fence();
#pragma unroll
            for (int kk = 0; kk < 4; kk++)
                wgmma_ss_n256_tb(acc, da + (uint64_t)((kk * 32) >> 4), db + (uint64_t)((kk * 2048) >> 4), (kt | kk) != 0);
            wgmma_commit();
            wgmma_wait<1>();
            if (prev >= 0 && lane == 0) mbar_arrive(smem_u32(&sm.empty[prev]));
            prev = stage;
            if (++stage == OP_STAGES) { stage = 0; phase ^= 1; }
        }
        wgmma_wait<0>();
        float4* part = g_part + (size_t)tile * (OP_KSPLIT * OP_KSPLIT * 8 * 256);
#pragma unroll
        for (int d = 0; d < OP_KSPLIT; d++) {
            if (d == kr) continue;
#pragma unroll
            for (int j = 0; j < 8; j++)
                __stcg(part + ((d * OP_KSPLIT + kr) * 8 + j) * 256 + ct,
                       make_float4(acc[(8 * d + j) * 4], acc[(8 * d + j) * 4 + 1], acc[(8 * d + j) * 4 + 2], acc[(8 * d + j) * 4 + 3]));
        }
        __threadfence();
        named_sync(1, 256);
        if (ct < OP_KSPLIT && ct != kr)
            asm volatile("red.release.gpu.global.add.u32 [%0], 1;" ::"l"(&g_pcnt[tile * OP_KSPLIT + ct]) : "memory");
        float r[32];
#pragma unroll
        for (int d = 0; d < OP_KSPLIT; d++) {
            if (d == kr) {
#pragma unroll
                for (int i = 0; i < 32; i++) r[i] = acc[32 * d + i];
            }
        }
        if (ct == 0) {
            unsigned int v, spins = 0;
            do {
                asm volatile("ld.acquire.gpu.global.u32 %0, [%1];" : "=r"(v) : "l"(&g_pcnt[tile * OP_KSPLIT + kr]) : "memory");
            } while (v < OP_KSPLIT - 1 && ++spins < (1u << 24));
        }
        named_sync(1, 256);
#pragma unroll
        for (int sr = 0; sr < OP_KSPLIT; sr++) {
            if (sr == kr) continue;
#pragma unroll
            for (int j = 0; j < 8; j++) {
                const float4 v = __ldcg(part + ((kr * OP_KSPLIT + sr) * 8 + j) * 256 + ct);
                r[4 * j] += v.x;
                r[4 * j + 1] += v.y;
                r[4 * j + 2] += v.z;
                r[4 * j + 3] += v.w;
            }
        }
#pragma unroll
        for (int j = 0; j < 8; j++) {
#pragma unroll
            for (int hh = 0; hh < 2; hh++) {
                const size_t off = (size_t)(r0 + hh * 8) * DM + n0 + kr * 64 + j * 8 + (lane & 3) * 2;
                const float s0 = bf16_round(r[4 * j + 2 * hh]), s1 = bf16_round(r[4 * j + 2 * hh + 1]);
                const float o0 = bf16lo(xv[2 * j + hh]) + bf16_round(s0 * bf16lo(gv[2 * j + hh]));
                const float o1 = bf16hi(xv[2 * j + hh]) + bf16_round(s1 * bf16hi(gv[2 * j + hh]));
                *reinterpret_cast<uint32_t*>(out + off) = pack_bf16(o0, o1);
            }
        }
    }
}

typedef CUresult (*EncodeFn)(CUtensorMap*, CUtensorMapDataType, cuuint32_t, void*, const cuuint64_t*, const cuuint64_t*,
                             const cuuint32_t*, const cuuint32_t*, CUtensorMapInterleave, CUtensorMapSwizzle,
                             CUtensorMapL2promotion, CUtensorMapFloatOOBfill);

static CUtensorMap make_map(EncodeFn fn, const void* ptr, uint64_t rows, uint64_t cols, uint32_t box_rows, uint32_t box_blk) {
    CUtensorMap m;
    cuuint64_t dims[3] = {64, rows, cols / 64};
    cuuint64_t strides[2] = {cols * 2, 128};
    cuuint32_t box[3] = {64, box_rows, box_blk};
    cuuint32_t es[3] = {1, 1, 1};
    fn(&m, CU_TENSOR_MAP_DATA_TYPE_BFLOAT16, 3, const_cast<void*>(ptr), dims, strides, box, es, CU_TENSOR_MAP_INTERLEAVE_NONE,
       CU_TENSOR_MAP_SWIZZLE_128B, CU_TENSOR_MAP_L2_PROMOTION_L2_256B, CU_TENSOR_MAP_FLOAT_OOB_FILL_NONE);
    return m;
}

extern "C" void kernel_launch(void* const* d_in, const int* in_sizes, int n_in, void* d_out, int out_size) {
    const bf16* x = (const bf16*)d_in[0];
    const bf16* kc = (const bf16*)d_in[1];
    const bf16* vc = (const bf16*)d_in[2];
    const bf16* wq = (const bf16*)d_in[3];
    const bf16* wo = (const bf16*)d_in[4];
    const bf16* w1 = (const bf16*)d_in[6];
    const bf16* w2 = (const bf16*)d_in[7];
    bf16* out = (bf16*)d_out;

    static EncodeFn fn = nullptr;
    static void *p_xn = nullptr, *p_h = nullptr, *p_o = nullptr, *p_g = nullptr;
    static Sched sched;
    if (!fn) {
        void* f = nullptr;
        cudaDriverEntryPointQueryResult st;
        cudaGetDriverEntryPoint("cuTensorMapEncodeTiled", &f, cudaEnableDefault, &st);
        fn = (EncodeFn)f;
        cudaGetSymbolAddress(&p_xn, g_xn);
        cudaGetSymbolAddress(&p_h, g_h);
        cudaGetSymbolAddress(&p_o, g_o);
        cudaGetSymbolAddress(&p_g, g_g);
        cudaFuncSetAttribute(attn_kernel, cudaFuncAttributeMaxDynamicSharedMemorySize, (int)sizeof(AttnSmem) + 1024);
        cudaFuncSetAttribute(oproj_kernel, cudaFuncAttributeMaxDynamicSharedMemorySize, (int)sizeof(OpSmem) + 1024);
        static uint16_t f1[NUM_CTAS][MAX_ITEMS], at[NUM_CTAS][MAX_ITEMS], f2[NUM_CTAS][MAX_ITEMS];
        static int n1[NUM_CTAS], na[NUM_CTAS], n2[NUM_CTAS];
        static double load[NUM_CTAS];
        const double C_ATT = 58.0, C_F1 = 6.5, C_F2 = 19.5;
        for (int i = 0; i < NUM_CTAS; i++) { n1[i] = na[i] = n2[i] = 0; load[i] = 0; }
        for (int t = 0; t < NH * 8; t++) {
            int cta = t % NUM_CTAS;
            at[cta][na[cta]++] = (uint16_t)((T_ATT << 12) | ((t >> 3) << 4) | (t & 7));
            load[cta] += C_ATT;
        }
        auto least = [&]() { int bi = 0; for (int i = 1; i < NUM_CTAS; i++) if (load[i] < load[bi]) bi = i; return bi; };
        for (int t = 0; t < 32; t++) {
            int cta = least();
            f2[cta][n2[cta]++] = (uint16_t)((T_F2 << 12) | ((t & 3) << 4) | (t >> 2));
            load[cta] += C_F2;
        }
        for (int t = 0; t < 112; t++) {
            int cta = least();
            f1[cta][n1[cta]++] = (uint16_t)((T_F1 << 12) | ((t % 14) << 4) | (t / 14));
            load[cta] += C_F1;
        }
        for (int i = 0; i < NUM_CTAS; i++) {
            int n = 0;
            for (int j = 0; j < n1[i]; j++) sched.item[i][n++] = f1[i][j];
            for (int j = 0; j < na[i]; j++) sched.item[i][n++] = at[i][j];
            for (int j = 0; j < n2[i]; j++) sched.item[i][n++] = f2[i][j];
            sched.count[i] = (uint8_t)n;
        }
    }
    CUtensorMap tm_xn_at = make_map(fn, p_xn, SEQ, DM, 128, 2);
    CUtensorMap tm_wq = make_map(fn, wq, DM, NH * DH, 128, 1);
    CUtensorMap tm_k = make_map(fn, kc, NH * SEQ, DH, 128, 1);
    CUtensorMap tm_v = make_map(fn, vc, NH * SEQ, DH, 128, 1);
    CUtensorMap tm_o_st = make_map(fn, p_o, SEQ, NH * DH, 64, 2);
    CUtensorMap tm_w1 = make_map(fn, w1, DM, FF, 128, 1);
    CUtensorMap tm_h_st = make_map(fn, p_h, SEQ, FF, 64, 2);
    CUtensorMap tm_h_ld = make_map(fn, p_h, SEQ, FF, 128, 2);
    CUtensorMap tm_w2 = make_map(fn, w2, FF, DM, 128, 1);
    CUtensorMap tm_g_st = make_map(fn, p_g, SEQ, DM, 64, 2);
    CUtensorMap tm_o_g = make_map(fn, p_o, SEQ, NH * DH, 128, 1);
    CUtensorMap tm_wo = make_map(fn, wo, NH * DH, DM, 64, 4);

    ln_kernel<<<SEQ / 8, 256>>>(x);
    attn_kernel<<<NUM_CTAS * 2, 384, sizeof(AttnSmem) + 1024>>>(tm_xn_at, tm_wq, tm_k, tm_v, tm_o_st, tm_w1, tm_h_st, tm_h_ld,
                                                            tm_w2, tm_g_st, sched);
    oproj_kernel<<<dim3(OP_KSPLIT, DM / 256, SEQ / 128), 384, sizeof(OpSmem) + 1024>>>(tm_o_g, tm_wo, x, out);
}
```

```cpp
#include <cuda_runtime.h>
#include <cuda_bf16.h>
#include <cuda.h>
#include <stdint.h>

typedef __nv_bfloat16 bf16;
#define PP(x) x

constexpr int SEQ = 2048, DM = 512, NH = 32, DH = 128, FF = 1792;

__device__ __align__(1024) bf16 g_xn[SEQ * DM];
__device__ __align__(1024) bf16 g_h[SEQ * FF];
__device__ __align__(1024) bf16 g_o[SEQ * NH * DH];
__device__ __align__(1024) bf16 g_g[SEQ * DM];
__device__ unsigned int g_hcnt[SEQ / 128];
__device__ float4 g_part[32 * 16 * 8 * 256];
__device__ unsigned int g_pcnt[128];
__device__ volatile float g_dummy;

__device__ __forceinline__ uint32_t smem_u32(const void* p) { return (uint32_t)__cvta_generic_to_shared(p); }

__device__ __forceinline__ void mbar_init(uint32_t bar, uint32_t count) {
    asm volatile("mbarrier.init.shared::cta.b64 [%0], %1;" ::"r"(bar), "r"(count) : "memory");
}
__device__ __forceinline__ void mbar_expect_tx(uint32_t bar, uint32_t bytes) {
    asm volatile("mbarrier.arrive.expect_tx.shared::cta.b64 _, [%0], %1;" ::"r"(bar), "r"(bytes) : "memory");
}
__device__ __forceinline__ void mbar_arrive(uint32_t bar) {
    asm volatile("mbarrier.arrive.shared::cta.b64 _, [%0];" ::"r"(bar) : "memory");
}
__device__ __forceinline__ bool mbar_try_wait(uint32_t bar, uint32_t parity) {
    uint32_t ok;
    asm volatile(
        "{\n.reg .pred p;\n"
        "mbarrier.test_wait.parity.shared::cta.b64 p, [%1], %2;\n"
        "selp.u32 %0, 1, 0, p;\n}\n"
        : "=r"(ok)
        : "r"(bar), "r"(parity)
        : "memory");
    return ok != 0;
}
__device__ __forceinline__ void mbar_wait(uint32_t bar, uint32_t parity) {
    asm volatile(
        "{\n.reg .pred P1;\n.reg .u32 n;\nmov.u32 n, 0;\n"
        "LAB_WAIT:\n"
        "mbarrier.try_wait.parity.shared::cta.b64 P1, [%0], %1;\n"
        "@P1 bra DONE;\n"
        "add.u32 n, n, 1;\n"
        "setp.lt.u32 P1, n, 4194304;\n"
        "@P1 bra LAB_WAIT;\n"
        "trap;\n"
        "DONE:\n}\n" ::"r"(bar), "r"(parity)
        : "memory");
}
__device__ __forceinline__ void tma_load_3d(uint32_t dst, const CUtensorMap* map, uint32_t bar, int c0, int c1, int c2) {
    asm volatile(
        "cp.async.bulk.tensor.3d.shared::cluster.global.mbarrier::complete_tx::bytes [%0], [%1, {%3, %4, %5}], [%2];"
        ::"r"(dst), "l"((uint64_t)map), "r"(bar), "r"(c0), "r"(c1), "r"(c2)
        : "memory");
}
__device__ __forceinline__ void tma_store_3d(const CUtensorMap* map, uint32_t src, int c0, int c1, int c2) {
    asm volatile("cp.async.bulk.tensor.3d.global.shared::cta.bulk_group [%0, {%2, %3, %4}], [%1];"
                 ::"l"((uint64_t)map), "r"(src), "r"(c0), "r"(c1), "r"(c2)
                 : "memory");
}
__device__ __forceinline__ void tma_commit() { asm volatile("cp.async.bulk.commit_group;" ::: "memory"); }
__device__ __forceinline__ void tma_wait_read0() { asm volatile("cp.async.bulk.wait_group.read 0;" ::: "memory"); }
__device__ __forceinline__ void tma_wait_all0() { asm volatile("cp.async.bulk.wait_group 0;" ::: "memory"); }
__device__ __forceinline__ void fence_proxy_async() { asm volatile("fence.proxy.async.shared::cta;" ::: "memory"); }
__device__ __forceinline__ void prefetch_tmap(const CUtensorMap* map) {
    asm volatile("prefetch.tensormap [%0];" ::"l"((uint64_t)map) : "memory");
}
__device__ __forceinline__ void named_sync(int id, int n) { asm volatile("bar.sync %0, %1;" ::"r"(id), "r"(n) : "memory"); }
__device__ __forceinline__ void named_arrive(int id, int n) { asm volatile("bar.arrive %0, %1;" ::"r"(id), "r"(n) : "memory"); }

__device__ __forceinline__ void wgmma_fence() { asm volatile("wgmma.fence.sync.aligned;" ::: "memory"); }
__device__ __forceinline__ void wgmma_commit() { asm volatile("wgmma.commit_group.sync.aligned;" ::: "memory"); }
template <int N>
__device__ __forceinline__ void wgmma_wait() { asm volatile("wgmma.wait_group.sync.aligned %0;" ::"n"(N) : "memory"); }

template <int R>
__device__ __forceinline__ void reg_alloc() { asm volatile("setmaxnreg.inc.sync.aligned.u32 %0;" ::"n"(R)); }
template <int R>
__device__ __forceinline__ void reg_dealloc() { asm volatile("setmaxnreg.dec.sync.aligned.u32 %0;" ::"n"(R)); }

__device__ __forceinline__ uint64_t make_desc(uint32_t saddr, uint32_t lbo_bytes, uint32_t sbo_bytes) {
    uint64_t d = 0;
    d |= (uint64_t)((saddr & 0x3FFFF) >> 4);
    d |= (uint64_t)((lbo_bytes >> 4) & 0x3FFF) << 16;
    d |= (uint64_t)((sbo_bytes >> 4) & 0x3FFF) << 32;
    d |= (uint64_t)1 << 62;
    return d;
}

__device__ __forceinline__ float ex2(float x) {
    float y;
    asm volatile("ex2.approx.ftz.f32 %0, %1;" : "=f"(y) : "f"(x));
    return y;
}
__device__ __forceinline__ uint32_t pack_bf16(float lo, float hi) {
    uint32_t r;
    asm("cvt.rn.bf16x2.f32 %0, %1, %2;" : "=r"(r) : "f"(hi), "f"(lo));
    return r;
}
__device__ __forceinline__ uint32_t mul_bf16x2(uint32_t a, uint32_t b) {
    uint32_t r;
    asm("mul.rn.bf16x2 %0, %1, %2;" : "=r"(r) : "r"(a), "r"(b));
    return r;
}
__device__ __forceinline__ uint32_t fma_bf16x2(uint32_t a, uint32_t b, uint32_t c) {
    uint32_t r;
    asm("fma.rn.bf16x2 %0, %1, %2, %3;" : "=r"(r) : "r"(a), "r"(b), "r"(c));
    return r;
}
__device__ __forceinline__ uint32_t max_bf16x2(uint32_t a, uint32_t b) {
    uint32_t r;
    asm("max.bf16x2 %0, %1, %2;" : "=r"(r) : "r"(a), "r"(b));
    return r;
}
__device__ __forceinline__ float bf16lo(uint32_t v) { return __uint_as_float(v << 16); }
__device__ __forceinline__ float bf16hi(uint32_t v) { return __uint_as_float(v & 0xffff0000u); }
__device__ __forceinline__ float bf16_round(float x) { return __bfloat162float(__float2bfloat16_rn(x)); }
__device__ __forceinline__ float silu_f(float x) { return __fdividef(x, 1.0f + __expf(-x)); }

__device__ __forceinline__ void stmatrix_x4(uint32_t addr, uint32_t r0, uint32_t r1, uint32_t r2, uint32_t r3) {
    asm volatile("stmatrix.sync.aligned.m8n8.x4.shared.b16 [%0], {%1, %2, %3, %4};"
                 ::"r"(addr), "r"(r0), "r"(r1), "r"(r2), "r"(r3)
                 : "memory");
}

#define ACC64(d) \
    "+f"(d[0]), "+f"(d[1]), "+f"(d[2]), "+f"(d[3]), "+f"(d[4]), "+f"(d[5]), "+f"(d[6]), "+f"(d[7]), \
    "+f"(d[8]), "+f"(d[9]), "+f"(d[10]), "+f"(d[11]), "+f"(d[12]), "+f"(d[13]), "+f"(d[14]), "+f"(d[15]), \
    "+f"(d[16]), "+f"(d[17]), "+f"(d[18]), "+f"(d[19]), "+f"(d[20]), "+f"(d[21]), "+f"(d[22]), "+f"(d[23]), \
    "+f"(d[24]), "+f"(d[25]), "+f"(d[26]), "+f"(d[27]), "+f"(d[28]), "+f"(d[29]), "+f"(d[30]), "+f"(d[31]), \
    "+f"(d[32]), "+f"(d[33]), "+f"(d[34]), "+f"(d[35]), "+f"(d[36]), "+f"(d[37]), "+f"(d[38]), "+f"(d[39]), \
    "+f"(d[40]), "+f"(d[41]), "+f"(d[42]), "+f"(d[43]), "+f"(d[44]), "+f"(d[45]), "+f"(d[46]), "+f"(d[47]), \
    "+f"(d[48]), "+f"(d[49]), "+f"(d[50]), "+f"(d[51]), "+f"(d[52]), "+f"(d[53]), "+f"(d[54]), "+f"(d[55]), \
    "+f"(d[56]), "+f"(d[57]), "+f"(d[58]), "+f"(d[59]), "+f"(d[60]), "+f"(d[61]), "+f"(d[62]), "+f"(d[63])

#define ACC64_STR \
    "{%0, %1, %2, %3, %4, %5, %6, %7, %8, %9, %10, %11, %12, %13, %14, %15, " \
    "%16, %17, %18, %19, %20, %21, %22, %23, %24, %25, %26, %27, %28, %29, %30, %31, " \
    "%32, %33, %34, %35, %36, %37, %38, %39, %40, %41, %42, %43, %44, %45, %46, %47, " \
    "%48, %49, %50, %51, %52, %53, %54, %55, %56, %57, %58, %59, %60, %61, %62, %63}"

template <int TB>
__device__ __forceinline__ void wgmma_ss_n128(float (&d)[64], uint64_t da, uint64_t db, int scale_d) {
    asm volatile(
        "{\n.reg .pred p;\nsetp.ne.b32 p, %66, 0;\n"
        "wgmma.mma_async.sync.aligned.m64n128k16.f32.bf16.bf16 " ACC64_STR ", %64, %65, p, 1, 1, 0, %67;\n}\n"
        : ACC64(d)
        : "l"(da), "l"(db), "r"(scale_d), "n"(TB));
}
template <int TB>
__device__ __forceinline__ void wgmma_rs_n128(float (&d)[64], uint32_t a0, uint32_t a1, uint32_t a2, uint32_t a3,
                                              uint64_t db, int scale_d) {
    asm volatile(
        "{\n.reg .pred p;\nsetp.ne.b32 p, %69, 0;\n"
        "wgmma.mma_async.sync.aligned.m64n128k16.f32.bf16.bf16 " ACC64_STR ", {%64, %65, %66, %67}, %68, p, 1, 1, %70;\n}\n"
        : ACC64(d)
        : "r"(a0), "r"(a1), "r"(a2), "r"(a3), "l"(db), "r"(scale_d), "n"(TB));
}

constexpr uint32_t DESC_HI = 0x40000040u;
__device__ __forceinline__ uint32_t desc_lo(uint32_t saddr, uint32_t lbo_bytes) {
    return ((saddr & 0x3FFFF) >> 4) | ((lbo_bytes >> 4) << 16);
}
template <int TB>
__device__ __forceinline__ void wgmma_ss_lo(float (&d)[64], uint32_t da, uint32_t db, int scale_d) {
    asm volatile(
        "{\n.reg .pred p;\n.reg .b64 xa, xb;\nsetp.ne.b32 p, %66, 0;\n"
        "mov.b64 xa, {%64, %68};\nmov.b64 xb, {%65, %68};\n"
        "wgmma.mma_async.sync.aligned.m64n128k16.f32.bf16.bf16 " ACC64_STR ", xa, xb, p, 1, 1, 0, %67;\n}\n"
        : ACC64(d)
        : "r"(da), "r"(db), "r"(scale_d), "n"(TB), "r"(DESC_HI));
}
__device__ __forceinline__ void wgmma_rs_lo_tb(float (&d)[64], uint32_t a0, uint32_t a1, uint32_t a2, uint32_t a3, uint32_t db) {
    asm volatile(
        "{\n.reg .b64 xb;\nmov.b64 xb, {%68, %69};\n"
        "wgmma.mma_async.sync.aligned.m64n128k16.f32.bf16.bf16 " ACC64_STR ", {%64, %65, %66, %67}, xb, 1, 1, 1, 1;\n}\n"
        : ACC64(d)
        : "r"(a0), "r"(a1), "r"(a2), "r"(a3), "r"(db), "r"(DESC_HI));
}

__global__ void __launch_bounds__(256) ln_kernel(const bf16* __restrict__ x) {
    int warp = threadIdx.x >> 5, lane = threadIdx.x & 31;
    int row = blockIdx.x * 8 + warp;
    if (blockIdx.x == 0 && threadIdx.x < SEQ / 128) g_hcnt[threadIdx.x] = 0;
    if (blockIdx.x == 1 && threadIdx.x < 128) g_pcnt[threadIdx.x] = 0;
    const uint4* src = reinterpret_cast<const uint4*>(x + (size_t)row * DM);
    uint4 v[2];
    v[0] = src[lane];
    v[1] = src[lane + 32];
    float f[16];
#pragma unroll
    for (int i = 0; i < 2; i++) {
        const __nv_bfloat162* p = reinterpret_cast<const __nv_bfloat162*>(&v[i]);
#pragma unroll
        for (int j = 0; j < 4; j++) {
            float2 t = __bfloat1622float2(p[j]);
            f[i * 8 + j * 2] = t.x;
            f[i * 8 + j * 2 + 1] = t.y;
        }
    }
    float s = 0.f;
#pragma unroll
    for (int i = 0; i < 16; i++) s += f[i];
#pragma unroll
    for (int o = 16; o > 0; o >>= 1) s += __shfl_xor_sync(0xffffffffu, s, o);
    float mean = s * (1.0f / DM);
    float q = 0.f;
#pragma unroll
    for (int i = 0; i < 16; i++) {
        float d = f[i] - mean;
        q += d * d;
    }
#pragma unroll
    for (int o = 16; o > 0; o >>= 1) q += __shfl_xor_sync(0xffffffffu, q, o);
    float var_b = bf16_round(q * (1.0f / DM));
    float mean_b = bf16_round(mean);
    float den = bf16_round(sqrtf(bf16_round(var_b + 1e-5f)));
    uint4 o[2];
#pragma unroll
    for (int i = 0; i < 2; i++) {
        uint32_t* p = reinterpret_cast<uint32_t*>(&o[i]);
#pragma unroll
        for (int j = 0; j < 4; j++) {
            float a = bf16_round(f[i * 8 + j * 2] - mean_b) / den;
            float b = bf16_round(f[i * 8 + j * 2 + 1] - mean_b) / den;
            p[j] = pack_bf16(a, b);
        }
    }
    uint4* dst = reinterpret_cast<uint4*>(g_xn + (size_t)row * DM);
    dst[lane] = o[0];
    dst[lane + 32] = o[1];
}

constexpr int AT_STAGES = 3;
constexpr int TILE_BYTES = 128 * 128 * 2;
struct __align__(1024) AttnSmem {
    uint8_t k[AT_STAGES][TILE_BYTES];
    uint8_t v[AT_STAGES][TILE_BYTES];
    uint8_t o[TILE_BYTES];
    uint64_t full_k[AT_STAGES], full_v[AT_STAGES], empty_k[AT_STAGES], empty_v[AT_STAGES];
};

constexpr int NUM_CTAS = 132;
constexpr int MAX_ITEMS = 12;
enum { T_ATT = 0, T_F1 = 1, T_F2 = 2 };
struct Sched {
    uint16_t item[NUM_CTAS][MAX_ITEMS];
    uint8_t count[NUM_CTAS];
};

__global__ void __launch_bounds__(384, 1)
attn_kernel(const __grid_constant__ CUtensorMap tm_xn, const __grid_constant__ CUtensorMap tm_wq,
            const __grid_constant__ CUtensorMap tm_k, const __grid_constant__ CUtensorMap tm_v,
            const __grid_constant__ CUtensorMap tm_o, const __grid_constant__ CUtensorMap tm_w1,
            const __grid_constant__ CUtensorMap tm_hst, const __grid_constant__ CUtensorMap tm_hld,
            const __grid_constant__ CUtensorMap tm_w2, const __grid_constant__ CUtensorMap tm_gst,
            const __grid_constant__ Sched sched) {
    extern __shared__ uint8_t smem_raw[];
    AttnSmem& sm = *reinterpret_cast<AttnSmem*>((reinterpret_cast<uintptr_t>(smem_raw) + 1023) & ~uintptr_t(1023));
    const int tid = threadIdx.x;
    const int wg = __shfl_sync(0xffffffffu, tid >> 7, 0);
    const int n_items = sched.count[blockIdx.x];

    if (tid == 0) {
#pragma unroll
        for (int s = 0; s < AT_STAGES; s++) {
            mbar_init(smem_u32(&sm.full_k[s]), 1);
            mbar_init(smem_u32(&sm.full_v[s]), 1);
            mbar_init(smem_u32(&sm.empty_k[s]), 8);
            mbar_init(smem_u32(&sm.empty_v[s]), 8);
        }
        asm volatile("fence.mbarrier_init.release.cluster;" ::: "memory");
    }
    __syncthreads();

    if (wg == 0) {
        reg_dealloc<24>();
        if (tid == 0) {
            int stage = 0;
            uint32_t phase = 0;
            for (int it = 0; it < n_items; it++) {
                const int item = sched.item[blockIdx.x][it];
                const int type = item >> 12, a = (item >> 4) & 0xff, b = item & 15;
                const CUtensorMap* ta = (type == T_F2) ? &tm_hld : &tm_xn;
                const CUtensorMap* tb = (type == T_ATT) ? &tm_wq : (type == T_F1 ? &tm_w1 : &tm_w2);
                const int nch = (type == T_F2) ? FF / 128 : DM / 128;
                if (type == T_F2) {
                    unsigned int v, spins = 0;
                    do {
                        asm volatile("ld.acquire.gpu.global.u32 %0, [%1];" : "=r"(v) : "l"(&g_hcnt[b]) : "memory");
                    } while (v < 2 * (FF / 128) && ++spins < (1u << 24));
                    asm volatile("fence.proxy.async;" ::: "memory");
                }
                for (int kc = 0; kc < nch; kc++) {
                    mbar_wait(smem_u32(&sm.empty_k[stage]), phase ^ 1);
                    mbar_expect_tx(smem_u32(&sm.full_k[stage]), TILE_BYTES);
                    tma_load_3d(smem_u32(sm.k[stage]), ta, smem_u32(&sm.full_k[stage]), 0, b * 128, kc * 2);
                    mbar_wait(smem_u32(&sm.empty_v[stage]), phase ^ 1);
                    mbar_expect_tx(smem_u32(&sm.full_v[stage]), TILE_BYTES);
                    tma_load_3d(smem_u32(sm.v[stage]), tb, smem_u32(&sm.full_v[stage]), 0, kc * 128, a * 2);
                    if (++stage == AT_STAGES) { stage = 0; phase ^= 1; }
                }
                if (type == T_ATT) {
                    for (int j = 0; j < 16; j++) {
                        mbar_wait(smem_u32(&sm.empty_k[stage]), phase ^ 1);
                        mbar_expect_tx(smem_u32(&sm.full_k[stage]), TILE_BYTES);
                        tma_load_3d(smem_u32(sm.k[stage]), &tm_k, smem_u32(&sm.full_k[stage]), 0, a * SEQ + j * 128, 0);
                        mbar_wait(smem_u32(&sm.empty_v[stage]), phase ^ 1);
                        mbar_expect_tx(smem_u32(&sm.full_v[stage]), TILE_BYTES);
                        tma_load_3d(smem_u32(sm.v[stage]), &tm_v, smem_u32(&sm.full_v[stage]), 0, a * SEQ + j * 128, 0);
                        if (++stage == AT_STAGES) { stage = 0; phase ^= 1; }
                    }
                }
            }
        }
    } else {
        reg_alloc<240>();
        const int cw = wg - 1;
        const int lane = tid & 31;
        const int warp_in_wg = (tid >> 5) & 3;
        const float c = 1.4426950408889634f;
        const uint32_t SCALE_HI2 = 0x3DB53DB5u, SCALE_LO2 = 0x371E371Eu;
        constexpr int BAR_SCHED0 = 1, BAR_EPI0 = 3;
        const uint32_t obase = smem_u32(sm.o) + cw * 16384;
        const int st_row = warp_in_wg * 16 + ((lane >> 3) & 1) * 8 + (lane & 7);

        PP(if (cw == 1) named_arrive(BAR_SCHED0 + 0, 256));

        int stage = 0;
        uint32_t phase = 0;
        int pending_mb = -1;
        float S[64], O[64];
        uint32_t P[32], P2[32];

        for (int it = 0; it < n_items; it++) {
            const int item = sched.item[blockIdx.x][it];
            const int type = item >> 12, ia = (item >> 4) & 0xff, ib = item & 15;
            const int nch = (type == T_F2) ? FF / 128 : DM / 128;
            {
                int prev = -1;
#pragma unroll 1
                for (int kc = 0; kc < nch; kc++) {
                    mbar_wait(smem_u32(&sm.full_k[stage]), phase);
                    mbar_wait(smem_u32(&sm.full_v[stage]), phase);
                    const uint64_t da = make_desc(smem_u32(sm.k[stage]) + cw * 64 * 128, 16, 1024);
                    const uint64_t db = make_desc(smem_u32(sm.v[stage]), 16384, 1024);
                    wgmma_fence();
#pragma unroll
                    for (int kk = 0; kk < 8; kk++) {
                        wgmma_ss_n128<1>(S, da + (uint64_t)(((kk >> 2) * 16384 + (kk & 3) * 32) >> 4),
                                         db + (uint64_t)((kk * 2048) >> 4), (kc | kk) != 0);
                    }
                    wgmma_commit();
                    wgmma_wait<1>();
                    if (prev >= 0 && lane == 0) {
                        mbar_arrive(smem_u32(&sm.empty_k[prev]));
                        mbar_arrive(smem_u32(&sm.empty_v[prev]));
                    }
                    prev = stage;
                    if (++stage == AT_STAGES) { stage = 0; phase ^= 1; }
                }
                wgmma_wait<0>();
                if (lane == 0) {
                    mbar_arrive(smem_u32(&sm.empty_k[prev]));
                    mbar_arrive(smem_u32(&sm.empty_v[prev]));
                }
            }
            if (type != T_ATT) {
#pragma unroll
                for (int i = 0; i < 64; i++) S[i] = silu_f(bf16_round(S[i]));
            }
            if ((tid & 127) == 0) {
                if (pending_mb >= 0) {
                    tma_wait_all0();
                    asm volatile("fence.proxy.async;" ::: "memory");
                    __threadfence();
                    atomicAdd(&g_hcnt[pending_mb], 1u);
                } else {
                    tma_wait_read0();
                }
            }
            pending_mb = -1;
            named_sync(BAR_EPI0 + cw, 128);
#pragma unroll
            for (int i = 0; i < 16; i += 2) {
                const int cc = i + (lane >> 4);
                const uint32_t addr = obase + (cc >> 3) * 8192 + st_row * 128 + (((cc & 7) ^ (st_row & 7)) << 4);
                stmatrix_x4(addr, pack_bf16(S[4 * i], S[4 * i + 1]), pack_bf16(S[4 * i + 2], S[4 * i + 3]),
                            pack_bf16(S[4 * i + 4], S[4 * i + 5]), pack_bf16(S[4 * i + 6], S[4 * i + 7]));
            }
            fence_proxy_async();
            named_sync(BAR_EPI0 + cw, 128);
            if (type != T_ATT) {
                if ((tid & 127) == 0) {
                    tma_store_3d(type == T_F1 ? &tm_hst : &tm_gst, obase, 0, ib * 128 + cw * 64, ia * 2);
                    tma_commit();
                }
                if (type == T_F1) pending_mb = ib;
                continue;
            }
            const uint32_t dq = desc_lo(obase, 16);
#pragma unroll
            for (int i = 0; i < 64; i++) O[i] = 0.f;

            float m0 = -INFINITY, m1 = -INFINITY, l0 = 0.f, l1 = 0.f, a0 = 0.f, a1 = 0.f;
            bool resc = false;
            const float TAU = 11.0f;
            const uint32_t dk0 = desc_lo(smem_u32(sm.k[0]), 16), dv0 = desc_lo(smem_u32(sm.v[0]), 16384);
            const uint32_t fk0 = smem_u32(&sm.full_k[0]), fv0 = smem_u32(&sm.full_v[0]);
            const uint32_t ek0 = smem_u32(&sm.empty_k[0]), ev0 = smem_u32(&sm.empty_v[0]);

            auto softmax = [&](uint32_t (&Pn)[32]) {
                uint32_t T[32];
#pragma unroll
                for (int i = 0; i < 32; i++) {
                    const uint32_t sb = pack_bf16(S[2 * i], S[2 * i + 1]);
                    T[i] = fma_bf16x2(sb, SCALE_HI2, mul_bf16x2(sb, SCALE_LO2));
                }
                uint32_t y0 = max_bf16x2(T[0], T[2]), y1 = max_bf16x2(T[1], T[3]);
#pragma unroll
                for (int i = 2; i < 16; i++) {
                    y0 = max_bf16x2(y0, T[2 * i]);
                    y1 = max_bf16x2(y1, T[2 * i + 1]);
                }
                float x0 = fmaxf(bf16lo(y0), bf16hi(y0));
                float x1 = fmaxf(bf16lo(y1), bf16hi(y1));
                x0 = fmaxf(x0, __shfl_xor_sync(0xffffffffu, x0, 1));
                x1 = fmaxf(x1, __shfl_xor_sync(0xffffffffu, x1, 1));
                x0 = fmaxf(x0, __shfl_xor_sync(0xffffffffu, x0, 2));
                x1 = fmaxf(x1, __shfl_xor_sync(0xffffffffu, x1, 2));
                resc = __any_sync(0xffffffffu, (x0 - m0 > TAU) || (x1 - m1 > TAU));
                x0 = resc ? fmaxf(x0, m0) : m0;
                x1 = resc ? fmaxf(x1, m1) : m1;
                a0 = ex2((m0 - x0) * c);
                a1 = ex2((m1 - x1) * c);
                m0 = x0;
                m1 = x1;
                const float n0 = -m0 * c, n1 = -m1 * c;
                float s0 = 0.f, s1 = 0.f;
#pragma unroll
                for (int i = 0; i < 16; i++) {
                    const float e0 = ex2(fmaf(bf16lo(T[2 * i]), c, n0));
                    const float e1 = ex2(fmaf(bf16hi(T[2 * i]), c, n0));
                    const float e2 = ex2(fmaf(bf16lo(T[2 * i + 1]), c, n1));
                    const float e3 = ex2(fmaf(bf16hi(T[2 * i + 1]), c, n1));
                    s0 += e0 + e1;
                    s1 += e2 + e3;
                    Pn[2 * i] = pack_bf16(e0, e1);
                    Pn[2 * i + 1] = pack_bf16(e2, e3);
                }
                l0 = l0 * a0 + s0;
                l1 = l1 * a1 + s1;
                while (s0 + s1 < 0.f) s0 = g_dummy;
            };
            auto issue_qk = [&](uint32_t dk) {
                wgmma_fence();
#pragma unroll
                for (int kk = 0; kk < 8; kk++)
                    wgmma_ss_lo<0>(S, dq + (((kk >> 2) * 8192 + (kk & 3) * 32) >> 4),
                                   dk + (((kk >> 2) * 16384 + (kk & 3) * 32) >> 4), kk != 0);
                wgmma_commit();
            };
            auto issue_pv = [&](uint32_t (&Pc)[32], uint32_t dv) {
                if (resc) {
#pragma unroll
                    for (int i = 0; i < 16; i++) {
                        O[4 * i] *= a0;
                        O[4 * i + 1] *= a0;
                        O[4 * i + 2] *= a1;
                        O[4 * i + 3] *= a1;
                    }
                }
                wgmma_fence();
#pragma unroll
                for (int kk = 0; kk < 8; kk++)
                    wgmma_rs_lo_tb(O, Pc[4 * kk], Pc[4 * kk + 1], Pc[4 * kk + 2], Pc[4 * kk + 3], dv + ((kk * 2048) >> 4));
                wgmma_commit();
            };

            int vstage = stage;
            uint32_t vphase = phase;
            bool okk, okv;
            {
                mbar_wait(fk0 + stage * 8, phase);
                PP(named_sync(BAR_SCHED0 + cw, 256));
                issue_qk(dk0 + stage * (TILE_BYTES >> 4));
                PP(named_arrive(BAR_SCHED0 + (cw ^ 1), 256));
                if (++stage == AT_STAGES) { stage = 0; phase ^= 1; }
                okk = mbar_try_wait(fk0 + stage * 8, phase);
                okv = mbar_try_wait(fv0 + vstage * 8, vphase);
                wgmma_wait<0>();
                if (lane == 0) mbar_arrive(ek0 + vstage * 8);
            }
            softmax(P);
            resc = false;

            auto step = [&](uint32_t (&Pc)[32], uint32_t (&Pn)[32]) {
                const int ust = __shfl_sync(0xffffffffu, stage, 0), uvs = __shfl_sync(0xffffffffu, vstage, 0);
                if (!okk) mbar_wait(fk0 + stage * 8, phase);
                if (!okv) mbar_wait(fv0 + vstage * 8, vphase);
                PP(named_sync(BAR_SCHED0 + cw, 256));
                issue_qk(dk0 + ust * (TILE_BYTES >> 4));
                issue_pv(Pc, dv0 + uvs * (TILE_BYTES >> 4));
                PP(named_arrive(BAR_SCHED0 + (cw ^ 1), 256));
                const int pv = vstage;
                vstage = stage;
                vphase = phase;
                if (++stage == AT_STAGES) { stage = 0; phase ^= 1; }
                okk = mbar_try_wait(fk0 + stage * 8, phase);
                okv = mbar_try_wait(fv0 + vstage * 8, vphase);
                wgmma_wait<1>();
                if (lane == 0) mbar_arrive(ek0 + vstage * 8);
                softmax(Pn);
                wgmma_wait<0>();
                if (lane == 0) mbar_arrive(ev0 + pv * 8);
            };
#pragma unroll 1
            for (int j = 0; j < 7; j++) {
                step(P, P2);
                step(P2, P);
            }
            step(P, P2);
            if (!okv) mbar_wait(fv0 + vstage * 8, vphase);
            issue_pv(P2, dv0 + vstage * (TILE_BYTES >> 4));
            wgmma_wait<0>();
            if (lane == 0) mbar_arrive(ev0 + vstage * 8);
            l0 += __shfl_xor_sync(0xffffffffu, l0, 1);
            l1 += __shfl_xor_sync(0xffffffffu, l1, 1);
            l0 += __shfl_xor_sync(0xffffffffu, l0, 2);
            l1 += __shfl_xor_sync(0xffffffffu, l1, 2);
            const float i0 = 1.0f / l0, i1 = 1.0f / l1;
            named_sync(BAR_EPI0 + cw, 128);
#pragma unroll
            for (int i = 0; i < 16; i += 2) {
                const int cc = i + (lane >> 4);
                const uint32_t addr = obase + (cc >> 3) * 8192 + st_row * 128 + (((cc & 7) ^ (st_row & 7)) << 4);
                stmatrix_x4(addr, pack_bf16(O[4 * i] * i0, O[4 * i + 1] * i0), pack_bf16(O[4 * i + 2] * i1, O[4 * i + 3] * i1),
                            pack_bf16(O[4 * i + 4] * i0, O[4 * i + 5] * i0), pack_bf16(O[4 * i + 6] * i1, O[4 * i + 7] * i1));
            }
            fence_proxy_async();
            named_sync(BAR_EPI0 + cw, 128);
            if ((tid & 127) == 0) {
                tma_store_3d(&tm_o, obase, 0, ib * 128 + cw * 64, ia * 2);
                tma_commit();
            }
        }
        if ((tid & 127) == 0) {
            tma_wait_all0();
            if (pending_mb >= 0) {
                asm volatile("fence.proxy.async;" ::: "memory");
                __threadfence();
                atomicAdd(&g_hcnt[pending_mb], 1u);
            }
        }
    }
}

constexpr int OP_STAGES = 4;
constexpr int OP_KSPLIT = 4;
struct __align__(1024) OpSmem {
    uint8_t a[OP_STAGES][128 * 64 * 2];
    uint8_t b[OP_STAGES][64 * 256 * 2];
    uint64_t full[OP_STAGES], empty[OP_STAGES];
};

#define ACC8(d, o) "+f"(d[o]), "+f"(d[o + 1]), "+f"(d[o + 2]), "+f"(d[o + 3]), "+f"(d[o + 4]), "+f"(d[o + 5]), "+f"(d[o + 6]), "+f"(d[o + 7])
__device__ __forceinline__ void wgmma_ss_n256_tb(float (&d)[128], uint64_t da, uint64_t db, int scale_d) {
    asm volatile(
        "{\n.reg .pred p;\nsetp.ne.b32 p, %130, 0;\n"
        "wgmma.mma_async.sync.aligned.m64n256k16.f32.bf16.bf16 "
        "{%0, %1, %2, %3, %4, %5, %6, %7, %8, %9, %10, %11, %12, %13, %14, %15, "
        "%16, %17, %18, %19, %20, %21, %22, %23, %24, %25, %26, %27, %28, %29, %30, %31, "
        "%32, %33, %34, %35, %36, %37, %38, %39, %40, %41, %42, %43, %44, %45, %46, %47, "
        "%48, %49, %50, %51, %52, %53, %54, %55, %56, %57, %58, %59, %60, %61, %62, %63, "
        "%64, %65, %66, %67, %68, %69, %70, %71, %72, %73, %74, %75, %76, %77, %78, %79, "
        "%80, %81, %82, %83, %84, %85, %86, %87, %88, %89, %90, %91, %92, %93, %94, %95, "
        "%96, %97, %98, %99, %100, %101, %102, %103, %104, %105, %106, %107, %108, %109, %110, %111, "
        "%112, %113, %114, %115, %116, %117, %118, %119, %120, %121, %122, %123, %124, %125, %126, %127}, "
        "%128, %129, p, 1, 1, 0, 1;\n}\n"
        : ACC8(d, 0), ACC8(d, 8), ACC8(d, 16), ACC8(d, 24), ACC8(d, 32), ACC8(d, 40), ACC8(d, 48), ACC8(d, 56),
          ACC8(d, 64), ACC8(d, 72), ACC8(d, 80), ACC8(d, 88), ACC8(d, 96), ACC8(d, 104), ACC8(d, 112), ACC8(d, 120)
        : "l"(da), "l"(db), "r"(scale_d));
}
__device__ __forceinline__ void cluster_sync_all() {
    asm volatile("barrier.cluster.arrive.release.aligned;\nbarrier.cluster.wait.acquire.aligned;" ::: "memory");
}

__global__ void __launch_bounds__(384, 1)
oproj_kernel(const __grid_constant__ CUtensorMap tm_o, const __grid_constant__ CUtensorMap tm_wo,
             const bf16* __restrict__ x, bf16* __restrict__ out) {
    extern __shared__ uint8_t smem_raw[];
    OpSmem& sm = *reinterpret_cast<OpSmem*>((reinterpret_cast<uintptr_t>(smem_raw) + 1023) & ~uintptr_t(1023));
    const int tid = threadIdx.x, wg = tid >> 7;
    const int kr = blockIdx.x;
    const int n0 = blockIdx.y * 256, m0 = blockIdx.z * 128;
    const int tile = blockIdx.y + 2 * blockIdx.z;
    constexpr int KT = NH * DH / OP_KSPLIT / 64;
    if (tid == 0) {
        for (int s = 0; s < OP_STAGES; s++) {
            mbar_init(smem_u32(&sm.full[s]), 1);
            mbar_init(smem_u32(&sm.empty[s]), 8);
        }
        asm volatile("fence.mbarrier_init.release.cluster;" ::: "memory");
    }
    __syncthreads();
    if (wg == 0) {
        reg_dealloc<40>();
        if (tid == 0) {
            int stage = 0;
            uint32_t phase = 0;
            for (int kt = 0; kt < KT; kt++) {
                const int kg = kr * KT + kt;
                mbar_wait(smem_u32(&sm.empty[stage]), phase ^ 1);
                mbar_expect_tx(smem_u32(&sm.full[stage]), 49152);
                tma_load_3d(smem_u32(sm.a[stage]), &tm_o, smem_u32(&sm.full[stage]), 0, m0, kg);
                tma_load_3d(smem_u32(sm.b[stage]), &tm_wo, smem_u32(&sm.full[stage]), 0, kg * 64, n0 >> 6);
                if (++stage == OP_STAGES) { stage = 0; phase ^= 1; }
            }
        }
    } else {
        reg_alloc<232>();
        const int cw = wg - 1, lane = tid & 31, warp_in_wg = (tid >> 5) & 3;
        const int ct = tid - 128;
        float acc[128];
        const int r0 = m0 + cw * 64 + warp_in_wg * 16 + (lane >> 2);
        uint32_t xv[16], gv[16];
#pragma unroll
        for (int j = 0; j < 8; j++) {
#pragma unroll
            for (int hh = 0; hh < 2; hh++) {
                const size_t off = (size_t)(r0 + hh * 8) * DM + n0 + kr * 64 + j * 8 + (lane & 3) * 2;
                xv[2 * j + hh] = *reinterpret_cast<const uint32_t*>(x + off);
                gv[2 * j + hh] = *reinterpret_cast<const uint32_t*>(g_g + off);
            }
        }
        int stage = 0, prev = -1;
        uint32_t phase = 0;
#pragma unroll 1
        for (int kt = 0; kt < KT; kt++) {
            mbar_wait(smem_u32(&sm.full[stage]), phase);
            const uint64_t da = make_desc(smem_u32(sm.a[stage]) + cw * 64 * 128, 16, 1024);
            const uint64_t db = make_desc(smem_u32(sm.b[stage]), 8192, 1024);
            wgmma_fence();
#pragma unroll
            for (int kk = 0; kk < 4; kk++)
                wgmma_ss_n256_tb(acc, da + (uint64_t)((kk * 32) >> 4), db + (uint64_t)((kk * 2048) >> 4), (kt | kk) != 0);
            wgmma_commit();
            wgmma_wait<1>();
            if (prev >= 0 && lane == 0) mbar_arrive(smem_u32(&sm.empty[prev]));
            prev = stage;
            if (++stage == OP_STAGES) { stage = 0; phase ^= 1; }
        }
        wgmma_wait<0>();
        float4* part = g_part + (size_t)tile * (OP_KSPLIT * OP_KSPLIT * 8 * 256);
#pragma unroll
        for (int d = 0; d < OP_KSPLIT; d++) {
            if (d == kr) continue;
#pragma unroll
            for (int j = 0; j < 8; j++)
                __stcg(part + ((d * OP_KSPLIT + kr) * 8 + j) * 256 + ct,
                       make_float4(acc[(8 * d + j) * 4], acc[(8 * d + j) * 4 + 1], acc[(8 * d + j) * 4 + 2], acc[(8 * d + j) * 4 + 3]));
        }
        __threadfence();
        named_sync(1, 256);
        if (ct < OP_KSPLIT && ct != kr)
            asm volatile("red.release.gpu.global.add.u32 [%0], 1;" ::"l"(&g_pcnt[tile * OP_KSPLIT + ct]) : "memory");
        float r[32];
#pragma unroll
        for (int d = 0; d < OP_KSPLIT; d++) {
            if (d == kr) {
#pragma unroll
                for (int i = 0; i < 32; i++) r[i] = acc[32 * d + i];
            }
        }
        if (ct == 0) {
            unsigned int v, spins = 0;
            do {
                asm volatile("ld.acquire.gpu.global.u32 %0, [%1];" : "=r"(v) : "l"(&g_pcnt[tile * OP_KSPLIT + kr]) : "memory");
            } while (v < OP_KSPLIT - 1 && ++spins < (1u << 24));
        }
        named_sync(1, 256);
#pragma unroll
        for (int sr = 0; sr < OP_KSPLIT; sr++) {
            if (sr == kr) continue;
#pragma unroll
            for (int j = 0; j < 8; j++) {
                const float4 v = __ldcg(part + ((kr * OP_KSPLIT + sr) * 8 + j) * 256 + ct);
                r[4 * j] += v.x;
                r[4 * j + 1] += v.y;
                r[4 * j + 2] += v.z;
                r[4 * j + 3] += v.w;
            }
        }
#pragma unroll
        for (int j = 0; j < 8; j++) {
#pragma unroll
            for (int hh = 0; hh < 2; hh++) {
                const size_t off = (size_t)(r0 + hh * 8) * DM + n0 + kr * 64 + j * 8 + (lane & 3) * 2;
                const float s0 = bf16_round(r[4 * j + 2 * hh]), s1 = bf16_round(r[4 * j + 2 * hh + 1]);
                const float o0 = bf16lo(xv[2 * j + hh]) + bf16_round(s0 * bf16lo(gv[2 * j + hh]));
                const float o1 = bf16hi(xv[2 * j + hh]) + bf16_round(s1 * bf16hi(gv[2 * j + hh]));
                *reinterpret_cast<uint32_t*>(out + off) = pack_bf16(o0, o1);
            }
        }
    }
}

typedef CUresult (*EncodeFn)(CUtensorMap*, CUtensorMapDataType, cuuint32_t, void*, const cuuint64_t*, const cuuint64_t*,
                             const cuuint32_t*, const cuuint32_t*, CUtensorMapInterleave, CUtensorMapSwizzle,
                             CUtensorMapL2promotion, CUtensorMapFloatOOBfill);

static CUtensorMap make_map(EncodeFn fn, const void* ptr, uint64_t rows, uint64_t cols, uint32_t box_rows, uint32_t box_blk) {
    CUtensorMap m;
    cuuint64_t dims[3] = {64, rows, cols / 64};
    cuuint64_t strides[2] = {cols * 2, 128};
    cuuint32_t box[3] = {64, box_rows, box_blk};
    cuuint32_t es[3] = {1, 1, 1};
    fn(&m, CU_TENSOR_MAP_DATA_TYPE_BFLOAT16, 3, const_cast<void*>(ptr), dims, strides, box, es, CU_TENSOR_MAP_INTERLEAVE_NONE,
       CU_TENSOR_MAP_SWIZZLE_128B, CU_TENSOR_MAP_L2_PROMOTION_L2_256B, CU_TENSOR_MAP_FLOAT_OOB_FILL_NONE);
    return m;
}

extern "C" void kernel_launch(void* const* d_in, const int* in_sizes, int n_in, void* d_out, int out_size) {
    const bf16* x = (const bf16*)d_in[0];
    const bf16* kc = (const bf16*)d_in[1];
    const bf16* vc = (const bf16*)d_in[2];
    const bf16* wq = (const bf16*)d_in[3];
    const bf16* wo = (const bf16*)d_in[4];
    const bf16* w1 = (const bf16*)d_in[6];
    const bf16* w2 = (const bf16*)d_in[7];
    bf16* out = (bf16*)d_out;

    static EncodeFn fn = nullptr;
    static void *p_xn = nullptr, *p_h = nullptr, *p_o = nullptr, *p_g = nullptr;
    static Sched sched;
    if (!fn) {
        void* f = nullptr;
        cudaDriverEntryPointQueryResult st;
        cudaGetDriverEntryPoint("cuTensorMapEncodeTiled", &f, cudaEnableDefault, &st);
        fn = (EncodeFn)f;
        cudaGetSymbolAddress(&p_xn, g_xn);
        cudaGetSymbolAddress(&p_h, g_h);
        cudaGetSymbolAddress(&p_o, g_o);
        cudaGetSymbolAddress(&p_g, g_g);
        cudaFuncSetAttribute(attn_kernel, cudaFuncAttributeMaxDynamicSharedMemorySize, (int)sizeof(AttnSmem) + 1024);
        cudaFuncSetAttribute(oproj_kernel, cudaFuncAttributeMaxDynamicSharedMemorySize, (int)sizeof(OpSmem) + 1024);
        static uint16_t f1[NUM_CTAS][MAX_ITEMS], at[NUM_CTAS][MAX_ITEMS], f2[NUM_CTAS][MAX_ITEMS];
        static int n1[NUM_CTAS], na[NUM_CTAS], n2[NUM_CTAS];
        static double load[NUM_CTAS];
        const double C_ATT = 58.0, C_F1 = 6.5, C_F2 = 19.5;
        for (int i = 0; i < NUM_CTAS; i++) { n1[i] = na[i] = n2[i] = 0; load[i] = 0; }
        for (int t = 0; t < NH * 16; t++) {
            int cta = t % NUM_CTAS;
            at[cta][na[cta]++] = (uint16_t)((T_ATT << 12) | ((t >> 4) << 4) | (t & 15));
            load[cta] += C_ATT;
        }
        auto least = [&]() { int bi = 0; for (int i = 1; i < NUM_CTAS; i++) if (load[i] < load[bi]) bi = i; return bi; };
        for (int t = 0; t < 64; t++) {
            int cta = least();
            f2[cta][n2[cta]++] = (uint16_t)((T_F2 << 12) | ((t & 3) << 4) | (t >> 2));
            load[cta] += C_F2;
        }
        for (int t = 0; t < 224; t++) {
            int cta = least();
            f1[cta][n1[cta]++] = (uint16_t)((T_F1 << 12) | ((t % 14) << 4) | (t / 14));
            load[cta] += C_F1;
        }
        for (int i = 0; i < NUM_CTAS; i++) {
            int n = 0;
            for (int j = 0; j < n1[i]; j++) sched.item[i][n++] = f1[i][j];
            for (int j = 0; j < na[i]; j++) sched.item[i][n++] = at[i][j];
            for (int j = 0; j < n2[i]; j++) sched.item[i][n++] = f2[i][j];
            sched.count[i] = (uint8_t)n;
        }
    }
    CUtensorMap tm_xn_at = make_map(fn, p_xn, SEQ, DM, 128, 2);
    CUtensorMap tm_wq = make_map(fn, wq, DM, NH * DH, 128, 2);
    CUtensorMap tm_k = make_map(fn, kc, NH * SEQ, DH, 128, 2);
    CUtensorMap tm_v = make_map(fn, vc, NH * SEQ, DH, 128, 2);
    CUtensorMap tm_o_st = make_map(fn, p_o, SEQ, NH * DH, 64, 2);
    CUtensorMap tm_w1 = make_map(fn, w1, DM, FF, 128, 2);
    CUtensorMap tm_h_st = make_map(fn, p_h, SEQ, FF, 64, 2);
    CUtensorMap tm_h_ld = make_map(fn, p_h, SEQ, FF, 128, 2);
    CUtensorMap tm_w2 = make_map(fn, w2, FF, DM, 128, 2);
    CUtensorMap tm_g_st = make_map(fn, p_g, SEQ, DM, 64, 2);
    CUtensorMap tm_o_g = make_map(fn, p_o, SEQ, NH * DH, 128, 1);
    CUtensorMap tm_wo = make_map(fn, wo, NH * DH, DM, 64, 4);

    ln_kernel<<<SEQ / 8, 256>>>(x);
    attn_kernel<<<NUM_CTAS, 384, sizeof(AttnSmem) + 1024>>>(tm_xn_at, tm_wq, tm_k, tm_v, tm_o_st, tm_w1, tm_h_st, tm_h_ld,
                                                            tm_w2, tm_g_st, sched);
    oproj_kernel<<<dim3(OP_KSPLIT, DM / 256, SEQ / 128), 384, sizeof(OpSmem) + 1024>>>(tm_o_g, tm_wo, x, out);
}
```

```cpp
#include <cuda_runtime.h>
#include <cuda_bf16.h>
#include <cuda.h>
#include <stdint.h>

typedef __nv_bfloat16 bf16;
#define PP(x) x

constexpr int SEQ = 2048, DM = 512, NH = 32, DH = 128, FF = 1792;

__device__ __align__(1024) bf16 g_xn[SEQ * DM];
__device__ __align__(1024) bf16 g_h[SEQ * FF];
__device__ __align__(1024) bf16 g_o[SEQ * NH * DH];
__device__ __align__(1024) bf16 g_g[SEQ * DM];
__device__ unsigned int g_hcnt[SEQ / 128];
__device__ float4 g_part[32 * 16 * 8 * 256];
__device__ unsigned int g_pcnt[128];
__device__ volatile float g_dummy;

__device__ __forceinline__ uint32_t smem_u32(const void* p) { return (uint32_t)__cvta_generic_to_shared(p); }

__device__ __forceinline__ void mbar_init(uint32_t bar, uint32_t count) {
    asm volatile("mbarrier.init.shared::cta.b64 [%0], %1;" ::"r"(bar), "r"(count) : "memory");
}
__device__ __forceinline__ void mbar_expect_tx(uint32_t bar, uint32_t bytes) {
    asm volatile("mbarrier.arrive.expect_tx.shared::cta.b64 _, [%0], %1;" ::"r"(bar), "r"(bytes) : "memory");
}
__device__ __forceinline__ void mbar_arrive(uint32_t bar) {
    asm volatile("mbarrier.arrive.shared::cta.b64 _, [%0];" ::"r"(bar) : "memory");
}
__device__ __forceinline__ bool mbar_try_wait(uint32_t bar, uint32_t parity) {
    uint32_t ok;
    asm volatile(
        "{\n.reg .pred p;\n"
        "mbarrier.test_wait.parity.shared::cta.b64 p, [%1], %2;\n"
        "selp.u32 %0, 1, 0, p;\n}\n"
        : "=r"(ok)
        : "r"(bar), "r"(parity)
        : "memory");
    return ok != 0;
}
__device__ __forceinline__ void mbar_wait(uint32_t bar, uint32_t parity) {
    asm volatile(
        "{\n.reg .pred P1;\n.reg .u32 n;\nmov.u32 n, 0;\n"
        "LAB_WAIT:\n"
        "mbarrier.try_wait.parity.shared::cta.b64 P1, [%0], %1;\n"
        "@P1 bra DONE;\n"
        "add.u32 n, n, 1;\n"
        "setp.lt.u32 P1, n, 4194304;\n"
        "@P1 bra LAB_WAIT;\n"
        "trap;\n"
        "DONE:\n}\n" ::"r"(bar), "r"(parity)
        : "memory");
}
__device__ __forceinline__ void tma_load_3d(uint32_t dst, const CUtensorMap* map, uint32_t bar, int c0, int c1, int c2) {
    asm volatile(
        "cp.async.bulk.tensor.3d.shared::cluster.global.mbarrier::complete_tx::bytes [%0], [%1, {%3, %4, %5}], [%2];"
        ::"r"(dst), "l"((uint64_t)map), "r"(bar), "r"(c0), "r"(c1), "r"(c2)
        : "memory");
}
__device__ __forceinline__ void tma_store_3d(const CUtensorMap* map, uint32_t src, int c0, int c1, int c2) {
    asm volatile("cp.async.bulk.tensor.3d.global.shared::cta.bulk_group [%0, {%2, %3, %4}], [%1];"
                 ::"l"((uint64_t)map), "r"(src), "r"(c0), "r"(c1), "r"(c2)
                 : "memory");
}
__device__ __forceinline__ void tma_commit() { asm volatile("cp.async.bulk.commit_group;" ::: "memory"); }
__device__ __forceinline__ void tma_wait_read0() { asm volatile("cp.async.bulk.wait_group.read 0;" ::: "memory"); }
__device__ __forceinline__ void tma_wait_all0() { asm volatile("cp.async.bulk.wait_group 0;" ::: "memory"); }
__device__ __forceinline__ void fence_proxy_async() { asm volatile("fence.proxy.async.shared::cta;" ::: "memory"); }
__device__ __forceinline__ void prefetch_tmap(const CUtensorMap* map) {
    asm volatile("prefetch.tensormap [%0];" ::"l"((uint64_t)map) : "memory");
}
__device__ __forceinline__ void named_sync(int id, int n) { asm volatile("bar.sync %0, %1;" ::"r"(id), "r"(n) : "memory"); }
__device__ __forceinline__ void named_arrive(int id, int n) { asm volatile("bar.arrive %0, %1;" ::"r"(id), "r"(n) : "memory"); }

__device__ __forceinline__ void wgmma_fence() { asm volatile("wgmma.fence.sync.aligned;" ::: "memory"); }
__device__ __forceinline__ void wgmma_commit() { asm volatile("wgmma.commit_group.sync.aligned;" ::: "memory"); }
template <int N>
__device__ __forceinline__ void wgmma_wait() { asm volatile("wgmma.wait_group.sync.aligned %0;" ::"n"(N) : "memory"); }

template <int R>
__device__ __forceinline__ void reg_alloc() { asm volatile("setmaxnreg.inc.sync.aligned.u32 %0;" ::"n"(R)); }
template <int R>
__device__ __forceinline__ void reg_dealloc() { asm volatile("setmaxnreg.dec.sync.aligned.u32 %0;" ::"n"(R)); }

__device__ __forceinline__ uint64_t make_desc(uint32_t saddr, uint32_t lbo_bytes, uint32_t sbo_bytes) {
    uint64_t d = 0;
    d |= (uint64_t)((saddr & 0x3FFFF) >> 4);
    d |= (uint64_t)((lbo_bytes >> 4) & 0x3FFF) << 16;
    d |= (uint64_t)((sbo_bytes >> 4) & 0x3FFF) << 32;
    d |= (uint64_t)1 << 62;
    return d;
}

__device__ __forceinline__ float ex2(float x) {
    float y;
    asm volatile("ex2.approx.ftz.f32 %0, %1;" : "=f"(y) : "f"(x));
    return y;
}
__device__ __forceinline__ uint32_t pack_bf16(float lo, float hi) {
    uint32_t r;
    asm("cvt.rn.bf16x2.f32 %0, %1, %2;" : "=r"(r) : "f"(hi), "f"(lo));
    return r;
}
__device__ __forceinline__ uint32_t mul_bf16x2(uint32_t a, uint32_t b) {
    uint32_t r;
    asm("mul.rn.bf16x2 %0, %1, %2;" : "=r"(r) : "r"(a), "r"(b));
    return r;
}
__device__ __forceinline__ uint32_t fma_bf16x2(uint32_t a, uint32_t b, uint32_t c) {
    uint32_t r;
    asm("fma.rn.bf16x2 %0, %1, %2, %3;" : "=r"(r) : "r"(a), "r"(b), "r"(c));
    return r;
}
__device__ __forceinline__ uint32_t max_bf16x2(uint32_t a, uint32_t b) {
    uint32_t r;
    asm("max.bf16x2 %0, %1, %2;" : "=r"(r) : "r"(a), "r"(b));
    return r;
}
__device__ __forceinline__ float bf16lo(uint32_t v) { return __uint_as_float(v << 16); }
__device__ __forceinline__ float bf16hi(uint32_t v) { return __uint_as_float(v & 0xffff0000u); }
__device__ __forceinline__ float bf16_round(float x) { return __bfloat162float(__float2bfloat16_rn(x)); }
__device__ __forceinline__ float silu_f(float x) {
    const float h = 0.5f * x;
    float t;
    asm("tanh.approx.f32 %0, %1;" : "=f"(t) : "f"(h));
    return fmaf(h, t, h);
}

__device__ __forceinline__ void stmatrix_x4(uint32_t addr, uint32_t r0, uint32_t r1, uint32_t r2, uint32_t r3) {
    asm volatile("stmatrix.sync.aligned.m8n8.x4.shared.b16 [%0], {%1, %2, %3, %4};"
                 ::"r"(addr), "r"(r0), "r"(r1), "r"(r2), "r"(r3)
                 : "memory");
}

#define ACC64(d) \
    "+f"(d[0]), "+f"(d[1]), "+f"(d[2]), "+f"(d[3]), "+f"(d[4]), "+f"(d[5]), "+f"(d[6]), "+f"(d[7]), \
    "+f"(d[8]), "+f"(d[9]), "+f"(d[10]), "+f"(d[11]), "+f"(d[12]), "+f"(d[13]), "+f"(d[14]), "+f"(d[15]), \
    "+f"(d[16]), "+f"(d[17]), "+f"(d[18]), "+f"(d[19]), "+f"(d[20]), "+f"(d[21]), "+f"(d[22]), "+f"(d[23]), \
    "+f"(d[24]), "+f"(d[25]), "+f"(d[26]), "+f"(d[27]), "+f"(d[28]), "+f"(d[29]), "+f"(d[30]), "+f"(d[31]), \
    "+f"(d[32]), "+f"(d[33]), "+f"(d[34]), "+f"(d[35]), "+f"(d[36]), "+f"(d[37]), "+f"(d[38]), "+f"(d[39]), \
    "+f"(d[40]), "+f"(d[41]), "+f"(d[42]), "+f"(d[43]), "+f"(d[44]), "+f"(d[45]), "+f"(d[46]), "+f"(d[47]), \
    "+f"(d[48]), "+f"(d[49]), "+f"(d[50]), "+f"(d[51]), "+f"(d[52]), "+f"(d[53]), "+f"(d[54]), "+f"(d[55]), \
    "+f"(d[56]), "+f"(d[57]), "+f"(d[58]), "+f"(d[59]), "+f"(d[60]), "+f"(d[61]), "+f"(d[62]), "+f"(d[63])

#define ACC64_STR \
    "{%0, %1, %2, %3, %4, %5, %6, %7, %8, %9, %10, %11, %12, %13, %14, %15, " \
    "%16, %17, %18, %19, %20, %21, %22, %23, %24, %25, %26, %27, %28, %29, %30, %31, " \
    "%32, %33, %34, %35, %36, %37, %38, %39, %40, %41, %42, %43, %44, %45, %46, %47, " \
    "%48, %49, %50, %51, %52, %53, %54, %55, %56, %57, %58, %59, %60, %61, %62, %63}"

template <int TB>
__device__ __forceinline__ void wgmma_ss_n128(float (&d)[64], uint64_t da, uint64_t db, int scale_d) {
    asm volatile(
        "{\n.reg .pred p;\nsetp.ne.b32 p, %66, 0;\n"
        "wgmma.mma_async.sync.aligned.m64n128k16.f32.bf16.bf16 " ACC64_STR ", %64, %65, p, 1, 1, 0, %67;\n}\n"
        : ACC64(d)
        : "l"(da), "l"(db), "r"(scale_d), "n"(TB));
}
template <int TB>
__device__ __forceinline__ void wgmma_rs_n128(float (&d)[64], uint32_t a0, uint32_t a1, uint32_t a2, uint32_t a3,
                                              uint64_t db, int scale_d) {
    asm volatile(
        "{\n.reg .pred p;\nsetp.ne.b32 p, %69, 0;\n"
        "wgmma.mma_async.sync.aligned.m64n128k16.f32.bf16.bf16 " ACC64_STR ", {%64, %65, %66, %67}, %68, p, 1, 1, %70;\n}\n"
        : ACC64(d)
        : "r"(a0), "r"(a1), "r"(a2), "r"(a3), "l"(db), "r"(scale_d), "n"(TB));
}

constexpr uint32_t DESC_HI = 0x40000040u;
__device__ __forceinline__ uint32_t desc_lo(uint32_t saddr, uint32_t lbo_bytes) {
    return ((saddr & 0x3FFFF) >> 4) | ((lbo_bytes >> 4) << 16);
}
template <int TB>
__device__ __forceinline__ void wgmma_ss_lo(float (&d)[64], uint32_t da, uint32_t db, int scale_d) {
    asm volatile(
        "{\n.reg .pred p;\n.reg .b64 xa, xb;\nsetp.ne.b32 p, %66, 0;\n"
        "mov.b64 xa, {%64, %68};\nmov.b64 xb, {%65, %68};\n"
        "wgmma.mma_async.sync.aligned.m64n128k16.f32.bf16.bf16 " ACC64_STR ", xa, xb, p, 1, 1, 0, %67;\n}\n"
        : ACC64(d)
        : "r"(da), "r"(db), "r"(scale_d), "n"(TB), "r"(DESC_HI));
}
__device__ __forceinline__ void wgmma_rs_lo_tb(float (&d)[64], uint32_t a0, uint32_t a1, uint32_t a2, uint32_t a3, uint32_t db) {
    asm volatile(
        "{\n.reg .b64 xb;\nmov.b64 xb, {%68, %69};\n"
        "wgmma.mma_async.sync.aligned.m64n128k16.f32.bf16.bf16 " ACC64_STR ", {%64, %65, %66, %67}, xb, 1, 1, 1, 1;\n}\n"
        : ACC64(d)
        : "r"(a0), "r"(a1), "r"(a2), "r"(a3), "r"(db), "r"(DESC_HI));
}

__global__ void __launch_bounds__(256) ln_kernel(const bf16* __restrict__ x) {
    int warp = threadIdx.x >> 5, lane = threadIdx.x & 31;
    int row = blockIdx.x * 8 + warp;
    if (blockIdx.x == 0 && threadIdx.x < SEQ / 128) g_hcnt[threadIdx.x] = 0;
    if (blockIdx.x == 1 && threadIdx.x < 128) g_pcnt[threadIdx.x] = 0;
    const uint4* src = reinterpret_cast<const uint4*>(x + (size_t)row * DM);
    uint4 v[2];
    v[0] = src[lane];
    v[1] = src[lane + 32];
    float f[16];
#pragma unroll
    for (int i = 0; i < 2; i++) {
        const __nv_bfloat162* p = reinterpret_cast<const __nv_bfloat162*>(&v[i]);
#pragma unroll
        for (int j = 0; j < 4; j++) {
            float2 t = __bfloat1622float2(p[j]);
            f[i * 8 + j * 2] = t.x;
            f[i * 8 + j * 2 + 1] = t.y;
        }
    }
    float s = 0.f;
#pragma unroll
    for (int i = 0; i < 16; i++) s += f[i];
#pragma unroll
    for (int o = 16; o > 0; o >>= 1) s += __shfl_xor_sync(0xffffffffu, s, o);
    float mean = s * (1.0f / DM);
    float q = 0.f;
#pragma unroll
    for (int i = 0; i < 16; i++) {
        float d = f[i] - mean;
        q += d * d;
    }
#pragma unroll
    for (int o = 16; o > 0; o >>= 1) q += __shfl_xor_sync(0xffffffffu, q, o);
    float var_b = bf16_round(q * (1.0f / DM));
    float mean_b = bf16_round(mean);
    float den = bf16_round(sqrtf(bf16_round(var_b + 1e-5f)));
    uint4 o[2];
#pragma unroll
    for (int i = 0; i < 2; i++) {
        uint32_t* p = reinterpret_cast<uint32_t*>(&o[i]);
#pragma unroll
        for (int j = 0; j < 4; j++) {
            float a = bf16_round(f[i * 8 + j * 2] - mean_b) / den;
            float b = bf16_round(f[i * 8 + j * 2 + 1] - mean_b) / den;
            p[j] = pack_bf16(a, b);
        }
    }
    uint4* dst = reinterpret_cast<uint4*>(g_xn + (size_t)row * DM);
    dst[lane] = o[0];
    dst[lane + 32] = o[1];
}

constexpr int AT_STAGES = 3;
constexpr int TILE_BYTES = 128 * 128 * 2;
struct __align__(1024) AttnSmem {
    uint8_t k[AT_STAGES][TILE_BYTES];
    uint8_t v[AT_STAGES][TILE_BYTES];
    uint8_t o[TILE_BYTES];
    uint64_t full_k[AT_STAGES], full_v[AT_STAGES], empty_k[AT_STAGES], empty_v[AT_STAGES];
    uint64_t st_free[2];
};

constexpr int NUM_CTAS = 132;
constexpr int MAX_ITEMS = 12;
enum { T_ATT = 0, T_F1 = 1, T_F2 = 2 };
struct Sched {
    uint16_t item[NUM_CTAS][MAX_ITEMS];
    uint8_t count[NUM_CTAS];
};

__global__ void __launch_bounds__(384, 1)
attn_kernel(const __grid_constant__ CUtensorMap tm_xn, const __grid_constant__ CUtensorMap tm_wq,
            const __grid_constant__ CUtensorMap tm_k, const __grid_constant__ CUtensorMap tm_v,
            const __grid_constant__ CUtensorMap tm_o, const __grid_constant__ CUtensorMap tm_w1,
            const __grid_constant__ CUtensorMap tm_hst, const __grid_constant__ CUtensorMap tm_hld,
            const __grid_constant__ CUtensorMap tm_w2, const __grid_constant__ CUtensorMap tm_gst,
            const __grid_constant__ Sched sched) {
    extern __shared__ uint8_t smem_raw[];
    AttnSmem& sm = *reinterpret_cast<AttnSmem*>((reinterpret_cast<uintptr_t>(smem_raw) + 1023) & ~uintptr_t(1023));
    const int tid = threadIdx.x;
    const int wg = __shfl_sync(0xffffffffu, tid >> 7, 0);
    const int n_items = sched.count[blockIdx.x];

    if (tid == 0) {
#pragma unroll
        for (int s = 0; s < AT_STAGES; s++) {
            mbar_init(smem_u32(&sm.full_k[s]), 1);
            mbar_init(smem_u32(&sm.full_v[s]), 1);
            mbar_init(smem_u32(&sm.empty_k[s]), 8);
            mbar_init(smem_u32(&sm.empty_v[s]), 8);
        }
        mbar_init(smem_u32(&sm.st_free[0]), 1);
        mbar_init(smem_u32(&sm.st_free[1]), 1);
        asm volatile("fence.mbarrier_init.release.cluster;" ::: "memory");
    }
    __syncthreads();
    constexpr int BAR_SCHED0 = 1, BAR_EPI0 = 3, BAR_ST0 = 5;

    if (wg == 0) {
        reg_dealloc<24>();
        if (tid >= 32 && tid < 96) {
            const int cw = (tid >> 5) - 1;
            const uint32_t obase = smem_u32(sm.o) + cw * 16384;
            for (int it = 0; it < n_items; it++) {
                const int item = sched.item[blockIdx.x][it];
                const int type = item >> 12, a = (item >> 4) & 0xff, b = item & 15;
                named_sync(BAR_ST0 + cw, 160);
                if ((tid & 31) == 0) {
                    tma_store_3d(type == T_ATT ? &tm_o : (type == T_F1 ? &tm_hst : &tm_gst), obase, 0, b * 128 + cw * 64, a * 2);
                    tma_commit();
                    tma_wait_read0();
                    mbar_arrive(smem_u32(&sm.st_free[cw]));
                    if (type == T_F1) {
                        tma_wait_all0();
                        asm volatile("fence.proxy.async;" ::: "memory");
                        __threadfence();
                        atomicAdd(&g_hcnt[b], 1u);
                    }
                }
                __syncwarp();
            }
            if ((tid & 31) == 0) tma_wait_all0();
        }
        if (tid == 0) {
            int stage = 0;
            uint32_t phase = 0;
            for (int it = 0; it < n_items; it++) {
                const int item = sched.item[blockIdx.x][it];
                const int type = item >> 12, a = (item >> 4) & 0xff, b = item & 15;
                const CUtensorMap* ta = (type == T_F2) ? &tm_hld : &tm_xn;
                const CUtensorMap* tb = (type == T_ATT) ? &tm_wq : (type == T_F1 ? &tm_w1 : &tm_w2);
                const int nch = (type == T_F2) ? FF / 128 : DM / 128;
                if (type == T_F2) {
                    unsigned int v, spins = 0;
                    do {
                        asm volatile("ld.acquire.gpu.global.u32 %0, [%1];" : "=r"(v) : "l"(&g_hcnt[b]) : "memory");
                    } while (v < 2 * (FF / 128) && ++spins < (1u << 24));
                    asm volatile("fence.proxy.async;" ::: "memory");
                }
                for (int kc = 0; kc < nch; kc++) {
                    mbar_wait(smem_u32(&sm.empty_k[stage]), phase ^ 1);
                    mbar_expect_tx(smem_u32(&sm.full_k[stage]), TILE_BYTES);
                    tma_load_3d(smem_u32(sm.k[stage]), ta, smem_u32(&sm.full_k[stage]), 0, b * 128, kc * 2);
                    mbar_wait(smem_u32(&sm.empty_v[stage]), phase ^ 1);
                    mbar_expect_tx(smem_u32(&sm.full_v[stage]), TILE_BYTES);
                    tma_load_3d(smem_u32(sm.v[stage]), tb, smem_u32(&sm.full_v[stage]), 0, kc * 128, a * 2);
                    if (++stage == AT_STAGES) { stage = 0; phase ^= 1; }
                }
                if (type == T_ATT) {
                    for (int j = 0; j < 16; j++) {
                        mbar_wait(smem_u32(&sm.empty_k[stage]), phase ^ 1);
                        mbar_expect_tx(smem_u32(&sm.full_k[stage]), TILE_BYTES);
                        tma_load_3d(smem_u32(sm.k[stage]), &tm_k, smem_u32(&sm.full_k[stage]), 0, a * SEQ + j * 128, 0);
                        mbar_wait(smem_u32(&sm.empty_v[stage]), phase ^ 1);
                        mbar_expect_tx(smem_u32(&sm.full_v[stage]), TILE_BYTES);
                        tma_load_3d(smem_u32(sm.v[stage]), &tm_v, smem_u32(&sm.full_v[stage]), 0, a * SEQ + j * 128, 0);
                        if (++stage == AT_STAGES) { stage = 0; phase ^= 1; }
                    }
                }
            }
        }
    } else {
        reg_alloc<240>();
        const int cw = wg - 1;
        const int lane = tid & 31;
        const int warp_in_wg = (tid >> 5) & 3;
        const float c = 1.4426950408889634f;
        const uint32_t SCALE_HI2 = 0x3DB53DB5u, SCALE_LO2 = 0x371E371Eu;
        const uint32_t obase = smem_u32(sm.o) + cw * 16384;
        const int st_row = warp_in_wg * 16 + ((lane >> 3) & 1) * 8 + (lane & 7);

        const uint32_t dq = __shfl_sync(0xffffffffu, desc_lo(obase, 16), 0);
        const uint32_t dk0 = __shfl_sync(0xffffffffu, desc_lo(smem_u32(sm.k[0]), 16), 0);
        const uint32_t dv0 = dk0 - (1u << 16) + (1024u << 16) + AT_STAGES * (TILE_BYTES >> 4);

        PP(if (cw == 1) named_arrive(BAR_SCHED0 + 0, 256));

        int stage = 0;
        uint32_t phase = 0;
        float S[64], O[64];
        uint32_t P[32];

        for (int it = 0; it < n_items; it++) {
            const int item = sched.item[blockIdx.x][it];
            const int type = item >> 12;
            const int nch = (type == T_F2) ? FF / 128 : DM / 128;
            {
                int prev = -1;
#pragma unroll 1
                for (int kc = 0; kc < nch; kc++) {
                    mbar_wait(smem_u32(&sm.full_k[stage]), phase);
                    mbar_wait(smem_u32(&sm.full_v[stage]), phase);
                    const uint64_t da = make_desc(smem_u32(sm.k[stage]) + cw * 64 * 128, 16, 1024);
                    const uint64_t db = make_desc(smem_u32(sm.v[stage]), 16384, 1024);
                    wgmma_fence();
#pragma unroll
                    for (int kk = 0; kk < 8; kk++) {
                        wgmma_ss_n128<1>(S, da + (uint64_t)(((kk >> 2) * 16384 + (kk & 3) * 32) >> 4),
                                         db + (uint64_t)((kk * 2048) >> 4), (kc | kk) != 0);
                    }
                    wgmma_commit();
                    wgmma_wait<1>();
                    if (prev >= 0 && lane == 0) {
                        mbar_arrive(smem_u32(&sm.empty_k[prev]));
                        mbar_arrive(smem_u32(&sm.empty_v[prev]));
                    }
                    prev = stage;
                    if (++stage == AT_STAGES) { stage = 0; phase ^= 1; }
                }
                wgmma_wait<0>();
                if (lane == 0) {
                    mbar_arrive(smem_u32(&sm.empty_k[prev]));
                    mbar_arrive(smem_u32(&sm.empty_v[prev]));
                }
            }
            if (type != T_ATT) {
#pragma unroll
                for (int i = 0; i < 64; i++) S[i] = silu_f(bf16_round(S[i]));
            }
            mbar_wait(smem_u32(&sm.st_free[cw]), (it & 1) ^ 1);
#pragma unroll
            for (int i = 0; i < 16; i += 2) {
                const int cc = i + (lane >> 4);
                const uint32_t addr = obase + (cc >> 3) * 8192 + st_row * 128 + (((cc & 7) ^ (st_row & 7)) << 4);
                stmatrix_x4(addr, pack_bf16(S[4 * i], S[4 * i + 1]), pack_bf16(S[4 * i + 2], S[4 * i + 3]),
                            pack_bf16(S[4 * i + 4], S[4 * i + 5]), pack_bf16(S[4 * i + 6], S[4 * i + 7]));
            }
            fence_proxy_async();
            if (type != T_ATT) {
                named_arrive(BAR_ST0 + cw, 160);
                continue;
            }
            named_sync(BAR_EPI0 + cw, 128);
#pragma unroll
            for (int i = 0; i < 64; i++) O[i] = 0.f;

            float m0 = -INFINITY, m1 = -INFINITY, l0 = 0.f, l1 = 0.f, a0 = 0.f, a1 = 0.f;
            bool resc = false;
            const float TAU = 11.0f;
            const uint32_t fk0 = smem_u32(&sm.full_k[0]), fv0 = smem_u32(&sm.full_v[0]);
            const uint32_t ek0 = smem_u32(&sm.empty_k[0]), ev0 = smem_u32(&sm.empty_v[0]);

            uint32_t T[32];
            float n0, n1;
            auto softmax1 = [&]() {
#pragma unroll
                for (int i = 0; i < 32; i++) {
                    const uint32_t sb = pack_bf16(S[2 * i], S[2 * i + 1]);
                    T[i] = fma_bf16x2(sb, SCALE_HI2, mul_bf16x2(sb, SCALE_LO2));
                }
                uint32_t y0 = max_bf16x2(T[0], T[2]), y1 = max_bf16x2(T[1], T[3]);
#pragma unroll
                for (int i = 2; i < 16; i++) {
                    y0 = max_bf16x2(y0, T[2 * i]);
                    y1 = max_bf16x2(y1, T[2 * i + 1]);
                }
                float x0 = fmaxf(bf16lo(y0), bf16hi(y0));
                float x1 = fmaxf(bf16lo(y1), bf16hi(y1));
                x0 = fmaxf(x0, __shfl_xor_sync(0xffffffffu, x0, 1));
                x1 = fmaxf(x1, __shfl_xor_sync(0xffffffffu, x1, 1));
                x0 = fmaxf(x0, __shfl_xor_sync(0xffffffffu, x0, 2));
                x1 = fmaxf(x1, __shfl_xor_sync(0xffffffffu, x1, 2));
                resc = __any_sync(0xffffffffu, (x0 - m0 > TAU) || (x1 - m1 > TAU));
                x0 = resc ? fmaxf(x0, m0) : m0;
                x1 = resc ? fmaxf(x1, m1) : m1;
                a0 = ex2((m0 - x0) * c);
                a1 = ex2((m1 - x1) * c);
                m0 = x0;
                m1 = x1;
                n0 = -m0 * c;
                n1 = -m1 * c;
                while (n0 != n0) n0 = g_dummy;
            };
            auto softmax2 = [&]() {
                float s0 = 0.f, s1 = 0.f;
#pragma unroll
                for (int i = 0; i < 16; i++) {
                    const float e0 = ex2(fmaf(bf16lo(T[2 * i]), c, n0));
                    const float e1 = ex2(fmaf(bf16hi(T[2 * i]), c, n0));
                    const float e2 = ex2(fmaf(bf16lo(T[2 * i + 1]), c, n1));
                    const float e3 = ex2(fmaf(bf16hi(T[2 * i + 1]), c, n1));
                    s0 += e0 + e1;
                    s1 += e2 + e3;
                    P[2 * i] = pack_bf16(e0, e1);
                    P[2 * i + 1] = pack_bf16(e2, e3);
                }
                l0 = l0 * a0 + s0;
                l1 = l1 * a1 + s1;
            };
            auto issue_qk = [&](uint32_t dk) {
                wgmma_fence();
#pragma unroll
                for (int kk = 0; kk < 8; kk++)
                    wgmma_ss_lo<0>(S, dq + (((kk >> 2) * 8192 + (kk & 3) * 32) >> 4),
                                   dk + (((kk >> 2) * 16384 + (kk & 3) * 32) >> 4), kk != 0);
                wgmma_commit();
            };
            auto issue_pv = [&](uint32_t dv) {
                if (resc) {
#pragma unroll
                    for (int i = 0; i < 16; i++) {
                        O[4 * i] *= a0;
                        O[4 * i + 1] *= a0;
                        O[4 * i + 2] *= a1;
                        O[4 * i + 3] *= a1;
                    }
                }
                wgmma_fence();
#pragma unroll
                for (int kk = 0; kk < 8; kk++)
                    wgmma_rs_lo_tb(O, P[4 * kk], P[4 * kk + 1], P[4 * kk + 2], P[4 * kk + 3], dv + ((kk * 2048) >> 4));
                wgmma_commit();
            };

            int vstage = stage;
            uint32_t vphase = phase;
            bool okk, okv;
            {
                mbar_wait(fk0 + stage * 8, phase);
                PP(named_sync(BAR_SCHED0 + cw, 256));
                issue_qk(dk0 + stage * (TILE_BYTES >> 4));
                PP(named_arrive(BAR_SCHED0 + (cw ^ 1), 256));
                if (++stage == AT_STAGES) { stage = 0; phase ^= 1; }
                okk = mbar_try_wait(fk0 + stage * 8, phase);
                okv = mbar_try_wait(fv0 + vstage * 8, vphase);
                wgmma_wait<0>();
                if (lane == 0) mbar_arrive(ek0 + vstage * 8);
            }
            softmax1();
            softmax2();
            resc = false;

#pragma unroll 1
            for (int j = 1; j < 16; j++) {
                const int ust = __shfl_sync(0xffffffffu, stage, 0), uvs = __shfl_sync(0xffffffffu, vstage, 0);
                if (!okk) mbar_wait(fk0 + stage * 8, phase);
                if (!okv) mbar_wait(fv0 + vstage * 8, vphase);
                PP(named_sync(BAR_SCHED0 + cw, 256));
                issue_qk(dk0 + ust * (TILE_BYTES >> 4));
                issue_pv(dv0 + uvs * (TILE_BYTES >> 4));
                PP(named_arrive(BAR_SCHED0 + (cw ^ 1), 256));
                const int pv = vstage;
                vstage = stage;
                vphase = phase;
                if (++stage == AT_STAGES) { stage = 0; phase ^= 1; }
                okk = mbar_try_wait(fk0 + stage * 8, phase);
                okv = mbar_try_wait(fv0 + vstage * 8, vphase);
                wgmma_wait<1>();
                if (lane == 0) mbar_arrive(ek0 + vstage * 8);
                softmax1();
                wgmma_wait<0>();
                if (lane == 0) mbar_arrive(ev0 + pv * 8);
                softmax2();
            }
            if (!okv) mbar_wait(fv0 + vstage * 8, vphase);
            issue_pv(dv0 + vstage * (TILE_BYTES >> 4));
            wgmma_wait<0>();
            if (lane == 0) mbar_arrive(ev0 + vstage * 8);
            l0 += __shfl_xor_sync(0xffffffffu, l0, 1);
            l1 += __shfl_xor_sync(0xffffffffu, l1, 1);
            l0 += __shfl_xor_sync(0xffffffffu, l0, 2);
            l1 += __shfl_xor_sync(0xffffffffu, l1, 2);
            const float i0 = 1.0f / l0, i1 = 1.0f / l1;
            named_sync(BAR_EPI0 + cw, 128);
#pragma unroll
            for (int i = 0; i < 16; i += 2) {
                const int cc = i + (lane >> 4);
                const uint32_t addr = obase + (cc >> 3) * 8192 + st_row * 128 + (((cc & 7) ^ (st_row & 7)) << 4);
                stmatrix_x4(addr, pack_bf16(O[4 * i] * i0, O[4 * i + 1] * i0), pack_bf16(O[4 * i + 2] * i1, O[4 * i + 3] * i1),
                            pack_bf16(O[4 * i + 4] * i0, O[4 * i + 5] * i0), pack_bf16(O[4 * i + 6] * i1, O[4 * i + 7] * i1));
            }
            fence_proxy_async();
            named_arrive(BAR_ST0 + cw, 160);
        }
    }
}

constexpr int OP_STAGES = 4;
constexpr int OP_KSPLIT = 4;
struct __align__(1024) OpSmem {
    uint8_t a[OP_STAGES][128 * 64 * 2];
    uint8_t b[OP_STAGES][64 * 256 * 2];
    uint64_t full[OP_STAGES], empty[OP_STAGES];
};

#define ACC8(d, o) "+f"(d[o]), "+f"(d[o + 1]), "+f"(d[o + 2]), "+f"(d[o + 3]), "+f"(d[o + 4]), "+f"(d[o + 5]), "+f"(d[o + 6]), "+f"(d[o + 7])
__device__ __forceinline__ void wgmma_ss_n256_tb(float (&d)[128], uint64_t da, uint64_t db, int scale_d) {
    asm volatile(
        "{\n.reg .pred p;\nsetp.ne.b32 p, %130, 0;\n"
        "wgmma.mma_async.sync.aligned.m64n256k16.f32.bf16.bf16 "
        "{%0, %1, %2, %3, %4, %5, %6, %7, %8, %9, %10, %11, %12, %13, %14, %15, "
        "%16, %17, %18, %19, %20, %21, %22, %23, %24, %25, %26, %27, %28, %29, %30, %31, "
        "%32, %33, %34, %35, %36, %37, %38, %39, %40, %41, %42, %43, %44, %45, %46, %47, "
        "%48, %49, %50, %51, %52, %53, %54, %55, %56, %57, %58, %59, %60, %61, %62, %63, "
        "%64, %65, %66, %67, %68, %69, %70, %71, %72, %73, %74, %75, %76, %77, %78, %79, "
        "%80, %81, %82, %83, %84, %85, %86, %87, %88, %89, %90, %91, %92, %93, %94, %95, "
        "%96, %97, %98, %99, %100, %101, %102, %103, %104, %105, %106, %107, %108, %109, %110, %111, "
        "%112, %113, %114, %115, %116, %117, %118, %119, %120, %121, %122, %123, %124, %125, %126, %127}, "
        "%128, %129, p, 1, 1, 0, 1;\n}\n"
        : ACC8(d, 0), ACC8(d, 8), ACC8(d, 16), ACC8(d, 24), ACC8(d, 32), ACC8(d, 40), ACC8(d, 48), ACC8(d, 56),
          ACC8(d, 64), ACC8(d, 72), ACC8(d, 80), ACC8(d, 88), ACC8(d, 96), ACC8(d, 104), ACC8(d, 112), ACC8(d, 120)
        : "l"(da), "l"(db), "r"(scale_d));
}
__device__ __forceinline__ void cluster_sync_all() {
    asm volatile("barrier.cluster.arrive.release.aligned;\nbarrier.cluster.wait.acquire.aligned;" ::: "memory");
}

__global__ void __launch_bounds__(384, 1)
oproj_kernel(const __grid_constant__ CUtensorMap tm_o, const __grid_constant__ CUtensorMap tm_wo,
             const bf16* __restrict__ x, bf16* __restrict__ out) {
    extern __shared__ uint8_t smem_raw[];
    OpSmem& sm = *reinterpret_cast<OpSmem*>((reinterpret_cast<uintptr_t>(smem_raw) + 1023) & ~uintptr_t(1023));
    const int tid = threadIdx.x, wg = tid >> 7;
    const int kr = blockIdx.x;
    const int n0 = blockIdx.y * 256, m0 = blockIdx.z * 128;
    const int tile = blockIdx.y + 2 * blockIdx.z;
    constexpr int KT = NH * DH / OP_KSPLIT / 64;
    if (tid == 0) {
        for (int s = 0; s < OP_STAGES; s++) {
            mbar_init(smem_u32(&sm.full[s]), 1);
            mbar_init(smem_u32(&sm.empty[s]), 8);
        }
        asm volatile("fence.mbarrier_init.release.cluster;" ::: "memory");
    }
    __syncthreads();
    if (wg == 0) {
        reg_dealloc<40>();
        if (tid == 0) {
            int stage = 0;
            uint32_t phase = 0;
            for (int kt = 0; kt < KT; kt++) {
                const int kg = kr * KT + kt;
                mbar_wait(smem_u32(&sm.empty[stage]), phase ^ 1);
                mbar_expect_tx(smem_u32(&sm.full[stage]), 49152);
                tma_load_3d(smem_u32(sm.a[stage]), &tm_o, smem_u32(&sm.full[stage]), 0, m0, kg);
                tma_load_3d(smem_u32(sm.b[stage]), &tm_wo, smem_u32(&sm.full[stage]), 0, kg * 64, n0 >> 6);
                if (++stage == OP_STAGES) { stage = 0; phase ^= 1; }
            }
        }
    } else {
        reg_alloc<232>();
        const int cw = wg - 1, lane = tid & 31, warp_in_wg = (tid >> 5) & 3;
        const int ct = tid - 128;
        float acc[128];
        const int r0 = m0 + cw * 64 + warp_in_wg * 16 + (lane >> 2);
        uint32_t xv[16], gv[16];
#pragma unroll
        for (int j = 0; j < 8; j++) {
#pragma unroll
            for (int hh = 0; hh < 2; hh++) {
                const size_t off = (size_t)(r0 + hh * 8) * DM + n0 + kr * 64 + j * 8 + (lane & 3) * 2;
                xv[2 * j + hh] = *reinterpret_cast<const uint32_t*>(x + off);
                gv[2 * j + hh] = *reinterpret_cast<const uint32_t*>(g_g + off);
            }
        }
        int stage = 0, prev = -1;
        uint32_t phase = 0;
#pragma unroll 1
        for (int kt = 0; kt < KT; kt++) {
            mbar_wait(smem_u32(&sm.full[stage]), phase);
            const uint64_t da = make_desc(smem_u32(sm.a[stage]) + cw * 64 * 128, 16, 1024);
            const uint64_t db = make_desc(smem_u32(sm.b[stage]), 8192, 1024);
            wgmma_fence();
#pragma unroll
            for (int kk = 0; kk < 4; kk++)
                wgmma_ss_n256_tb(acc, da + (uint64_t)((kk * 32) >> 4), db + (uint64_t)((kk * 2048) >> 4), (kt | kk) != 0);
            wgmma_commit();
            wgmma_wait<1>();
            if (prev >= 0 && lane == 0) mbar_arrive(smem_u32(&sm.empty[prev]));
            prev = stage;
            if (++stage == OP_STAGES) { stage = 0; phase ^= 1; }
        }
        wgmma_wait<0>();
        float4* part = g_part + (size_t)tile * (OP_KSPLIT * OP_KSPLIT * 8 * 256);
#pragma unroll
        for (int d = 0; d < OP_KSPLIT; d++) {
            if (d == kr) continue;
#pragma unroll
            for (int j = 0; j < 8; j++)
                __stcg(part + ((d * OP_KSPLIT + kr) * 8 + j) * 256 + ct,
                       make_float4(acc[(8 * d + j) * 4], acc[(8 * d + j) * 4 + 1], acc[(8 * d + j) * 4 + 2], acc[(8 * d + j) * 4 + 3]));
        }
        __threadfence();
        named_sync(1, 256);
        if (ct < OP_KSPLIT && ct != kr)
            asm volatile("red.release.gpu.global.add.u32 [%0], 1;" ::"l"(&g_pcnt[tile * OP_KSPLIT + ct]) : "memory");
        float r[32];
#pragma unroll
        for (int d = 0; d < OP_KSPLIT; d++) {
            if (d == kr) {
#pragma unroll
                for (int i = 0; i < 32; i++) r[i] = acc[32 * d + i];
            }
        }
        if (ct == 0) {
            unsigned int v, spins = 0;
            do {
                asm volatile("ld.acquire.gpu.global.u32 %0, [%1];" : "=r"(v) : "l"(&g_pcnt[tile * OP_KSPLIT + kr]) : "memory");
            } while (v < OP_KSPLIT - 1 && ++spins < (1u << 24));
        }
        named_sync(1, 256);
#pragma unroll
        for (int sr = 0; sr < OP_KSPLIT; sr++) {
            if (sr == kr) continue;
#pragma unroll
            for (int j = 0; j < 8; j++) {
                const float4 v = __ldcg(part + ((kr * OP_KSPLIT + sr) * 8 + j) * 256 + ct);
                r[4 * j] += v.x;
                r[4 * j + 1] += v.y;
                r[4 * j + 2] += v.z;
                r[4 * j + 3] += v.w;
            }
        }
#pragma unroll
        for (int j = 0; j < 8; j++) {
#pragma unroll
            for (int hh = 0; hh < 2; hh++) {
                const size_t off = (size_t)(r0 + hh * 8) * DM + n0 + kr * 64 + j * 8 + (lane & 3) * 2;
                const float s0 = bf16_round(r[4 * j + 2 * hh]), s1 = bf16_round(r[4 * j + 2 * hh + 1]);
                const float o0 = bf16lo(xv[2 * j + hh]) + bf16_round(s0 * bf16lo(gv[2 * j + hh]));
                const float o1 = bf16hi(xv[2 * j + hh]) + bf16_round(s1 * bf16hi(gv[2 * j + hh]));
                *reinterpret_cast<uint32_t*>(out + off) = pack_bf16(o0, o1);
            }
        }
    }
}

typedef CUresult (*EncodeFn)(CUtensorMap*, CUtensorMapDataType, cuuint32_t, void*, const cuuint64_t*, const cuuint64_t*,
                             const cuuint32_t*, const cuuint32_t*, CUtensorMapInterleave, CUtensorMapSwizzle,
                             CUtensorMapL2promotion, CUtensorMapFloatOOBfill);

static CUtensorMap make_map(EncodeFn fn, const void* ptr, uint64_t rows, uint64_t cols, uint32_t box_rows, uint32_t box_blk) {
    CUtensorMap m;
    cuuint64_t dims[3] = {64, rows, cols / 64};
    cuuint64_t strides[2] = {cols * 2, 128};
    cuuint32_t box[3] = {64, box_rows, box_blk};
    cuuint32_t es[3] = {1, 1, 1};
    fn(&m, CU_TENSOR_MAP_DATA_TYPE_BFLOAT16, 3, const_cast<void*>(ptr), dims, strides, box, es, CU_TENSOR_MAP_INTERLEAVE_NONE,
       CU_TENSOR_MAP_SWIZZLE_128B, CU_TENSOR_MAP_L2_PROMOTION_L2_256B, CU_TENSOR_MAP_FLOAT_OOB_FILL_NONE);
    return m;
}

extern "C" void kernel_launch(void* const* d_in, const int* in_sizes, int n_in, void* d_out, int out_size) {
    const bf16* x = (const bf16*)d_in[0];
    const bf16* kc = (const bf16*)d_in[1];
    const bf16* vc = (const bf16*)d_in[2];
    const bf16* wq = (const bf16*)d_in[3];
    const bf16* wo = (const bf16*)d_in[4];
    const bf16* w1 = (const bf16*)d_in[6];
    const bf16* w2 = (const bf16*)d_in[7];
    bf16* out = (bf16*)d_out;

    static EncodeFn fn = nullptr;
    static void *p_xn = nullptr, *p_h = nullptr, *p_o = nullptr, *p_g = nullptr;
    static Sched sched;
    if (!fn) {
        void* f = nullptr;
        cudaDriverEntryPointQueryResult st;
        cudaGetDriverEntryPoint("cuTensorMapEncodeTiled", &f, cudaEnableDefault, &st);
        fn = (EncodeFn)f;
        cudaGetSymbolAddress(&p_xn, g_xn);
        cudaGetSymbolAddress(&p_h, g_h);
        cudaGetSymbolAddress(&p_o, g_o);
        cudaGetSymbolAddress(&p_g, g_g);
        cudaFuncSetAttribute(attn_kernel, cudaFuncAttributeMaxDynamicSharedMemorySize, (int)sizeof(AttnSmem) + 1024);
        cudaFuncSetAttribute(oproj_kernel, cudaFuncAttributeMaxDynamicSharedMemorySize, (int)sizeof(OpSmem) + 1024);
        static uint16_t f1[NUM_CTAS][MAX_ITEMS], at[NUM_CTAS][MAX_ITEMS], f2[NUM_CTAS][MAX_ITEMS];
        static int n1[NUM_CTAS], na[NUM_CTAS], n2[NUM_CTAS];
        static double load[NUM_CTAS];
        const double C_ATT = 58.0, C_F1 = 6.5, C_F2 = 19.5;
        for (int i = 0; i < NUM_CTAS; i++) { n1[i] = na[i] = n2[i] = 0; load[i] = 0; }
        for (int t = 0; t < NH * 16; t++) {
            int cta = t % NUM_CTAS;
            at[cta][na[cta]++] = (uint16_t)((T_ATT << 12) | ((t >> 4) << 4) | (t & 15));
            load[cta] += C_ATT;
        }
        auto least = [&]() { int bi = 0; for (int i = 1; i < NUM_CTAS; i++) if (load[i] < load[bi]) bi = i; return bi; };
        for (int t = 0; t < 64; t++) {
            int cta = least();
            f2[cta][n2[cta]++] = (uint16_t)((T_F2 << 12) | ((t & 3) << 4) | (t >> 2));
            load[cta] += C_F2;
        }
        for (int t = 0; t < 224; t++) {
            int cta = least();
            f1[cta][n1[cta]++] = (uint16_t)((T_F1 << 12) | ((t % 14) << 4) | (t / 14));
            load[cta] += C_F1;
        }
        for (int i = 0; i < NUM_CTAS; i++) {
            int n = 0;
            for (int j = 0; j < n1[i]; j++) sched.item[i][n++] = f1[i][j];
            for (int j = 0; j < na[i]; j++) sched.item[i][n++] = at[i][j];
            for (int j = 0; j < n2[i]; j++) sched.item[i][n++] = f2[i][j];
            sched.count[i] = (uint8_t)n;
        }
    }
    CUtensorMap tm_xn_at = make_map(fn, p_xn, SEQ, DM, 128, 2);
    CUtensorMap tm_wq = make_map(fn, wq, DM, NH * DH, 128, 2);
    CUtensorMap tm_k = make_map(fn, kc, NH * SEQ, DH, 128, 2);
    CUtensorMap tm_v = make_map(fn, vc, NH * SEQ, DH, 128, 2);
    CUtensorMap tm_o_st = make_map(fn, p_o, SEQ, NH * DH, 64, 2);
    CUtensorMap tm_w1 = make_map(fn, w1, DM, FF, 128, 2);
    CUtensorMap tm_h_st = make_map(fn, p_h, SEQ, FF, 64, 2);
    CUtensorMap tm_h_ld = make_map(fn, p_h, SEQ, FF, 128, 2);
    CUtensorMap tm_w2 = make_map(fn, w2, FF, DM, 128, 2);
    CUtensorMap tm_g_st = make_map(fn, p_g, SEQ, DM, 64, 2);
    CUtensorMap tm_o_g = make_map(fn, p_o, SEQ, NH * DH, 128, 1);
    CUtensorMap tm_wo = make_map(fn, wo, NH * DH, DM, 64, 4);

    ln_kernel<<<SEQ / 8, 256>>>(x);
    attn_kernel<<<NUM_CTAS, 384, sizeof(AttnSmem) + 1024>>>(tm_xn_at, tm_wq, tm_k, tm_v, tm_o_st, tm_w1, tm_h_st, tm_h_ld,
                                                            tm_w2, tm_g_st, sched);
    oproj_kernel<<<dim3(OP_KSPLIT, DM / 256, SEQ / 128), 384, sizeof(OpSmem) + 1024>>>(tm_o_g, tm_wo, x, out);
}
```

```cpp
#include <cuda_runtime.h>
#include <cuda_bf16.h>
#include <cuda.h>
#include <stdint.h>

typedef __nv_bfloat16 bf16;
#define PP(x) x

constexpr int SEQ = 2048, DM = 512, NH = 32, DH = 128, FF = 1792;

__device__ __align__(1024) bf16 g_xn[SEQ * DM];
__device__ __align__(1024) bf16 g_h[SEQ * FF];
__device__ __align__(1024) bf16 g_o[SEQ * NH * DH];
__device__ __align__(1024) bf16 g_g[SEQ * DM];
__device__ unsigned int g_hcnt[SEQ / 128];
__device__ unsigned int g_ocnt[SEQ / 128];
__device__ unsigned int g_gcnt[64];
__device__ volatile float g_dummy;

__device__ __forceinline__ uint32_t smem_u32(const void* p) { return (uint32_t)__cvta_generic_to_shared(p); }

__device__ __forceinline__ void mbar_init(uint32_t bar, uint32_t count) {
    asm volatile("mbarrier.init.shared::cta.b64 [%0], %1;" ::"r"(bar), "r"(count) : "memory");
}
__device__ __forceinline__ void mbar_expect_tx(uint32_t bar, uint32_t bytes) {
    asm volatile("mbarrier.arrive.expect_tx.shared::cta.b64 _, [%0], %1;" ::"r"(bar), "r"(bytes) : "memory");
}
__device__ __forceinline__ void mbar_arrive(uint32_t bar) {
    asm volatile("mbarrier.arrive.shared::cta.b64 _, [%0];" ::"r"(bar) : "memory");
}
__device__ __forceinline__ bool mbar_try_wait(uint32_t bar, uint32_t parity) {
    uint32_t ok;
    asm volatile(
        "{\n.reg .pred p;\n"
        "mbarrier.test_wait.parity.shared::cta.b64 p, [%1], %2;\n"
        "selp.u32 %0, 1, 0, p;\n}\n"
        : "=r"(ok)
        : "r"(bar), "r"(parity)
        : "memory");
    return ok != 0;
}
__device__ __forceinline__ void mbar_wait(uint32_t bar, uint32_t parity) {
    asm volatile(
        "{\n.reg .pred P1;\n.reg .u32 n;\nmov.u32 n, 0;\n"
        "LAB_WAIT:\n"
        "mbarrier.try_wait.parity.shared::cta.b64 P1, [%0], %1;\n"
        "@P1 bra DONE;\n"
        "add.u32 n, n, 1;\n"
        "setp.lt.u32 P1, n, 4194304;\n"
        "@P1 bra LAB_WAIT;\n"
        "trap;\n"
        "DONE:\n}\n" ::"r"(bar), "r"(parity)
        : "memory");
}
__device__ __forceinline__ void tma_load_3d(uint32_t dst, const CUtensorMap* map, uint32_t bar, int c0, int c1, int c2) {
    asm volatile(
        "cp.async.bulk.tensor.3d.shared::cluster.global.mbarrier::complete_tx::bytes [%0], [%1, {%3, %4, %5}], [%2];"
        ::"r"(dst), "l"((uint64_t)map), "r"(bar), "r"(c0), "r"(c1), "r"(c2)
        : "memory");
}
__device__ __forceinline__ void tma_store_3d(const CUtensorMap* map, uint32_t src, int c0, int c1, int c2) {
    asm volatile("cp.async.bulk.tensor.3d.global.shared::cta.bulk_group [%0, {%2, %3, %4}], [%1];"
                 ::"l"((uint64_t)map), "r"(src), "r"(c0), "r"(c1), "r"(c2)
                 : "memory");
}
__device__ __forceinline__ void tma_commit() { asm volatile("cp.async.bulk.commit_group;" ::: "memory"); }
__device__ __forceinline__ void tma_wait_read0() { asm volatile("cp.async.bulk.wait_group.read 0;" ::: "memory"); }
__device__ __forceinline__ void tma_wait_all0() { asm volatile("cp.async.bulk.wait_group 0;" ::: "memory"); }
__device__ __forceinline__ void fence_proxy_async() { asm volatile("fence.proxy.async.shared::cta;" ::: "memory"); }
__device__ __forceinline__ void prefetch_tmap(const CUtensorMap* map) {
    asm volatile("prefetch.tensormap [%0];" ::"l"((uint64_t)map) : "memory");
}
__device__ __forceinline__ void named_sync(int id, int n) { asm volatile("bar.sync %0, %1;" ::"r"(id), "r"(n) : "memory"); }
__device__ __forceinline__ void named_arrive(int id, int n) { asm volatile("bar.arrive %0, %1;" ::"r"(id), "r"(n) : "memory"); }

__device__ __forceinline__ void wgmma_fence() { asm volatile("wgmma.fence.sync.aligned;" ::: "memory"); }
__device__ __forceinline__ void wgmma_commit() { asm volatile("wgmma.commit_group.sync.aligned;" ::: "memory"); }
template <int N>
__device__ __forceinline__ void wgmma_wait() { asm volatile("wgmma.wait_group.sync.aligned %0;" ::"n"(N) : "memory"); }

template <int R>
__device__ __forceinline__ void reg_alloc() { asm volatile("setmaxnreg.inc.sync.aligned.u32 %0;" ::"n"(R)); }
template <int R>
__device__ __forceinline__ void reg_dealloc() { asm volatile("setmaxnreg.dec.sync.aligned.u32 %0;" ::"n"(R)); }

__device__ __forceinline__ uint64_t make_desc(uint32_t saddr, uint32_t lbo_bytes, uint32_t sbo_bytes) {
    uint64_t d = 0;
    d |= (uint64_t)((saddr & 0x3FFFF) >> 4);
    d |= (uint64_t)((lbo_bytes >> 4) & 0x3FFF) << 16;
    d |= (uint64_t)((sbo_bytes >> 4) & 0x3FFF) << 32;
    d |= (uint64_t)1 << 62;
    return d;
}

__device__ __forceinline__ float ex2(float x) {
    float y;
    asm volatile("ex2.approx.ftz.f32 %0, %1;" : "=f"(y) : "f"(x));
    return y;
}
__device__ __forceinline__ uint32_t pack_bf16(float lo, float hi) {
    uint32_t r;
    asm("cvt.rn.bf16x2.f32 %0, %1, %2;" : "=r"(r) : "f"(hi), "f"(lo));
    return r;
}
__device__ __forceinline__ uint32_t mul_bf16x2(uint32_t a, uint32_t b) {
    uint32_t r;
    asm("mul.rn.bf16x2 %0, %1, %2;" : "=r"(r) : "r"(a), "r"(b));
    return r;
}
__device__ __forceinline__ uint32_t fma_bf16x2(uint32_t a, uint32_t b, uint32_t c) {
    uint32_t r;
    asm("fma.rn.bf16x2 %0, %1, %2, %3;" : "=r"(r) : "r"(a), "r"(b), "r"(c));
    return r;
}
__device__ __forceinline__ uint32_t max_bf16x2(uint32_t a, uint32_t b) {
    uint32_t r;
    asm("max.bf16x2 %0, %1, %2;" : "=r"(r) : "r"(a), "r"(b));
    return r;
}
__device__ __forceinline__ float bf16lo(uint32_t v) { return __uint_as_float(v << 16); }
__device__ __forceinline__ float bf16hi(uint32_t v) { return __uint_as_float(v & 0xffff0000u); }
__device__ __forceinline__ float bf16_round(float x) { return __bfloat162float(__float2bfloat16_rn(x)); }
__device__ __forceinline__ float silu_f(float x) {
    const float h = 0.5f * x;
    float t;
    asm("tanh.approx.f32 %0, %1;" : "=f"(t) : "f"(h));
    return fmaf(h, t, h);
}

__device__ __forceinline__ void stmatrix_x4(uint32_t addr, uint32_t r0, uint32_t r1, uint32_t r2, uint32_t r3) {
    asm volatile("stmatrix.sync.aligned.m8n8.x4.shared.b16 [%0], {%1, %2, %3, %4};"
                 ::"r"(addr), "r"(r0), "r"(r1), "r"(r2), "r"(r3)
                 : "memory");
}

#define ACC64(d) \
    "+f"(d[0]), "+f"(d[1]), "+f"(d[2]), "+f"(d[3]), "+f"(d[4]), "+f"(d[5]), "+f"(d[6]), "+f"(d[7]), \
    "+f"(d[8]), "+f"(d[9]), "+f"(d[10]), "+f"(d[11]), "+f"(d[12]), "+f"(d[13]), "+f"(d[14]), "+f"(d[15]), \
    "+f"(d[16]), "+f"(d[17]), "+f"(d[18]), "+f"(d[19]), "+f"(d[20]), "+f"(d[21]), "+f"(d[22]), "+f"(d[23]), \
    "+f"(d[24]), "+f"(d[25]), "+f"(d[26]), "+f"(d[27]), "+f"(d[28]), "+f"(d[29]), "+f"(d[30]), "+f"(d[31]), \
    "+f"(d[32]), "+f"(d[33]), "+f"(d[34]), "+f"(d[35]), "+f"(d[36]), "+f"(d[37]), "+f"(d[38]), "+f"(d[39]), \
    "+f"(d[40]), "+f"(d[41]), "+f"(d[42]), "+f"(d[43]), "+f"(d[44]), "+f"(d[45]), "+f"(d[46]), "+f"(d[47]), \
    "+f"(d[48]), "+f"(d[49]), "+f"(d[50]), "+f"(d[51]), "+f"(d[52]), "+f"(d[53]), "+f"(d[54]), "+f"(d[55]), \
    "+f"(d[56]), "+f"(d[57]), "+f"(d[58]), "+f"(d[59]), "+f"(d[60]), "+f"(d[61]), "+f"(d[62]), "+f"(d[63])

#define ACC64_STR \
    "{%0, %1, %2, %3, %4, %5, %6, %7, %8, %9, %10, %11, %12, %13, %14, %15, " \
    "%16, %17, %18, %19, %20, %21, %22, %23, %24, %25, %26, %27, %28, %29, %30, %31, " \
    "%32, %33, %34, %35, %36, %37, %38, %39, %40, %41, %42, %43, %44, %45, %46, %47, " \
    "%48, %49, %50, %51, %52, %53, %54, %55, %56, %57, %58, %59, %60, %61, %62, %63}"

template <int TB>
__device__ __forceinline__ void wgmma_ss_n128(float (&d)[64], uint64_t da, uint64_t db, int scale_d) {
    asm volatile(
        "{\n.reg .pred p;\nsetp.ne.b32 p, %66, 0;\n"
        "wgmma.mma_async.sync.aligned.m64n128k16.f32.bf16.bf16 " ACC64_STR ", %64, %65, p, 1, 1, 0, %67;\n}\n"
        : ACC64(d)
        : "l"(da), "l"(db), "r"(scale_d), "n"(TB));
}
template <int TB>
__device__ __forceinline__ void wgmma_rs_n128(float (&d)[64], uint32_t a0, uint32_t a1, uint32_t a2, uint32_t a3,
                                              uint64_t db, int scale_d) {
    asm volatile(
        "{\n.reg .pred p;\nsetp.ne.b32 p, %69, 0;\n"
        "wgmma.mma_async.sync.aligned.m64n128k16.f32.bf16.bf16 " ACC64_STR ", {%64, %65, %66, %67}, %68, p, 1, 1, %70;\n}\n"
        : ACC64(d)
        : "r"(a0), "r"(a1), "r"(a2), "r"(a3), "l"(db), "r"(scale_d), "n"(TB));
}

constexpr uint32_t DESC_HI = 0x40000040u;
__device__ __forceinline__ uint32_t desc_lo(uint32_t saddr, uint32_t lbo_bytes) {
    return ((saddr & 0x3FFFF) >> 4) | ((lbo_bytes >> 4) << 16);
}
template <int TB>
__device__ __forceinline__ void wgmma_ss_lo(float (&d)[64], uint32_t da, uint32_t db, int scale_d) {
    asm volatile(
        "{\n.reg .pred p;\n.reg .b64 xa, xb;\nsetp.ne.b32 p, %66, 0;\n"
        "mov.b64 xa, {%64, %68};\nmov.b64 xb, {%65, %68};\n"
        "wgmma.mma_async.sync.aligned.m64n128k16.f32.bf16.bf16 " ACC64_STR ", xa, xb, p, 1, 1, 0, %67;\n}\n"
        : ACC64(d)
        : "r"(da), "r"(db), "r"(scale_d), "n"(TB), "r"(DESC_HI));
}
__device__ __forceinline__ void wgmma_rs_lo_tb(float (&d)[64], uint32_t a0, uint32_t a1, uint32_t a2, uint32_t a3, uint32_t db) {
    asm volatile(
        "{\n.reg .b64 xb;\nmov.b64 xb, {%68, %69};\n"
        "wgmma.mma_async.sync.aligned.m64n128k16.f32.bf16.bf16 " ACC64_STR ", {%64, %65, %66, %67}, xb, 1, 1, 1, 1;\n}\n"
        : ACC64(d)
        : "r"(a0), "r"(a1), "r"(a2), "r"(a3), "r"(db), "r"(DESC_HI));
}

__global__ void __launch_bounds__(256) ln_kernel(const bf16* __restrict__ x) {
    int warp = threadIdx.x >> 5, lane = threadIdx.x & 31;
    int row = blockIdx.x * 8 + warp;
    if (blockIdx.x == 0 && threadIdx.x < SEQ / 128) g_hcnt[threadIdx.x] = 0;
    if (blockIdx.x == 1 && threadIdx.x < SEQ / 128) g_ocnt[threadIdx.x] = 0;
    if (blockIdx.x == 2 && threadIdx.x < 64) g_gcnt[threadIdx.x] = 0;
    const uint4* src = reinterpret_cast<const uint4*>(x + (size_t)row * DM);
    uint4 v[2];
    v[0] = src[lane];
    v[1] = src[lane + 32];
    float f[16];
#pragma unroll
    for (int i = 0; i < 2; i++) {
        const __nv_bfloat162* p = reinterpret_cast<const __nv_bfloat162*>(&v[i]);
#pragma unroll
        for (int j = 0; j < 4; j++) {
            float2 t = __bfloat1622float2(p[j]);
            f[i * 8 + j * 2] = t.x;
            f[i * 8 + j * 2 + 1] = t.y;
        }
    }
    float s = 0.f;
#pragma unroll
    for (int i = 0; i < 16; i++) s += f[i];
#pragma unroll
    for (int o = 16; o > 0; o >>= 1) s += __shfl_xor_sync(0xffffffffu, s, o);
    float mean = s * (1.0f / DM);
    float q = 0.f;
#pragma unroll
    for (int i = 0; i < 16; i++) {
        float d = f[i] - mean;
        q += d * d;
    }
#pragma unroll
    for (int o = 16; o > 0; o >>= 1) q += __shfl_xor_sync(0xffffffffu, q, o);
    float var_b = bf16_round(q * (1.0f / DM));
    float mean_b = bf16_round(mean);
    float den = bf16_round(sqrtf(bf16_round(var_b + 1e-5f)));
    uint4 o[2];
#pragma unroll
    for (int i = 0; i < 2; i++) {
        uint32_t* p = reinterpret_cast<uint32_t*>(&o[i]);
#pragma unroll
        for (int j = 0; j < 4; j++) {
            float a = bf16_round(f[i * 8 + j * 2] - mean_b) / den;
            float b = bf16_round(f[i * 8 + j * 2 + 1] - mean_b) / den;
            p[j] = pack_bf16(a, b);
        }
    }
    uint4* dst = reinterpret_cast<uint4*>(g_xn + (size_t)row * DM);
    dst[lane] = o[0];
    dst[lane + 32] = o[1];
}

constexpr int AT_STAGES = 3;
constexpr int TILE_BYTES = 128 * 128 * 2;
struct __align__(1024) AttnSmem {
    uint8_t k[AT_STAGES][TILE_BYTES];
    uint8_t v[AT_STAGES][TILE_BYTES];
    uint8_t o[TILE_BYTES];
    uint64_t full_k[AT_STAGES], full_v[AT_STAGES], empty_k[AT_STAGES], empty_v[AT_STAGES];
    uint64_t st_free[2];
};

constexpr int NUM_CTAS = 132;
constexpr int MAX_ITEMS = 14;
enum { T_ATT = 0, T_F1 = 1, T_F2 = 2, T_OP = 3 };
struct Maps {
    CUtensorMap a[4], b[4], st[4];
    CUtensorMap k, v;
};
struct Sched {
    uint16_t item[NUM_CTAS][MAX_ITEMS];
    uint8_t count[NUM_CTAS];
};

__global__ void __launch_bounds__(384, 1)
attn_kernel(const __grid_constant__ Maps tm, const __grid_constant__ Sched sched, const bf16* __restrict__ x) {
    extern __shared__ uint8_t smem_raw[];
    AttnSmem& sm = *reinterpret_cast<AttnSmem*>((reinterpret_cast<uintptr_t>(smem_raw) + 1023) & ~uintptr_t(1023));
    const int tid = threadIdx.x;
    const int wg = __shfl_sync(0xffffffffu, tid >> 7, 0);
    const int n_items = sched.count[blockIdx.x];

    if (tid == 0) {
#pragma unroll
        for (int s = 0; s < AT_STAGES; s++) {
            mbar_init(smem_u32(&sm.full_k[s]), 1);
            mbar_init(smem_u32(&sm.full_v[s]), 1);
            mbar_init(smem_u32(&sm.empty_k[s]), 8);
            mbar_init(smem_u32(&sm.empty_v[s]), 8);
        }
        mbar_init(smem_u32(&sm.st_free[0]), 1);
        mbar_init(smem_u32(&sm.st_free[1]), 1);
        asm volatile("fence.mbarrier_init.release.cluster;" ::: "memory");
    }
    __syncthreads();
    constexpr int BAR_SCHED0 = 1, BAR_EPI0 = 3, BAR_ST0 = 5;

    if (wg == 0) {
        reg_dealloc<24>();
        if (tid >= 32 && tid < 96) {
            const int cw = (tid >> 5) - 1;
            const uint32_t obase = smem_u32(sm.o) + cw * 16384;
            for (int it = 0; it < n_items; it++) {
                const int item = sched.item[blockIdx.x][it];
                const int type = item >> 12, a = (item >> 4) & 0xff, b = item & 15;
                named_sync(BAR_ST0 + cw, 160);
                if ((tid & 31) == 0) {
                    tma_store_3d(&tm.st[type], obase, 0, b * 128 + cw * 64, a * 2);
                    tma_commit();
                    tma_wait_read0();
                    mbar_arrive(smem_u32(&sm.st_free[cw]));
                    if (type != T_OP) {
                        tma_wait_all0();
                        asm volatile("fence.proxy.async;" ::: "memory");
                        __threadfence();
                        atomicAdd(type == T_F1 ? &g_hcnt[b] : (type == T_ATT ? &g_ocnt[b] : &g_gcnt[b * 4 + a]), 1u);
                    }
                }
                __syncwarp();
            }
            if ((tid & 31) == 0) tma_wait_all0();
        }
        if (tid == 0) {
            int stage = 0;
            uint32_t phase = 0;
            for (int it = 0; it < n_items; it++) {
                const int item = sched.item[blockIdx.x][it];
                const int type = item >> 12, a = (item >> 4) & 0xff, b = item & 15;
                const CUtensorMap* ta = &tm.a[type];
                const CUtensorMap* tb = &tm.b[type];
                const int nch = (type == T_F2) ? FF / 128 : (type == T_OP ? NH * DH / 128 : DM / 128);
                if (type >= T_F2) {
                    const unsigned int* cnt = (type == T_F2) ? &g_hcnt[b] : &g_ocnt[b];
                    const unsigned int need = (type == T_F2) ? 2 * (FF / 128) : 2 * NH;
                    unsigned int v, spins = 0;
                    do {
                        asm volatile("ld.acquire.gpu.global.u32 %0, [%1];" : "=r"(v) : "l"(cnt) : "memory");
                    } while (v < need && ++spins < (1u << 24));
                    asm volatile("fence.proxy.async;" ::: "memory");
                }
                for (int kc = 0; kc < nch; kc++) {
                    if (type == T_OP && kc == nch - 1) {
                        unsigned int v, spins = 0;
                        do {
                            asm volatile("ld.acquire.gpu.global.u32 %0, [%1];" : "=r"(v) : "l"(&g_gcnt[b * 4 + a]) : "memory");
                        } while (v < 2 && ++spins < (1u << 24));
                    }
                    mbar_wait(smem_u32(&sm.empty_k[stage]), phase ^ 1);
                    mbar_expect_tx(smem_u32(&sm.full_k[stage]), TILE_BYTES);
                    tma_load_3d(smem_u32(sm.k[stage]), ta, smem_u32(&sm.full_k[stage]), 0, b * 128, kc * 2);
                    mbar_wait(smem_u32(&sm.empty_v[stage]), phase ^ 1);
                    mbar_expect_tx(smem_u32(&sm.full_v[stage]), TILE_BYTES);
                    tma_load_3d(smem_u32(sm.v[stage]), tb, smem_u32(&sm.full_v[stage]), 0, kc * 128, a * 2);
                    if (++stage == AT_STAGES) { stage = 0; phase ^= 1; }
                }
                if (type == T_ATT) {
                    for (int j = 0; j < 16; j++) {
                        mbar_wait(smem_u32(&sm.empty_k[stage]), phase ^ 1);
                        mbar_expect_tx(smem_u32(&sm.full_k[stage]), TILE_BYTES);
                        tma_load_3d(smem_u32(sm.k[stage]), &tm.k, smem_u32(&sm.full_k[stage]), 0, a * SEQ + j * 128, 0);
                        mbar_wait(smem_u32(&sm.empty_v[stage]), phase ^ 1);
                        mbar_expect_tx(smem_u32(&sm.full_v[stage]), TILE_BYTES);
                        tma_load_3d(smem_u32(sm.v[stage]), &tm.v, smem_u32(&sm.full_v[stage]), 0, a * SEQ + j * 128, 0);
                        if (++stage == AT_STAGES) { stage = 0; phase ^= 1; }
                    }
                }
            }
        }
    } else {
        reg_alloc<240>();
        const int cw = wg - 1;
        const int lane = tid & 31;
        const int warp_in_wg = (tid >> 5) & 3;
        const float c = 1.4426950408889634f;
        const uint32_t SCALE_HI2 = 0x3DB53DB5u, SCALE_LO2 = 0x371E371Eu;
        const uint32_t obase = smem_u32(sm.o) + cw * 16384;
        const int st_row = warp_in_wg * 16 + ((lane >> 3) & 1) * 8 + (lane & 7);

        const uint32_t dq = __shfl_sync(0xffffffffu, desc_lo(obase, 16), 0);
        const uint32_t dk0 = __shfl_sync(0xffffffffu, desc_lo(smem_u32(sm.k[0]), 16), 0);
        const uint32_t dv0 = dk0 - (1u << 16) + (1024u << 16) + AT_STAGES * (TILE_BYTES >> 4);

        PP(if (cw == 1) named_arrive(BAR_SCHED0 + 0, 256));

        int stage = 0;
        uint32_t phase = 0;
        float S[64], O[64];
        uint32_t P[32];

        for (int it = 0; it < n_items; it++) {
            const int item = sched.item[blockIdx.x][it];
            const int type = item >> 12;
            const int nch = (type == T_F2) ? FF / 128 : (type == T_OP ? NH * DH / 128 : DM / 128);
            {
                int prev = -1;
#pragma unroll 1
                for (int kc = 0; kc < nch; kc++) {
                    mbar_wait(smem_u32(&sm.full_k[stage]), phase);
                    mbar_wait(smem_u32(&sm.full_v[stage]), phase);
                    const uint64_t da = make_desc(smem_u32(sm.k[stage]) + cw * 64 * 128, 16, 1024);
                    const uint64_t db = make_desc(smem_u32(sm.v[stage]), 16384, 1024);
                    wgmma_fence();
#pragma unroll
                    for (int kk = 0; kk < 8; kk++) {
                        wgmma_ss_n128<1>(S, da + (uint64_t)(((kk >> 2) * 16384 + (kk & 3) * 32) >> 4),
                                         db + (uint64_t)((kk * 2048) >> 4), (kc | kk) != 0);
                    }
                    wgmma_commit();
                    wgmma_wait<1>();
                    if (prev >= 0 && lane == 0) {
                        mbar_arrive(smem_u32(&sm.empty_k[prev]));
                        mbar_arrive(smem_u32(&sm.empty_v[prev]));
                    }
                    prev = stage;
                    if (++stage == AT_STAGES) { stage = 0; phase ^= 1; }
                }
                if (type == T_OP) {
                    const size_t off0 = (size_t)((item & 15) * 128 + cw * 64 + warp_in_wg * 16 + (lane >> 2)) * DM +
                                        ((item >> 4) & 0xff) * 128 + (lane & 3) * 2;
#pragma unroll
                    for (int i = 0; i < 16; i++) {
#pragma unroll
                        for (int hh = 0; hh < 2; hh++) {
                            const size_t off = off0 + (size_t)hh * 8 * DM + i * 8;
                            O[4 * i + 2 * hh] = __uint_as_float(__ldg(reinterpret_cast<const uint32_t*>(x + off)));
                            O[4 * i + 2 * hh + 1] = __uint_as_float(__ldcg(reinterpret_cast<const uint32_t*>(g_g + off)));
                        }
                    }
                }
                wgmma_wait<0>();
                if (lane == 0) {
                    mbar_arrive(smem_u32(&sm.empty_k[prev]));
                    mbar_arrive(smem_u32(&sm.empty_v[prev]));
                }
            }
            if (type == T_OP) {
#pragma unroll
                for (int i = 0; i < 32; i++) {
                    const uint32_t xv = __float_as_uint(O[2 * i]), gv = __float_as_uint(O[2 * i + 1]);
                    S[2 * i] = bf16lo(xv) + bf16_round(bf16_round(S[2 * i]) * bf16lo(gv));
                    S[2 * i + 1] = bf16hi(xv) + bf16_round(bf16_round(S[2 * i + 1]) * bf16hi(gv));
                }
            } else if (type != T_ATT) {
#pragma unroll
                for (int i = 0; i < 64; i++) S[i] = silu_f(bf16_round(S[i]));
            }
            mbar_wait(smem_u32(&sm.st_free[cw]), (it & 1) ^ 1);
#pragma unroll
            for (int i = 0; i < 16; i += 2) {
                const int cc = i + (lane >> 4);
                const uint32_t addr = obase + (cc >> 3) * 8192 + st_row * 128 + (((cc & 7) ^ (st_row & 7)) << 4);
                stmatrix_x4(addr, pack_bf16(S[4 * i], S[4 * i + 1]), pack_bf16(S[4 * i + 2], S[4 * i + 3]),
                            pack_bf16(S[4 * i + 4], S[4 * i + 5]), pack_bf16(S[4 * i + 6], S[4 * i + 7]));
            }
            fence_proxy_async();
            if (type != T_ATT) {
                named_arrive(BAR_ST0 + cw, 160);
                continue;
            }
            named_sync(BAR_EPI0 + cw, 128);
#pragma unroll
            for (int i = 0; i < 64; i++) O[i] = 0.f;

            float m0 = -INFINITY, m1 = -INFINITY, l0 = 0.f, l1 = 0.f, a0 = 0.f, a1 = 0.f;
            bool resc = false;
            const float TAU = 11.0f;
            const uint32_t fk0 = smem_u32(&sm.full_k[0]), fv0 = smem_u32(&sm.full_v[0]);
            const uint32_t ek0 = smem_u32(&sm.empty_k[0]), ev0 = smem_u32(&sm.empty_v[0]);

            uint32_t T[32];
            float n0, n1;
            auto softmax1 = [&]() {
#pragma unroll
                for (int i = 0; i < 32; i++) {
                    const uint32_t sb = pack_bf16(S[2 * i], S[2 * i + 1]);
                    T[i] = fma_bf16x2(sb, SCALE_HI2, mul_bf16x2(sb, SCALE_LO2));
                }
                uint32_t y0 = max_bf16x2(T[0], T[2]), y1 = max_bf16x2(T[1], T[3]);
#pragma unroll
                for (int i = 2; i < 16; i++) {
                    y0 = max_bf16x2(y0, T[2 * i]);
                    y1 = max_bf16x2(y1, T[2 * i + 1]);
                }
                float x0 = fmaxf(bf16lo(y0), bf16hi(y0));
                float x1 = fmaxf(bf16lo(y1), bf16hi(y1));
                x0 = fmaxf(x0, __shfl_xor_sync(0xffffffffu, x0, 1));
                x1 = fmaxf(x1, __shfl_xor_sync(0xffffffffu, x1, 1));
                x0 = fmaxf(x0, __shfl_xor_sync(0xffffffffu, x0, 2));
                x1 = fmaxf(x1, __shfl_xor_sync(0xffffffffu, x1, 2));
                resc = __any_sync(0xffffffffu, (x0 - m0 > TAU) || (x1 - m1 > TAU));
                x0 = resc ? fmaxf(x0, m0) : m0;
                x1 = resc ? fmaxf(x1, m1) : m1;
                a0 = ex2((m0 - x0) * c);
                a1 = ex2((m1 - x1) * c);
                m0 = x0;
                m1 = x1;
                n0 = -m0 * c;
                n1 = -m1 * c;
                while (n0 != n0) n0 = g_dummy;
            };
            auto softmax2 = [&]() {
                float s0 = 0.f, s1 = 0.f;
#pragma unroll
                for (int i = 0; i < 16; i++) {
                    const float e0 = ex2(fmaf(bf16lo(T[2 * i]), c, n0));
                    const float e1 = ex2(fmaf(bf16hi(T[2 * i]), c, n0));
                    const float e2 = ex2(fmaf(bf16lo(T[2 * i + 1]), c, n1));
                    const float e3 = ex2(fmaf(bf16hi(T[2 * i + 1]), c, n1));
                    s0 += e0 + e1;
                    s1 += e2 + e3;
                    P[2 * i] = pack_bf16(e0, e1);
                    P[2 * i + 1] = pack_bf16(e2, e3);
                }
                l0 = l0 * a0 + s0;
                l1 = l1 * a1 + s1;
            };
            auto issue_qk = [&](uint32_t dk) {
                wgmma_fence();
#pragma unroll
                for (int kk = 0; kk < 8; kk++)
                    wgmma_ss_lo<0>(S, dq + (((kk >> 2) * 8192 + (kk & 3) * 32) >> 4),
                                   dk + (((kk >> 2) * 16384 + (kk & 3) * 32) >> 4), kk != 0);
                wgmma_commit();
            };
            auto issue_pv = [&](uint32_t dv) {
                if (resc) {
#pragma unroll
                    for (int i = 0; i < 16; i++) {
                        O[4 * i] *= a0;
                        O[4 * i + 1] *= a0;
                        O[4 * i + 2] *= a1;
                        O[4 * i + 3] *= a1;
                    }
                }
                wgmma_fence();
#pragma unroll
                for (int kk = 0; kk < 8; kk++)
                    wgmma_rs_lo_tb(O, P[4 * kk], P[4 * kk + 1], P[4 * kk + 2], P[4 * kk + 3], dv + ((kk * 2048) >> 4));
                wgmma_commit();
            };

            int vstage = stage;
            uint32_t vphase = phase;
            bool okk, okv;
            {
                mbar_wait(fk0 + stage * 8, phase);
                PP(named_sync(BAR_SCHED0 + cw, 256));
                issue_qk(dk0 + stage * (TILE_BYTES >> 4));
                PP(named_arrive(BAR_SCHED0 + (cw ^ 1), 256));
                if (++stage == AT_STAGES) { stage = 0; phase ^= 1; }
                okk = mbar_try_wait(fk0 + stage * 8, phase);
                okv = mbar_try_wait(fv0 + vstage * 8, vphase);
                wgmma_wait<0>();
                if (lane == 0) mbar_arrive(ek0 + vstage * 8);
            }
            softmax1();
            softmax2();
            resc = false;

#pragma unroll 1
            for (int j = 1; j < 16; j++) {
                const int ust = __shfl_sync(0xffffffffu, stage, 0), uvs = __shfl_sync(0xffffffffu, vstage, 0);
                if (!okk) mbar_wait(fk0 + stage * 8, phase);
                if (!okv) mbar_wait(fv0 + vstage * 8, vphase);
                PP(named_sync(BAR_SCHED0 + cw, 256));
                issue_qk(dk0 + ust * (TILE_BYTES >> 4));
                issue_pv(dv0 + uvs * (TILE_BYTES >> 4));
                PP(named_arrive(BAR_SCHED0 + (cw ^ 1), 256));
                const int pv = vstage;
                vstage = stage;
                vphase = phase;
                if (++stage == AT_STAGES) { stage = 0; phase ^= 1; }
                okk = mbar_try_wait(fk0 + stage * 8, phase);
                okv = mbar_try_wait(fv0 + vstage * 8, vphase);
                wgmma_wait<1>();
                if (lane == 0) mbar_arrive(ek0 + vstage * 8);
                softmax1();
                wgmma_wait<0>();
                if (lane == 0) mbar_arrive(ev0 + pv * 8);
                softmax2();
            }
            if (!okv) mbar_wait(fv0 + vstage * 8, vphase);
            issue_pv(dv0 + vstage * (TILE_BYTES >> 4));
            wgmma_wait<0>();
            if (lane == 0) mbar_arrive(ev0 + vstage * 8);
            l0 += __shfl_xor_sync(0xffffffffu, l0, 1);
            l1 += __shfl_xor_sync(0xffffffffu, l1, 1);
            l0 += __shfl_xor_sync(0xffffffffu, l0, 2);
            l1 += __shfl_xor_sync(0xffffffffu, l1, 2);
            const float i0 = 1.0f / l0, i1 = 1.0f / l1;
            named_sync(BAR_EPI0 + cw, 128);
#pragma unroll
            for (int i = 0; i < 16; i += 2) {
                const int cc = i + (lane >> 4);
                const uint32_t addr = obase + (cc >> 3) * 8192 + st_row * 128 + (((cc & 7) ^ (st_row & 7)) << 4);
                stmatrix_x4(addr, pack_bf16(O[4 * i] * i0, O[4 * i + 1] * i0), pack_bf16(O[4 * i + 2] * i1, O[4 * i + 3] * i1),
                            pack_bf16(O[4 * i + 4] * i0, O[4 * i + 5] * i0), pack_bf16(O[4 * i + 6] * i1, O[4 * i + 7] * i1));
            }
            fence_proxy_async();
            named_arrive(BAR_ST0 + cw, 160);
        }
    }
}

typedef CUresult (*EncodeFn)(CUtensorMap*, CUtensorMapDataType, cuuint32_t, void*, const cuuint64_t*, const cuuint64_t*,
                             const cuuint32_t*, const cuuint32_t*, CUtensorMapInterleave, CUtensorMapSwizzle,
                             CUtensorMapL2promotion, CUtensorMapFloatOOBfill);

static CUtensorMap make_map(EncodeFn fn, const void* ptr, uint64_t rows, uint64_t cols, uint32_t box_rows, uint32_t box_blk) {
    CUtensorMap m;
    cuuint64_t dims[3] = {64, rows, cols / 64};
    cuuint64_t strides[2] = {cols * 2, 128};
    cuuint32_t box[3] = {64, box_rows, box_blk};
    cuuint32_t es[3] = {1, 1, 1};
    fn(&m, CU_TENSOR_MAP_DATA_TYPE_BFLOAT16, 3, const_cast<void*>(ptr), dims, strides, box, es, CU_TENSOR_MAP_INTERLEAVE_NONE,
       CU_TENSOR_MAP_SWIZZLE_128B, CU_TENSOR_MAP_L2_PROMOTION_L2_256B, CU_TENSOR_MAP_FLOAT_OOB_FILL_NONE);
    return m;
}

extern "C" void kernel_launch(void* const* d_in, const int* in_sizes, int n_in, void* d_out, int out_size) {
    const bf16* x = (const bf16*)d_in[0];
    const bf16* kc = (const bf16*)d_in[1];
    const bf16* vc = (const bf16*)d_in[2];
    const bf16* wq = (const bf16*)d_in[3];
    const bf16* wo = (const bf16*)d_in[4];
    const bf16* w1 = (const bf16*)d_in[6];
    const bf16* w2 = (const bf16*)d_in[7];
    bf16* out = (bf16*)d_out;

    static EncodeFn fn = nullptr;
    static void *p_xn = nullptr, *p_h = nullptr, *p_o = nullptr, *p_g = nullptr;
    static Sched sched;
    if (!fn) {
        void* f = nullptr;
        cudaDriverEntryPointQueryResult st;
        cudaGetDriverEntryPoint("cuTensorMapEncodeTiled", &f, cudaEnableDefault, &st);
        fn = (EncodeFn)f;
        cudaGetSymbolAddress(&p_xn, g_xn);
        cudaGetSymbolAddress(&p_h, g_h);
        cudaGetSymbolAddress(&p_o, g_o);
        cudaGetSymbolAddress(&p_g, g_g);
        cudaFuncSetAttribute(attn_kernel, cudaFuncAttributeMaxDynamicSharedMemorySize, (int)sizeof(AttnSmem) + 1024);
        const double C_ATT = 54.3, C_F1 = 7.0, C_F2 = 19.8, C_OP = 40.0;
        static double fr[NUM_CTAS], odone[16], hdone[16];
        for (int i = 0; i < NUM_CTAS; i++) { fr[i] = 2.5; sched.count[i] = 0; }
        for (int i = 0; i < 16; i++) odone[i] = hdone[i] = 0;
        auto push = [&](int cta, int type, int a, int b) { sched.item[cta][sched.count[cta]++] = (uint16_t)((type << 12) | (a << 4) | b); };
        double t_att = 0;
        for (int t = 0; t < NH * 16; t++) {
            const int cta = t % NUM_CTAS;
            push(cta, T_ATT, t >> 4, t & 15);
            fr[cta] += C_ATT;
            if (fr[cta] > odone[t & 15]) odone[t & 15] = fr[cta];
            if (fr[cta] > t_att) t_att = fr[cta];
        }
        int n1 = 0, n2 = 0, n3 = 0;
        while (n1 < 224 || n2 < 64 || n3 < 64) {
            int cta = 0;
            for (int i = 1; i < NUM_CTAS; i++) if (fr[i] < fr[cta]) cta = i;
            const double t = fr[cta];
            if (n1 < 224 && (t + C_F1 <= t_att + 1.0 || n3 == 64)) {
                const int b = n1 / 14;
                push(cta, T_F1, n1 % 14, b);
                fr[cta] = t + C_F1;
                if (fr[cta] > hdone[b]) hdone[b] = fr[cta];
                n1++;
            } else if (n3 < 64) {
                const int b = n3 >> 2;
                push(cta, T_OP, n3 & 3, b);
                fr[cta] = (t > odone[b] ? t : odone[b]) + C_OP;
                n3++;
            } else {
                const int b = n2 >> 2;
                push(cta, T_F2, n2 & 3, b);
                fr[cta] = (t > hdone[b] ? t : hdone[b]) + C_F2;
                n2++;
            }
        }
    }
    Maps tm;
    tm.a[T_ATT] = tm.a[T_F1] = make_map(fn, p_xn, SEQ, DM, 128, 2);
    tm.a[T_F2] = make_map(fn, p_h, SEQ, FF, 128, 2);
    tm.a[T_OP] = make_map(fn, p_o, SEQ, NH * DH, 128, 2);
    tm.b[T_ATT] = make_map(fn, wq, DM, NH * DH, 128, 2);
    tm.b[T_F1] = make_map(fn, w1, DM, FF, 128, 2);
    tm.b[T_F2] = make_map(fn, w2, FF, DM, 128, 2);
    tm.b[T_OP] = make_map(fn, wo, NH * DH, DM, 128, 2);
    tm.st[T_ATT] = make_map(fn, p_o, SEQ, NH * DH, 64, 2);
    tm.st[T_F1] = make_map(fn, p_h, SEQ, FF, 64, 2);
    tm.st[T_F2] = make_map(fn, p_g, SEQ, DM, 64, 2);
    tm.st[T_OP] = make_map(fn, out, SEQ, DM, 64, 2);
    tm.k = make_map(fn, kc, NH * SEQ, DH, 128, 2);
    tm.v = make_map(fn, vc, NH * SEQ, DH, 128, 2);

    ln_kernel<<<SEQ / 8, 256>>>(x);
    attn_kernel<<<NUM_CTAS, 384, sizeof(AttnSmem) + 1024>>>(tm, sched, x);
}
```

```cpp
#include <cuda_runtime.h>
#include <cuda_bf16.h>
#include <cuda.h>
#include <stdint.h>

typedef __nv_bfloat16 bf16;
#define PP(x) x

constexpr int SEQ = 2048, DM = 512, NH = 32, DH = 128, FF = 1792;

__device__ __align__(1024) bf16 g_xn[SEQ * DM];
__device__ __align__(1024) bf16 g_h[SEQ * FF];
__device__ __align__(1024) bf16 g_o[SEQ * NH * DH];
__device__ __align__(1024) bf16 g_g[SEQ * DM];
__device__ unsigned int g_hcnt[SEQ / 128];
__device__ unsigned int g_ocnt[SEQ / 128];
__device__ unsigned int g_gcnt[64];
__device__ volatile float g_dummy;

__device__ __forceinline__ uint32_t smem_u32(const void* p) { return (uint32_t)__cvta_generic_to_shared(p); }

__device__ __forceinline__ void mbar_init(uint32_t bar, uint32_t count) {
    asm volatile("mbarrier.init.shared::cta.b64 [%0], %1;" ::"r"(bar), "r"(count) : "memory");
}
__device__ __forceinline__ void mbar_expect_tx(uint32_t bar, uint32_t bytes) {
    asm volatile("mbarrier.arrive.expect_tx.shared::cta.b64 _, [%0], %1;" ::"r"(bar), "r"(bytes) : "memory");
}
__device__ __forceinline__ void mbar_arrive(uint32_t bar) {
    asm volatile("mbarrier.arrive.shared::cta.b64 _, [%0];" ::"r"(bar) : "memory");
}
__device__ __forceinline__ bool mbar_try_wait(uint32_t bar, uint32_t parity) {
    uint32_t ok;
    asm volatile(
        "{\n.reg .pred p;\n"
        "mbarrier.test_wait.parity.shared::cta.b64 p, [%1], %2;\n"
        "selp.u32 %0, 1, 0, p;\n}\n"
        : "=r"(ok)
        : "r"(bar), "r"(parity)
        : "memory");
    return ok != 0;
}
__device__ __forceinline__ void mbar_wait(uint32_t bar, uint32_t parity) {
    asm volatile(
        "{\n.reg .pred P1;\n.reg .u32 n;\nmov.u32 n, 0;\n"
        "LAB_WAIT:\n"
        "mbarrier.try_wait.parity.shared::cta.b64 P1, [%0], %1;\n"
        "@P1 bra DONE;\n"
        "add.u32 n, n, 1;\n"
        "setp.lt.u32 P1, n, 4194304;\n"
        "@P1 bra LAB_WAIT;\n"
        "trap;\n"
        "DONE:\n}\n" ::"r"(bar), "r"(parity)
        : "memory");
}
__device__ __forceinline__ void tma_load_3d(uint32_t dst, const CUtensorMap* map, uint32_t bar, int c0, int c1, int c2) {
    asm volatile(
        "cp.async.bulk.tensor.3d.shared::cluster.global.mbarrier::complete_tx::bytes [%0], [%1, {%3, %4, %5}], [%2];"
        ::"r"(dst), "l"((uint64_t)map), "r"(bar), "r"(c0), "r"(c1), "r"(c2)
        : "memory");
}
__device__ __forceinline__ void tma_store_3d(const CUtensorMap* map, uint32_t src, int c0, int c1, int c2) {
    asm volatile("cp.async.bulk.tensor.3d.global.shared::cta.bulk_group [%0, {%2, %3, %4}], [%1];"
                 ::"l"((uint64_t)map), "r"(src), "r"(c0), "r"(c1), "r"(c2)
                 : "memory");
}
__device__ __forceinline__ void tma_commit() { asm volatile("cp.async.bulk.commit_group;" ::: "memory"); }
__device__ __forceinline__ void tma_wait_read0() { asm volatile("cp.async.bulk.wait_group.read 0;" ::: "memory"); }
__device__ __forceinline__ void tma_wait_all0() { asm volatile("cp.async.bulk.wait_group 0;" ::: "memory"); }
__device__ __forceinline__ void fence_proxy_async() { asm volatile("fence.proxy.async.shared::cta;" ::: "memory"); }
__device__ __forceinline__ void prefetch_tmap(const CUtensorMap* map) {
    asm volatile("prefetch.tensormap [%0];" ::"l"((uint64_t)map) : "memory");
}
__device__ __forceinline__ void named_sync(int id, int n) { asm volatile("bar.sync %0, %1;" ::"r"(id), "r"(n) : "memory"); }
__device__ __forceinline__ void named_arrive(int id, int n) { asm volatile("bar.arrive %0, %1;" ::"r"(id), "r"(n) : "memory"); }

__device__ __forceinline__ void wgmma_fence() { asm volatile("wgmma.fence.sync.aligned;" ::: "memory"); }
__device__ __forceinline__ void wgmma_commit() { asm volatile("wgmma.commit_group.sync.aligned;" ::: "memory"); }
template <int N>
__device__ __forceinline__ void wgmma_wait() { asm volatile("wgmma.wait_group.sync.aligned %0;" ::"n"(N) : "memory"); }

template <int R>
__device__ __forceinline__ void reg_alloc() { asm volatile("setmaxnreg.inc.sync.aligned.u32 %0;" ::"n"(R)); }
template <int R>
__device__ __forceinline__ void reg_dealloc() { asm volatile("setmaxnreg.dec.sync.aligned.u32 %0;" ::"n"(R)); }

__device__ __forceinline__ uint64_t make_desc(uint32_t saddr, uint32_t lbo_bytes, uint32_t sbo_bytes) {
    uint64_t d = 0;
    d |= (uint64_t)((saddr & 0x3FFFF) >> 4);
    d |= (uint64_t)((lbo_bytes >> 4) & 0x3FFF) << 16;
    d |= (uint64_t)((sbo_bytes >> 4) & 0x3FFF) << 32;
    d |= (uint64_t)1 << 62;
    return d;
}

__device__ __forceinline__ float ex2(float x) {
    float y;
    asm volatile("ex2.approx.ftz.f32 %0, %1;" : "=f"(y) : "f"(x));
    return y;
}
__device__ __forceinline__ uint32_t pack_bf16(float lo, float hi) {
    uint32_t r;
    asm("cvt.rn.bf16x2.f32 %0, %1, %2;" : "=r"(r) : "f"(hi), "f"(lo));
    return r;
}
__device__ __forceinline__ uint32_t mul_bf16x2(uint32_t a, uint32_t b) {
    uint32_t r;
    asm("mul.rn.bf16x2 %0, %1, %2;" : "=r"(r) : "r"(a), "r"(b));
    return r;
}
__device__ __forceinline__ uint32_t fma_bf16x2(uint32_t a, uint32_t b, uint32_t c) {
    uint32_t r;
    asm("fma.rn.bf16x2 %0, %1, %2, %3;" : "=r"(r) : "r"(a), "r"(b), "r"(c));
    return r;
}
__device__ __forceinline__ uint32_t max_bf16x2(uint32_t a, uint32_t b) {
    uint32_t r;
    asm("max.bf16x2 %0, %1, %2;" : "=r"(r) : "r"(a), "r"(b));
    return r;
}
__device__ __forceinline__ float bf16lo(uint32_t v) { return __uint_as_float(v << 16); }
__device__ __forceinline__ float bf16hi(uint32_t v) { return __uint_as_float(v & 0xffff0000u); }
__device__ __forceinline__ float bf16_round(float x) { return __bfloat162float(__float2bfloat16_rn(x)); }
__device__ __forceinline__ float silu_f(float x) {
    const float h = 0.5f * x;
    float t;
    asm("tanh.approx.f32 %0, %1;" : "=f"(t) : "f"(h));
    return fmaf(h, t, h);
}

__device__ __forceinline__ void stmatrix_x4(uint32_t addr, uint32_t r0, uint32_t r1, uint32_t r2, uint32_t r3) {
    asm volatile("stmatrix.sync.aligned.m8n8.x4.shared.b16 [%0], {%1, %2, %3, %4};"
                 ::"r"(addr), "r"(r0), "r"(r1), "r"(r2), "r"(r3)
                 : "memory");
}

#define ACC64(d) \
    "+f"(d[0]), "+f"(d[1]), "+f"(d[2]), "+f"(d[3]), "+f"(d[4]), "+f"(d[5]), "+f"(d[6]), "+f"(d[7]), \
    "+f"(d[8]), "+f"(d[9]), "+f"(d[10]), "+f"(d[11]), "+f"(d[12]), "+f"(d[13]), "+f"(d[14]), "+f"(d[15]), \
    "+f"(d[16]), "+f"(d[17]), "+f"(d[18]), "+f"(d[19]), "+f"(d[20]), "+f"(d[21]), "+f"(d[22]), "+f"(d[23]), \
    "+f"(d[24]), "+f"(d[25]), "+f"(d[26]), "+f"(d[27]), "+f"(d[28]), "+f"(d[29]), "+f"(d[30]), "+f"(d[31]), \
    "+f"(d[32]), "+f"(d[33]), "+f"(d[34]), "+f"(d[35]), "+f"(d[36]), "+f"(d[37]), "+f"(d[38]), "+f"(d[39]), \
    "+f"(d[40]), "+f"(d[41]), "+f"(d[42]), "+f"(d[43]), "+f"(d[44]), "+f"(d[45]), "+f"(d[46]), "+f"(d[47]), \
    "+f"(d[48]), "+f"(d[49]), "+f"(d[50]), "+f"(d[51]), "+f"(d[52]), "+f"(d[53]), "+f"(d[54]), "+f"(d[55]), \
    "+f"(d[56]), "+f"(d[57]), "+f"(d[58]), "+f"(d[59]), "+f"(d[60]), "+f"(d[61]), "+f"(d[62]), "+f"(d[63])

#define ACC64_STR \
    "{%0, %1, %2, %3, %4, %5, %6, %7, %8, %9, %10, %11, %12, %13, %14, %15, " \
    "%16, %17, %18, %19, %20, %21, %22, %23, %24, %25, %26, %27, %28, %29, %30, %31, " \
    "%32, %33, %34, %35, %36, %37, %38, %39, %40, %41, %42, %43, %44, %45, %46, %47, " \
    "%48, %49, %50, %51, %52, %53, %54, %55, %56, %57, %58, %59, %60, %61, %62, %63}"

template <int TB>
__device__ __forceinline__ void wgmma_ss_n128(float (&d)[64], uint64_t da, uint64_t db, int scale_d) {
    asm volatile(
        "{\n.reg .pred p;\nsetp.ne.b32 p, %66, 0;\n"
        "wgmma.mma_async.sync.aligned.m64n128k16.f32.bf16.bf16 " ACC64_STR ", %64, %65, p, 1, 1, 0, %67;\n}\n"
        : ACC64(d)
        : "l"(da), "l"(db), "r"(scale_d), "n"(TB));
}
template <int TB>
__device__ __forceinline__ void wgmma_rs_n128(float (&d)[64], uint32_t a0, uint32_t a1, uint32_t a2, uint32_t a3,
                                              uint64_t db, int scale_d) {
    asm volatile(
        "{\n.reg .pred p;\nsetp.ne.b32 p, %69, 0;\n"
        "wgmma.mma_async.sync.aligned.m64n128k16.f32.bf16.bf16 " ACC64_STR ", {%64, %65, %66, %67}, %68, p, 1, 1, %70;\n}\n"
        : ACC64(d)
        : "r"(a0), "r"(a1), "r"(a2), "r"(a3), "l"(db), "r"(scale_d), "n"(TB));
}

constexpr uint32_t DESC_HI = 0x40000040u;
__device__ __forceinline__ uint32_t desc_lo(uint32_t saddr, uint32_t lbo_bytes) {
    return ((saddr & 0x3FFFF) >> 4) | ((lbo_bytes >> 4) << 16);
}
template <int TB>
__device__ __forceinline__ void wgmma_ss_lo(float (&d)[64], uint32_t da, uint32_t db, int scale_d) {
    asm volatile(
        "{\n.reg .pred p;\n.reg .b64 xa, xb;\nsetp.ne.b32 p, %66, 0;\n"
        "mov.b64 xa, {%64, %68};\nmov.b64 xb, {%65, %68};\n"
        "wgmma.mma_async.sync.aligned.m64n128k16.f32.bf16.bf16 " ACC64_STR ", xa, xb, p, 1, 1, 0, %67;\n}\n"
        : ACC64(d)
        : "r"(da), "r"(db), "r"(scale_d), "n"(TB), "r"(DESC_HI));
}
__device__ __forceinline__ void wgmma_rs_lo_tb(float (&d)[64], uint32_t a0, uint32_t a1, uint32_t a2, uint32_t a3, uint32_t db) {
    asm volatile(
        "{\n.reg .b64 xb;\nmov.b64 xb, {%68, %69};\n"
        "wgmma.mma_async.sync.aligned.m64n128k16.f32.bf16.bf16 " ACC64_STR ", {%64, %65, %66, %67}, xb, 1, 1, 1, 1;\n}\n"
        : ACC64(d)
        : "r"(a0), "r"(a1), "r"(a2), "r"(a3), "r"(db), "r"(DESC_HI));
}

__global__ void __launch_bounds__(256) ln_kernel(const bf16* __restrict__ x) {
    int warp = threadIdx.x >> 5, lane = threadIdx.x & 31;
    int row = blockIdx.x * 8 + warp;
    if (blockIdx.x == 0 && threadIdx.x < SEQ / 128) g_hcnt[threadIdx.x] = 0;
    if (blockIdx.x == 1 && threadIdx.x < SEQ / 128) g_ocnt[threadIdx.x] = 0;
    if (blockIdx.x == 2 && threadIdx.x < 64) g_gcnt[threadIdx.x] = 0;
    const uint4* src = reinterpret_cast<const uint4*>(x + (size_t)row * DM);
    uint4 v[2];
    v[0] = src[lane];
    v[1] = src[lane + 32];
    float f[16];
#pragma unroll
    for (int i = 0; i < 2; i++) {
        const __nv_bfloat162* p = reinterpret_cast<const __nv_bfloat162*>(&v[i]);
#pragma unroll
        for (int j = 0; j < 4; j++) {
            float2 t = __bfloat1622float2(p[j]);
            f[i * 8 + j * 2] = t.x;
            f[i * 8 + j * 2 + 1] = t.y;
        }
    }
    float s = 0.f;
#pragma unroll
    for (int i = 0; i < 16; i++) s += f[i];
#pragma unroll
    for (int o = 16; o > 0; o >>= 1) s += __shfl_xor_sync(0xffffffffu, s, o);
    float mean = s * (1.0f / DM);
    float q = 0.f;
#pragma unroll
    for (int i = 0; i < 16; i++) {
        float d = f[i] - mean;
        q += d * d;
    }
#pragma unroll
    for (int o = 16; o > 0; o >>= 1) q += __shfl_xor_sync(0xffffffffu, q, o);
    float var_b = bf16_round(q * (1.0f / DM));
    float mean_b = bf16_round(mean);
    float den = bf16_round(sqrtf(bf16_round(var_b + 1e-5f)));
    uint4 o[2];
#pragma unroll
    for (int i = 0; i < 2; i++) {
        uint32_t* p = reinterpret_cast<uint32_t*>(&o[i]);
#pragma unroll
        for (int j = 0; j < 4; j++) {
            float a = bf16_round(f[i * 8 + j * 2] - mean_b) / den;
            float b = bf16_round(f[i * 8 + j * 2 + 1] - mean_b) / den;
            p[j] = pack_bf16(a, b);
        }
    }
    uint4* dst = reinterpret_cast<uint4*>(g_xn + ((size_t)(lane >> 4) * SEQ + row) * 128) + (lane & 15);
    dst[0] = o[0];
    dst[2 * SEQ * 16] = o[1];
}

constexpr int AT_STAGES = 3;
constexpr int TILE_BYTES = 128 * 128 * 2;
struct __align__(1024) AttnSmem {
    uint8_t k[AT_STAGES][TILE_BYTES];
    uint8_t v[AT_STAGES][TILE_BYTES];
    uint8_t o[TILE_BYTES];
    uint64_t full_k[AT_STAGES], full_v[AT_STAGES], empty_k[AT_STAGES], empty_v[AT_STAGES];
    uint64_t st_free[2];
};

constexpr int NUM_CTAS = 132;
constexpr int MAX_ITEMS = 14;
enum { T_ATT = 0, T_F1 = 1, T_F2 = 2, T_OP = 3 };
struct Maps {
    CUtensorMap a[4], b[4], st[4];
    CUtensorMap k, v;
};
struct Sched {
    uint16_t item[NUM_CTAS][MAX_ITEMS];
    uint8_t count[NUM_CTAS];
};

__global__ void __launch_bounds__(384, 1)
attn_kernel(const __grid_constant__ Maps tm, const __grid_constant__ Sched sched, const bf16* __restrict__ x) {
    extern __shared__ uint8_t smem_raw[];
    AttnSmem& sm = *reinterpret_cast<AttnSmem*>((reinterpret_cast<uintptr_t>(smem_raw) + 1023) & ~uintptr_t(1023));
    const int tid = threadIdx.x;
    const int wg = __shfl_sync(0xffffffffu, tid >> 7, 0);
    const int n_items = sched.count[blockIdx.x];

    if (tid == 0) {
#pragma unroll
        for (int s = 0; s < AT_STAGES; s++) {
            mbar_init(smem_u32(&sm.full_k[s]), 1);
            mbar_init(smem_u32(&sm.full_v[s]), 1);
            mbar_init(smem_u32(&sm.empty_k[s]), 8);
            mbar_init(smem_u32(&sm.empty_v[s]), 8);
        }
        mbar_init(smem_u32(&sm.st_free[0]), 1);
        mbar_init(smem_u32(&sm.st_free[1]), 1);
        asm volatile("fence.mbarrier_init.release.cluster;" ::: "memory");
    }
    __syncthreads();
    constexpr int BAR_SCHED0 = 1, BAR_EPI0 = 3, BAR_ST0 = 5;

    if (wg == 0) {
        reg_dealloc<24>();
        if (tid >= 32 && tid < 96) {
            const int cw = (tid >> 5) - 1;
            const uint32_t obase = smem_u32(sm.o) + cw * 16384;
            for (int it = 0; it < n_items; it++) {
                const int item = sched.item[blockIdx.x][it];
                const int type = item >> 12, a = (item >> 4) & 0xff, b = item & 15;
                named_sync(BAR_ST0 + cw, 160);
                if ((tid & 31) == 0) {
                    if (type <= T_F1) tma_store_3d(&tm.st[type], obase, 0, a * SEQ + b * 128 + cw * 64, 0);
                    else tma_store_3d(&tm.st[type], obase, 0, b * 128 + cw * 64, a * 2);
                    tma_commit();
                    tma_wait_read0();
                    mbar_arrive(smem_u32(&sm.st_free[cw]));
                    if (type != T_OP) {
                        tma_wait_all0();
                        asm volatile("fence.proxy.async;" ::: "memory");
                        __threadfence();
                        atomicAdd(type == T_F1 ? &g_hcnt[b] : (type == T_ATT ? &g_ocnt[b] : &g_gcnt[b * 4 + a]), 1u);
                    }
                }
                __syncwarp();
            }
            if ((tid & 31) == 0) tma_wait_all0();
        }
        if (tid == 0) {
            int stage = 0;
            uint32_t phase = 0;
            for (int it = 0; it < n_items; it++) {
                const int item = sched.item[blockIdx.x][it];
                const int type = item >> 12, a = (item >> 4) & 0xff, b = item & 15;
                const CUtensorMap* ta = &tm.a[type];
                const CUtensorMap* tb = &tm.b[type];
                const int nch = (type == T_F2) ? FF / 128 : (type == T_OP ? NH * DH / 128 : DM / 128);
                if (type >= T_F2) {
                    const unsigned int* cnt = (type == T_F2) ? &g_hcnt[b] : &g_ocnt[b];
                    const unsigned int need = (type == T_F2) ? 2 * (FF / 128) : 2 * NH;
                    unsigned int v, spins = 0;
                    do {
                        asm volatile("ld.acquire.gpu.global.u32 %0, [%1];" : "=r"(v) : "l"(cnt) : "memory");
                    } while (v < need && ++spins < (1u << 24));
                    asm volatile("fence.proxy.async;" ::: "memory");
                }
                for (int kc = 0; kc < nch; kc++) {
                    if (type == T_OP && kc == nch - 1) {
                        unsigned int v, spins = 0;
                        do {
                            asm volatile("ld.acquire.gpu.global.u32 %0, [%1];" : "=r"(v) : "l"(&g_gcnt[b * 4 + a]) : "memory");
                        } while (v < 2 && ++spins < (1u << 24));
                    }
                    mbar_wait(smem_u32(&sm.empty_k[stage]), phase ^ 1);
                    mbar_expect_tx(smem_u32(&sm.full_k[stage]), TILE_BYTES);
                    tma_load_3d(smem_u32(sm.k[stage]), ta, smem_u32(&sm.full_k[stage]), 0, kc * SEQ + b * 128, 0);
                    mbar_wait(smem_u32(&sm.empty_v[stage]), phase ^ 1);
                    mbar_expect_tx(smem_u32(&sm.full_v[stage]), TILE_BYTES);
                    tma_load_3d(smem_u32(sm.v[stage]), tb, smem_u32(&sm.full_v[stage]), 0, kc * 128, a * 2);
                    if (++stage == AT_STAGES) { stage = 0; phase ^= 1; }
                }
                if (type == T_ATT) {
                    for (int j = 0; j < 16; j++) {
                        mbar_wait(smem_u32(&sm.empty_k[stage]), phase ^ 1);
                        mbar_expect_tx(smem_u32(&sm.full_k[stage]), TILE_BYTES);
                        tma_load_3d(smem_u32(sm.k[stage]), &tm.k, smem_u32(&sm.full_k[stage]), 0, a * SEQ + j * 128, 0);
                        mbar_wait(smem_u32(&sm.empty_v[stage]), phase ^ 1);
                        mbar_expect_tx(smem_u32(&sm.full_v[stage]), TILE_BYTES);
                        tma_load_3d(smem_u32(sm.v[stage]), &tm.v, smem_u32(&sm.full_v[stage]), 0, a * SEQ + j * 128, 0);
                        if (++stage == AT_STAGES) { stage = 0; phase ^= 1; }
                    }
                }
            }
        }
    } else {
        reg_alloc<240>();
        const int cw = wg - 1;
        const int lane = tid & 31;
        const int warp_in_wg = (tid >> 5) & 3;
        const float c = 1.4426950408889634f;
        const uint32_t SCALE_HI2 = 0x3DB53DB5u, SCALE_LO2 = 0x371E371Eu;
        const uint32_t obase = smem_u32(sm.o) + cw * 16384;
        const int st_row = warp_in_wg * 16 + ((lane >> 3) & 1) * 8 + (lane & 7);

        const uint32_t dq = __shfl_sync(0xffffffffu, desc_lo(obase, 16), 0);
        const uint32_t dk0 = __shfl_sync(0xffffffffu, desc_lo(smem_u32(sm.k[0]), 16), 0);
        const uint32_t dv0 = dk0 - (1u << 16) + (1024u << 16) + AT_STAGES * (TILE_BYTES >> 4);

        PP(if (cw == 1) named_arrive(BAR_SCHED0 + 0, 256));

        int stage = 0;
        uint32_t phase = 0;
        float S[64], O[64];
        uint32_t P[32];

        for (int it = 0; it < n_items; it++) {
            const int item = sched.item[blockIdx.x][it];
            const int type = item >> 12;
            const int nch = (type == T_F2) ? FF / 128 : (type == T_OP ? NH * DH / 128 : DM / 128);
            {
                int prev = -1;
#pragma unroll 1
                for (int kc = 0; kc < nch; kc++) {
                    mbar_wait(smem_u32(&sm.full_k[stage]), phase);
                    mbar_wait(smem_u32(&sm.full_v[stage]), phase);
                    const uint64_t da = make_desc(smem_u32(sm.k[stage]) + cw * 64 * 128, 16, 1024);
                    const uint64_t db = make_desc(smem_u32(sm.v[stage]), 16384, 1024);
                    wgmma_fence();
#pragma unroll
                    for (int kk = 0; kk < 8; kk++) {
                        wgmma_ss_n128<1>(S, da + (uint64_t)(((kk >> 2) * 16384 + (kk & 3) * 32) >> 4),
                                         db + (uint64_t)((kk * 2048) >> 4), (kc | kk) != 0);
                    }
                    wgmma_commit();
                    wgmma_wait<1>();
                    if (prev >= 0 && lane == 0) {
                        mbar_arrive(smem_u32(&sm.empty_k[prev]));
                        mbar_arrive(smem_u32(&sm.empty_v[prev]));
                    }
                    prev = stage;
                    if (++stage == AT_STAGES) { stage = 0; phase ^= 1; }
                }
                if (type == T_OP) {
                    const size_t off0 = (size_t)((item & 15) * 128 + cw * 64 + warp_in_wg * 16 + (lane >> 2)) * DM +
                                        ((item >> 4) & 0xff) * 128 + (lane & 3) * 2;
#pragma unroll
                    for (int i = 0; i < 16; i++) {
#pragma unroll
                        for (int hh = 0; hh < 2; hh++) {
                            const size_t off = off0 + (size_t)hh * 8 * DM + i * 8;
                            O[4 * i + 2 * hh] = __uint_as_float(__ldg(reinterpret_cast<const uint32_t*>(x + off)));
                            O[4 * i + 2 * hh + 1] = __uint_as_float(__ldcg(reinterpret_cast<const uint32_t*>(g_g + off)));
                        }
                    }
                }
                wgmma_wait<0>();
                if (lane == 0) {
                    mbar_arrive(smem_u32(&sm.empty_k[prev]));
                    mbar_arrive(smem_u32(&sm.empty_v[prev]));
                }
            }
            if (type == T_OP) {
#pragma unroll
                for (int i = 0; i < 32; i++) {
                    const uint32_t xv = __float_as_uint(O[2 * i]), gv = __float_as_uint(O[2 * i + 1]);
                    S[2 * i] = bf16lo(xv) + bf16_round(bf16_round(S[2 * i]) * bf16lo(gv));
                    S[2 * i + 1] = bf16hi(xv) + bf16_round(bf16_round(S[2 * i + 1]) * bf16hi(gv));
                }
            } else if (type != T_ATT) {
#pragma unroll
                for (int i = 0; i < 64; i++) S[i] = silu_f(bf16_round(S[i]));
            }
            mbar_wait(smem_u32(&sm.st_free[cw]), (it & 1) ^ 1);
#pragma unroll
            for (int i = 0; i < 16; i += 2) {
                const int cc = i + (lane >> 4);
                const uint32_t addr = obase + (cc >> 3) * 8192 + st_row * 128 + (((cc & 7) ^ (st_row & 7)) << 4);
                stmatrix_x4(addr, pack_bf16(S[4 * i], S[4 * i + 1]), pack_bf16(S[4 * i + 2], S[4 * i + 3]),
                            pack_bf16(S[4 * i + 4], S[4 * i + 5]), pack_bf16(S[4 * i + 6], S[4 * i + 7]));
            }
            fence_proxy_async();
            if (type != T_ATT) {
                named_arrive(BAR_ST0 + cw, 160);
                continue;
            }
            named_sync(BAR_EPI0 + cw, 128);
#pragma unroll
            for (int i = 0; i < 64; i++) O[i] = 0.f;

            float m0 = -INFINITY, m1 = -INFINITY, l0 = 0.f, l1 = 0.f, a0 = 0.f, a1 = 0.f;
            bool resc = false;
            const float TAU = 11.0f;
            const uint32_t fk0 = smem_u32(&sm.full_k[0]), fv0 = smem_u32(&sm.full_v[0]);
            const uint32_t ek0 = smem_u32(&sm.empty_k[0]), ev0 = smem_u32(&sm.empty_v[0]);

            uint32_t T[32];
            float n0, n1;
            auto softmax1 = [&]() {
#pragma unroll
                for (int i = 0; i < 32; i++) {
                    const uint32_t sb = pack_bf16(S[2 * i], S[2 * i + 1]);
                    T[i] = fma_bf16x2(sb, SCALE_HI2, mul_bf16x2(sb, SCALE_LO2));
                }
                uint32_t y0 = max_bf16x2(T[0], T[2]), y1 = max_bf16x2(T[1], T[3]);
#pragma unroll
                for (int i = 2; i < 16; i++) {
                    y0 = max_bf16x2(y0, T[2 * i]);
                    y1 = max_bf16x2(y1, T[2 * i + 1]);
                }
                float x0 = fmaxf(bf16lo(y0), bf16hi(y0));
                float x1 = fmaxf(bf16lo(y1), bf16hi(y1));
                x0 = fmaxf(x0, __shfl_xor_sync(0xffffffffu, x0, 1));
                x1 = fmaxf(x1, __shfl_xor_sync(0xffffffffu, x1, 1));
                x0 = fmaxf(x0, __shfl_xor_sync(0xffffffffu, x0, 2));
                x1 = fmaxf(x1, __shfl_xor_sync(0xffffffffu, x1, 2));
                resc = __any_sync(0xffffffffu, (x0 - m0 > TAU) || (x1 - m1 > TAU));
                x0 = resc ? fmaxf(x0, m0) : m0;
                x1 = resc ? fmaxf(x1, m1) : m1;
                a0 = ex2((m0 - x0) * c);
                a1 = ex2((m1 - x1) * c);
                m0 = x0;
                m1 = x1;
                n0 = -m0 * c;
                n1 = -m1 * c;
                while (n0 != n0) n0 = g_dummy;
            };
            auto softmax2 = [&]() {
                float s0 = 0.f, s1 = 0.f;
#pragma unroll
                for (int i = 0; i < 16; i++) {
                    const float e0 = ex2(fmaf(bf16lo(T[2 * i]), c, n0));
                    const float e1 = ex2(fmaf(bf16hi(T[2 * i]), c, n0));
                    const float e2 = ex2(fmaf(bf16lo(T[2 * i + 1]), c, n1));
                    const float e3 = ex2(fmaf(bf16hi(T[2 * i + 1]), c, n1));
                    s0 += e0 + e1;
                    s1 += e2 + e3;
                    P[2 * i] = pack_bf16(e0, e1);
                    P[2 * i + 1] = pack_bf16(e2, e3);
                }
                l0 = l0 * a0 + s0;
                l1 = l1 * a1 + s1;
            };
            auto issue_qk = [&](uint32_t dk) {
                wgmma_fence();
#pragma unroll
                for (int kk = 0; kk < 8; kk++)
                    wgmma_ss_lo<0>(S, dq + (((kk >> 2) * 8192 + (kk & 3) * 32) >> 4),
                                   dk + (((kk >> 2) * 16384 + (kk & 3) * 32) >> 4), kk != 0);
                wgmma_commit();
            };
            auto issue_pv = [&](uint32_t dv) {
                if (resc) {
#pragma unroll
                    for (int i = 0; i < 16; i++) {
                        O[4 * i] *= a0;
                        O[4 * i + 1] *= a0;
                        O[4 * i + 2] *= a1;
                        O[4 * i + 3] *= a1;
                    }
                }
                wgmma_fence();
#pragma unroll
                for (int kk = 0; kk < 8; kk++)
                    wgmma_rs_lo_tb(O, P[4 * kk], P[4 * kk + 1], P[4 * kk + 2], P[4 * kk + 3], dv + ((kk * 2048) >> 4));
                wgmma_commit();
            };

            int vstage = stage;
            uint32_t vphase = phase;
            bool okk, okv;
            {
                mbar_wait(fk0 + stage * 8, phase);
                PP(named_sync(BAR_SCHED0 + cw, 256));
                issue_qk(dk0 + stage * (TILE_BYTES >> 4));
                PP(named_arrive(BAR_SCHED0 + (cw ^ 1), 256));
                if (++stage == AT_STAGES) { stage = 0; phase ^= 1; }
                okk = mbar_try_wait(fk0 + stage * 8, phase);
                okv = mbar_try_wait(fv0 + vstage * 8, vphase);
                wgmma_wait<0>();
                if (lane == 0) mbar_arrive(ek0 + vstage * 8);
            }
            softmax1();
            softmax2();
            resc = false;

#pragma unroll 1
            for (int j = 1; j < 16; j++) {
                const int ust = __shfl_sync(0xffffffffu, stage, 0), uvs = __shfl_sync(0xffffffffu, vstage, 0);
                if (!okk) mbar_wait(fk0 + stage * 8, phase);
                if (!okv) mbar_wait(fv0 + vstage * 8, vphase);
                PP(named_sync(BAR_SCHED0 + cw, 256));
                issue_qk(dk0 + ust * (TILE_BYTES >> 4));
                issue_pv(dv0 + uvs * (TILE_BYTES >> 4));
                PP(named_arrive(BAR_SCHED0 + (cw ^ 1), 256));
                const int pv = vstage;
                vstage = stage;
                vphase = phase;
                if (++stage == AT_STAGES) { stage = 0; phase ^= 1; }
                okk = mbar_try_wait(fk0 + stage * 8, phase);
                okv = mbar_try_wait(fv0 + vstage * 8, vphase);
                wgmma_wait<1>();
                if (lane == 0) mbar_arrive(ek0 + vstage * 8);
                softmax1();
                wgmma_wait<0>();
                if (lane == 0) mbar_arrive(ev0 + pv * 8);
                softmax2();
            }
            if (!okv) mbar_wait(fv0 + vstage * 8, vphase);
            issue_pv(dv0 + vstage * (TILE_BYTES >> 4));
            wgmma_wait<0>();
            if (lane == 0) mbar_arrive(ev0 + vstage * 8);
            l0 += __shfl_xor_sync(0xffffffffu, l0, 1);
            l1 += __shfl_xor_sync(0xffffffffu, l1, 1);
            l0 += __shfl_xor_sync(0xffffffffu, l0, 2);
            l1 += __shfl_xor_sync(0xffffffffu, l1, 2);
            const float i0 = 1.0f / l0, i1 = 1.0f / l1;
            named_sync(BAR_EPI0 + cw, 128);
#pragma unroll
            for (int i = 0; i < 16; i += 2) {
                const int cc = i + (lane >> 4);
                const uint32_t addr = obase + (cc >> 3) * 8192 + st_row * 128 + (((cc & 7) ^ (st_row & 7)) << 4);
                stmatrix_x4(addr, pack_bf16(O[4 * i] * i0, O[4 * i + 1] * i0), pack_bf16(O[4 * i + 2] * i1, O[4 * i + 3] * i1),
                            pack_bf16(O[4 * i + 4] * i0, O[4 * i + 5] * i0), pack_bf16(O[4 * i + 6] * i1, O[4 * i + 7] * i1));
            }
            fence_proxy_async();
            named_arrive(BAR_ST0 + cw, 160);
        }
    }
}

typedef CUresult (*EncodeFn)(CUtensorMap*, CUtensorMapDataType, cuuint32_t, void*, const cuuint64_t*, const cuuint64_t*,
                             const cuuint32_t*, const cuuint32_t*, CUtensorMapInterleave, CUtensorMapSwizzle,
                             CUtensorMapL2promotion, CUtensorMapFloatOOBfill);

static CUtensorMap make_map(EncodeFn fn, const void* ptr, uint64_t rows, uint64_t cols, uint32_t box_rows, uint32_t box_blk) {
    CUtensorMap m;
    cuuint64_t dims[3] = {64, rows, cols / 64};
    cuuint64_t strides[2] = {cols * 2, 128};
    cuuint32_t box[3] = {64, box_rows, box_blk};
    cuuint32_t es[3] = {1, 1, 1};
    fn(&m, CU_TENSOR_MAP_DATA_TYPE_BFLOAT16, 3, const_cast<void*>(ptr), dims, strides, box, es, CU_TENSOR_MAP_INTERLEAVE_NONE,
       CU_TENSOR_MAP_SWIZZLE_128B, CU_TENSOR_MAP_L2_PROMOTION_L2_256B, CU_TENSOR_MAP_FLOAT_OOB_FILL_NONE);
    return m;
}

extern "C" void kernel_launch(void* const* d_in, const int* in_sizes, int n_in, void* d_out, int out_size) {
    const bf16* x = (const bf16*)d_in[0];
    const bf16* kc = (const bf16*)d_in[1];
    const bf16* vc = (const bf16*)d_in[2];
    const bf16* wq = (const bf16*)d_in[3];
    const bf16* wo = (const bf16*)d_in[4];
    const bf16* w1 = (const bf16*)d_in[6];
    const bf16* w2 = (const bf16*)d_in[7];
    bf16* out = (bf16*)d_out;

    static EncodeFn fn = nullptr;
    static void *p_xn = nullptr, *p_h = nullptr, *p_o = nullptr, *p_g = nullptr;
    static Sched sched;
    if (!fn) {
        void* f = nullptr;
        cudaDriverEntryPointQueryResult st;
        cudaGetDriverEntryPoint("cuTensorMapEncodeTiled", &f, cudaEnableDefault, &st);
        fn = (EncodeFn)f;
        cudaGetSymbolAddress(&p_xn, g_xn);
        cudaGetSymbolAddress(&p_h, g_h);
        cudaGetSymbolAddress(&p_o, g_o);
        cudaGetSymbolAddress(&p_g, g_g);
        cudaFuncSetAttribute(attn_kernel, cudaFuncAttributeMaxDynamicSharedMemorySize, (int)sizeof(AttnSmem) + 1024);
        const double C_ATT = 54.3, C_F1 = 7.0, C_F2 = 19.8, C_OP = 40.0;
        static double fr[NUM_CTAS], odone[16], hdone[16];
        for (int i = 0; i < NUM_CTAS; i++) { fr[i] = 2.5; sched.count[i] = 0; }
        for (int i = 0; i < 16; i++) odone[i] = hdone[i] = 0;
        auto push = [&](int cta, int type, int a, int b) { sched.item[cta][sched.count[cta]++] = (uint16_t)((type << 12) | (a << 4) | b); };
        double t_att = 0;
        for (int t = 0; t < NH * 16; t++) {
            const int cta = t % NUM_CTAS;
            push(cta, T_ATT, t >> 4, t & 15);
            fr[cta] += C_ATT;
            if (fr[cta] > odone[t & 15]) odone[t & 15] = fr[cta];
            if (fr[cta] > t_att) t_att = fr[cta];
        }
        int n1 = 0, n2 = 0, n3 = 0;
        while (n1 < 224 || n2 < 64 || n3 < 64) {
            int cta = 0;
            for (int i = 1; i < NUM_CTAS; i++) if (fr[i] < fr[cta]) cta = i;
            const double t = fr[cta];
            if (n1 < 224 && (t + C_F1 <= t_att + 1.0 || n3 == 64)) {
                const int b = n1 / 14;
                push(cta, T_F1, n1 % 14, b);
                fr[cta] = t + C_F1;
                if (fr[cta] > hdone[b]) hdone[b] = fr[cta];
                n1++;
            } else if (n3 < 64) {
                const int b = n3 >> 2;
                push(cta, T_OP, n3 & 3, b);
                fr[cta] = (t > odone[b] ? t : odone[b]) + C_OP;
                n3++;
            } else {
                const int b = n2 >> 2;
                push(cta, T_F2, n2 & 3, b);
                fr[cta] = (t > hdone[b] ? t : hdone[b]) + C_F2;
                n2++;
            }
        }
    }
    Maps tm;
    tm.a[T_ATT] = tm.a[T_F1] = make_map(fn, p_xn, (DM / 128) * SEQ, 128, 128, 2);
    tm.a[T_F2] = make_map(fn, p_h, (FF / 128) * SEQ, 128, 128, 2);
    tm.a[T_OP] = make_map(fn, p_o, NH * SEQ, 128, 128, 2);
    tm.b[T_ATT] = make_map(fn, wq, DM, NH * DH, 128, 2);
    tm.b[T_F1] = make_map(fn, w1, DM, FF, 128, 2);
    tm.b[T_F2] = make_map(fn, w2, FF, DM, 128, 2);
    tm.b[T_OP] = make_map(fn, wo, NH * DH, DM, 128, 2);
    tm.st[T_ATT] = make_map(fn, p_o, NH * SEQ, 128, 64, 2);
    tm.st[T_F1] = make_map(fn, p_h, (FF / 128) * SEQ, 128, 64, 2);
    tm.st[T_F2] = make_map(fn, p_g, SEQ, DM, 64, 2);
    tm.st[T_OP] = make_map(fn, out, SEQ, DM, 64, 2);
    tm.k = make_map(fn, kc, NH * SEQ, DH, 128, 2);
    tm.v = make_map(fn, vc, NH * SEQ, DH, 128, 2);

    ln_kernel<<<SEQ / 8, 256>>>(x);
    attn_kernel<<<NUM_CTAS, 384, sizeof(AttnSmem) + 1024>>>(tm, sched, x);
}
```

```cpp
#include <cuda_runtime.h>
#include <cuda_bf16.h>
#include <cuda.h>
#include <stdint.h>

typedef __nv_bfloat16 bf16;
#define PP(x) x

constexpr int SEQ = 2048, DM = 512, NH = 32, DH = 128, FF = 1792;

__device__ __align__(1024) bf16 g_xn[SEQ * DM];
__device__ __align__(1024) bf16 g_h[SEQ * FF];
__device__ __align__(1024) bf16 g_o[SEQ * NH * DH];
__device__ __align__(1024) bf16 g_g[SEQ * DM];
__device__ unsigned int g_hcnt[SEQ / 128];
__device__ unsigned int g_ocnt[SEQ / 128];
__device__ unsigned int g_gcnt[64];
__device__ float4 g_part[64 * 2 * 16 * 128];
__device__ unsigned int g_tcnt[64 * 8];
__device__ volatile float g_dummy;

__device__ __forceinline__ uint32_t smem_u32(const void* p) { return (uint32_t)__cvta_generic_to_shared(p); }

__device__ __forceinline__ void mbar_init(uint32_t bar, uint32_t count) {
    asm volatile("mbarrier.init.shared::cta.b64 [%0], %1;" ::"r"(bar), "r"(count) : "memory");
}
__device__ __forceinline__ void mbar_expect_tx(uint32_t bar, uint32_t bytes) {
    asm volatile("mbarrier.arrive.expect_tx.shared::cta.b64 _, [%0], %1;" ::"r"(bar), "r"(bytes) : "memory");
}
__device__ __forceinline__ void mbar_arrive(uint32_t bar) {
    asm volatile("mbarrier.arrive.shared::cta.b64 _, [%0];" ::"r"(bar) : "memory");
}
__device__ __forceinline__ bool mbar_try_wait(uint32_t bar, uint32_t parity) {
    uint32_t ok;
    asm volatile(
        "{\n.reg .pred p;\n"
        "mbarrier.test_wait.parity.shared::cta.b64 p, [%1], %2;\n"
        "selp.u32 %0, 1, 0, p;\n}\n"
        : "=r"(ok)
        : "r"(bar), "r"(parity)
        : "memory");
    return ok != 0;
}
__device__ __forceinline__ void mbar_wait(uint32_t bar, uint32_t parity) {
    asm volatile(
        "{\n.reg .pred P1;\n.reg .u32 n;\nmov.u32 n, 0;\n"
        "LAB_WAIT:\n"
        "mbarrier.try_wait.parity.shared::cta.b64 P1, [%0], %1;\n"
        "@P1 bra DONE;\n"
        "add.u32 n, n, 1;\n"
        "setp.lt.u32 P1, n, 4194304;\n"
        "@P1 bra LAB_WAIT;\n"
        "trap;\n"
        "DONE:\n}\n" ::"r"(bar), "r"(parity)
        : "memory");
}
__device__ __forceinline__ void tma_load_3d(uint32_t dst, const CUtensorMap* map, uint32_t bar, int c0, int c1, int c2) {
    asm volatile(
        "cp.async.bulk.tensor.3d.shared::cluster.global.mbarrier::complete_tx::bytes [%0], [%1, {%3, %4, %5}], [%2];"
        ::"r"(dst), "l"((uint64_t)map), "r"(bar), "r"(c0), "r"(c1), "r"(c2)
        : "memory");
}
__device__ __forceinline__ void tma_store_3d(const CUtensorMap* map, uint32_t src, int c0, int c1, int c2) {
    asm volatile("cp.async.bulk.tensor.3d.global.shared::cta.bulk_group [%0, {%2, %3, %4}], [%1];"
                 ::"l"((uint64_t)map), "r"(src), "r"(c0), "r"(c1), "r"(c2)
                 : "memory");
}
__device__ __forceinline__ void tma_commit() { asm volatile("cp.async.bulk.commit_group;" ::: "memory"); }
__device__ __forceinline__ void tma_wait_read0() { asm volatile("cp.async.bulk.wait_group.read 0;" ::: "memory"); }
__device__ __forceinline__ void tma_wait_all0() { asm volatile("cp.async.bulk.wait_group 0;" ::: "memory"); }
__device__ __forceinline__ void fence_proxy_async() { asm volatile("fence.proxy.async.shared::cta;" ::: "memory"); }
__device__ __forceinline__ void prefetch_tmap(const CUtensorMap* map) {
    asm volatile("prefetch.tensormap [%0];" ::"l"((uint64_t)map) : "memory");
}
__device__ __forceinline__ void named_sync(int id, int n) { asm volatile("bar.sync %0, %1;" ::"r"(id), "r"(n) : "memory"); }
__device__ __forceinline__ void named_arrive(int id, int n) { asm volatile("bar.arrive %0, %1;" ::"r"(id), "r"(n) : "memory"); }

__device__ __forceinline__ void wgmma_fence() { asm volatile("wgmma.fence.sync.aligned;" ::: "memory"); }
__device__ __forceinline__ void wgmma_commit() { asm volatile("wgmma.commit_group.sync.aligned;" ::: "memory"); }
template <int N>
__device__ __forceinline__ void wgmma_wait() { asm volatile("wgmma.wait_group.sync.aligned %0;" ::"n"(N) : "memory"); }

template <int R>
__device__ __forceinline__ void reg_alloc() { asm volatile("setmaxnreg.inc.sync.aligned.u32 %0;" ::"n"(R)); }
template <int R>
__device__ __forceinline__ void reg_dealloc() { asm volatile("setmaxnreg.dec.sync.aligned.u32 %0;" ::"n"(R)); }

__device__ __forceinline__ uint64_t make_desc(uint32_t saddr, uint32_t lbo_bytes, uint32_t sbo_bytes) {
    uint64_t d = 0;
    d |= (uint64_t)((saddr & 0x3FFFF) >> 4);
    d |= (uint64_t)((lbo_bytes >> 4) & 0x3FFF) << 16;
    d |= (uint64_t)((sbo_bytes >> 4) & 0x3FFF) << 32;
    d |= (uint64_t)1 << 62;
    return d;
}

__device__ __forceinline__ float ex2(float x) {
    float y;
    asm volatile("ex2.approx.ftz.f32 %0, %1;" : "=f"(y) : "f"(x));
    return y;
}
__device__ __forceinline__ uint32_t pack_bf16(float lo, float hi) {
    uint32_t r;
    asm("cvt.rn.bf16x2.f32 %0, %1, %2;" : "=r"(r) : "f"(hi), "f"(lo));
    return r;
}
__device__ __forceinline__ uint32_t mul_bf16x2(uint32_t a, uint32_t b) {
    uint32_t r;
    asm("mul.rn.bf16x2 %0, %1, %2;" : "=r"(r) : "r"(a), "r"(b));
    return r;
}
__device__ __forceinline__ uint32_t fma_bf16x2(uint32_t a, uint32_t b, uint32_t c) {
    uint32_t r;
    asm("fma.rn.bf16x2 %0, %1, %2, %3;" : "=r"(r) : "r"(a), "r"(b), "r"(c));
    return r;
}
__device__ __forceinline__ uint32_t max_bf16x2(uint32_t a, uint32_t b) {
    uint32_t r;
    asm("max.bf16x2 %0, %1, %2;" : "=r"(r) : "r"(a), "r"(b));
    return r;
}
__device__ __forceinline__ float bf16lo(uint32_t v) { return __uint_as_float(v << 16); }
__device__ __forceinline__ float bf16hi(uint32_t v) { return __uint_as_float(v & 0xffff0000u); }
__device__ __forceinline__ float bf16_round(float x) { return __bfloat162float(__float2bfloat16_rn(x)); }
__device__ __forceinline__ float silu_f(float x) {
    const float h = 0.5f * x;
    float t;
    asm("tanh.approx.f32 %0, %1;" : "=f"(t) : "f"(h));
    return fmaf(h, t, h);
}

__device__ __forceinline__ void stmatrix_x4(uint32_t addr, uint32_t r0, uint32_t r1, uint32_t r2, uint32_t r3) {
    asm volatile("stmatrix.sync.aligned.m8n8.x4.shared.b16 [%0], {%1, %2, %3, %4};"
                 ::"r"(addr), "r"(r0), "r"(r1), "r"(r2), "r"(r3)
                 : "memory");
}

#define ACC64(d) \
    "+f"(d[0]), "+f"(d[1]), "+f"(d[2]), "+f"(d[3]), "+f"(d[4]), "+f"(d[5]), "+f"(d[6]), "+f"(d[7]), \
    "+f"(d[8]), "+f"(d[9]), "+f"(d[10]), "+f"(d[11]), "+f"(d[12]), "+f"(d[13]), "+f"(d[14]), "+f"(d[15]), \
    "+f"(d[16]), "+f"(d[17]), "+f"(d[18]), "+f"(d[19]), "+f"(d[20]), "+f"(d[21]), "+f"(d[22]), "+f"(d[23]), \
    "+f"(d[24]), "+f"(d[25]), "+f"(d[26]), "+f"(d[27]), "+f"(d[28]), "+f"(d[29]), "+f"(d[30]), "+f"(d[31]), \
    "+f"(d[32]), "+f"(d[33]), "+f"(d[34]), "+f"(d[35]), "+f"(d[36]), "+f"(d[37]), "+f"(d[38]), "+f"(d[39]), \
    "+f"(d[40]), "+f"(d[41]), "+f"(d[42]), "+f"(d[43]), "+f"(d[44]), "+f"(d[45]), "+f"(d[46]), "+f"(d[47]), \
    "+f"(d[48]), "+f"(d[49]), "+f"(d[50]), "+f"(d[51]), "+f"(d[52]), "+f"(d[53]), "+f"(d[54]), "+f"(d[55]), \
    "+f"(d[56]), "+f"(d[57]), "+f"(d[58]), "+f"(d[59]), "+f"(d[60]), "+f"(d[61]), "+f"(d[62]), "+f"(d[63])

#define ACC64_STR \
    "{%0, %1, %2, %3, %4, %5, %6, %7, %8, %9, %10, %11, %12, %13, %14, %15, " \
    "%16, %17, %18, %19, %20, %21, %22, %23, %24, %25, %26, %27, %28, %29, %30, %31, " \
    "%32, %33, %34, %35, %36, %37, %38, %39, %40, %41, %42, %43, %44, %45, %46, %47, " \
    "%48, %49, %50, %51, %52, %53, %54, %55, %56, %57, %58, %59, %60, %61, %62, %63}"

template <int TB>
__device__ __forceinline__ void wgmma_ss_n128(float (&d)[64], uint64_t da, uint64_t db, int scale_d) {
    asm volatile(
        "{\n.reg .pred p;\nsetp.ne.b32 p, %66, 0;\n"
        "wgmma.mma_async.sync.aligned.m64n128k16.f32.bf16.bf16 " ACC64_STR ", %64, %65, p, 1, 1, 0, %67;\n}\n"
        : ACC64(d)
        : "l"(da), "l"(db), "r"(scale_d), "n"(TB));
}
template <int TB>
__device__ __forceinline__ void wgmma_rs_n128(float (&d)[64], uint32_t a0, uint32_t a1, uint32_t a2, uint32_t a3,
                                              uint64_t db, int scale_d) {
    asm volatile(
        "{\n.reg .pred p;\nsetp.ne.b32 p, %69, 0;\n"
        "wgmma.mma_async.sync.aligned.m64n128k16.f32.bf16.bf16 " ACC64_STR ", {%64, %65, %66, %67}, %68, p, 1, 1, %70;\n}\n"
        : ACC64(d)
        : "r"(a0), "r"(a1), "r"(a2), "r"(a3), "l"(db), "r"(scale_d), "n"(TB));
}

constexpr uint32_t DESC_HI = 0x40000040u;
__device__ __forceinline__ uint32_t desc_lo(uint32_t saddr, uint32_t lbo_bytes) {
    return ((saddr & 0x3FFFF) >> 4) | ((lbo_bytes >> 4) << 16);
}
template <int TB>
__device__ __forceinline__ void wgmma_ss_lo(float (&d)[64], uint32_t da, uint32_t db, int scale_d) {
    asm volatile(
        "{\n.reg .pred p;\n.reg .b64 xa, xb;\nsetp.ne.b32 p, %66, 0;\n"
        "mov.b64 xa, {%64, %68};\nmov.b64 xb, {%65, %68};\n"
        "wgmma.mma_async.sync.aligned.m64n128k16.f32.bf16.bf16 " ACC64_STR ", xa, xb, p, 1, 1, 0, %67;\n}\n"
        : ACC64(d)
        : "r"(da), "r"(db), "r"(scale_d), "n"(TB), "r"(DESC_HI));
}
__device__ __forceinline__ void wgmma_rs_lo_tb(float (&d)[64], uint32_t a0, uint32_t a1, uint32_t a2, uint32_t a3, uint32_t db) {
    asm volatile(
        "{\n.reg .b64 xb;\nmov.b64 xb, {%68, %69};\n"
        "wgmma.mma_async.sync.aligned.m64n128k16.f32.bf16.bf16 " ACC64_STR ", {%64, %65, %66, %67}, xb, 1, 1, 1, 1;\n}\n"
        : ACC64(d)
        : "r"(a0), "r"(a1), "r"(a2), "r"(a3), "r"(db), "r"(DESC_HI));
}

__global__ void __launch_bounds__(256) ln_kernel(const bf16* __restrict__ x) {
    int warp = threadIdx.x >> 5, lane = threadIdx.x & 31;
    int row = blockIdx.x * 8 + warp;
    if (blockIdx.x == 0 && threadIdx.x < SEQ / 128) g_hcnt[threadIdx.x] = 0;
    if (blockIdx.x == 1 && threadIdx.x < SEQ / 128) g_ocnt[threadIdx.x] = 0;
    if (blockIdx.x == 2 && threadIdx.x < 64) g_gcnt[threadIdx.x] = 0;
    if (blockIdx.x == 3 || blockIdx.x == 4) g_tcnt[(blockIdx.x - 3) * 256 + threadIdx.x] = 0;
    const uint4* src = reinterpret_cast<const uint4*>(x + (size_t)row * DM);
    uint4 v[2];
    v[0] = src[lane];
    v[1] = src[lane + 32];
    float f[16];
#pragma unroll
    for (int i = 0; i < 2; i++) {
        const __nv_bfloat162* p = reinterpret_cast<const __nv_bfloat162*>(&v[i]);
#pragma unroll
        for (int j = 0; j < 4; j++) {
            float2 t = __bfloat1622float2(p[j]);
            f[i * 8 + j * 2] = t.x;
            f[i * 8 + j * 2 + 1] = t.y;
        }
    }
    float s = 0.f;
#pragma unroll
    for (int i = 0; i < 16; i++) s += f[i];
#pragma unroll
    for (int o = 16; o > 0; o >>= 1) s += __shfl_xor_sync(0xffffffffu, s, o);
    float mean = s * (1.0f / DM);
    float q = 0.f;
#pragma unroll
    for (int i = 0; i < 16; i++) {
        float d = f[i] - mean;
        q += d * d;
    }
#pragma unroll
    for (int o = 16; o > 0; o >>= 1) q += __shfl_xor_sync(0xffffffffu, q, o);
    float var_b = bf16_round(q * (1.0f / DM));
    float mean_b = bf16_round(mean);
    float den = bf16_round(sqrtf(bf16_round(var_b + 1e-5f)));
    uint4 o[2];
#pragma unroll
    for (int i = 0; i < 2; i++) {
        uint32_t* p = reinterpret_cast<uint32_t*>(&o[i]);
#pragma unroll
        for (int j = 0; j < 4; j++) {
            float a = bf16_round(f[i * 8 + j * 2] - mean_b) / den;
            float b = bf16_round(f[i * 8 + j * 2 + 1] - mean_b) / den;
            p[j] = pack_bf16(a, b);
        }
    }
    uint4* dst = reinterpret_cast<uint4*>(g_xn + ((size_t)(lane >> 4) * SEQ + row) * 128) + (lane & 15);
    dst[0] = o[0];
    dst[2 * SEQ * 16] = o[1];
}

constexpr int AT_STAGES = 3;
constexpr int TILE_BYTES = 128 * 128 * 2;
struct __align__(1024) AttnSmem {
    uint8_t k[AT_STAGES][TILE_BYTES];
    uint8_t v[AT_STAGES][TILE_BYTES];
    uint8_t o[TILE_BYTES];
    uint64_t full_k[AT_STAGES], full_v[AT_STAGES], empty_k[AT_STAGES], empty_v[AT_STAGES];
    uint64_t st_free[2];
};

constexpr int NUM_CTAS = 132;
constexpr int MAX_ITEMS = 14;
enum { T_ATT = 0, T_F1 = 1, T_F2 = 2, T_OP = 3 };
struct Maps {
    CUtensorMap a[4], b[4], st[4];
    CUtensorMap k, v;
};
struct Sched {
    uint16_t item[NUM_CTAS][MAX_ITEMS];
    uint8_t count[NUM_CTAS];
};

__global__ void __launch_bounds__(384, 1)
attn_kernel(const __grid_constant__ Maps tm, const __grid_constant__ Sched sched, const bf16* __restrict__ x,
            bf16* __restrict__ out) {
    extern __shared__ uint8_t smem_raw[];
    AttnSmem& sm = *reinterpret_cast<AttnSmem*>((reinterpret_cast<uintptr_t>(smem_raw) + 1023) & ~uintptr_t(1023));
    const int tid = threadIdx.x;
    const int wg = __shfl_sync(0xffffffffu, tid >> 7, 0);
    const int n_items = sched.count[blockIdx.x];

    if (tid == 0) {
#pragma unroll
        for (int s = 0; s < AT_STAGES; s++) {
            mbar_init(smem_u32(&sm.full_k[s]), 1);
            mbar_init(smem_u32(&sm.full_v[s]), 1);
            mbar_init(smem_u32(&sm.empty_k[s]), 8);
            mbar_init(smem_u32(&sm.empty_v[s]), 8);
        }
        mbar_init(smem_u32(&sm.st_free[0]), 1);
        mbar_init(smem_u32(&sm.st_free[1]), 1);
        asm volatile("fence.mbarrier_init.release.cluster;" ::: "memory");
    }
    __syncthreads();
    constexpr int BAR_SCHED0 = 1, BAR_EPI0 = 3, BAR_ST0 = 5;

    if (wg == 0) {
        reg_dealloc<24>();
        if (tid >= 32 && tid < 96) {
            const int cw = (tid >> 5) - 1;
            const uint32_t obase = smem_u32(sm.o) + cw * 16384;
            for (int it = 0; it < n_items; it++) {
                const int item = sched.item[blockIdx.x][it];
                const int type = item >> 12, a = (item >> 4) & 0xff, b = item & 15;
                if (type == T_OP && a >= 32) continue;
                named_sync(BAR_ST0 + cw, 160);
                if ((tid & 31) == 0) {
                    if (type <= T_F1) tma_store_3d(&tm.st[type], obase, 0, a * SEQ + b * 128 + cw * 64, 0);
                    else tma_store_3d(&tm.st[type], obase, 0, b * 128 + cw * 64, a * 2);
                    tma_commit();
                    tma_wait_read0();
                    mbar_arrive(smem_u32(&sm.st_free[cw]));
                    if (type != T_OP) {
                        tma_wait_all0();
                        asm volatile("fence.proxy.async;" ::: "memory");
                        __threadfence();
                        atomicAdd(type == T_F1 ? &g_hcnt[b] : (type == T_ATT ? &g_ocnt[b] : &g_gcnt[b * 4 + a]), 1u);
                    }
                }
                __syncwarp();
            }
            if ((tid & 31) == 0) tma_wait_all0();
        }
        if (tid == 0) {
            int stage = 0;
            uint32_t phase = 0;
            for (int it = 0; it < n_items; it++) {
                const int item = sched.item[blockIdx.x][it];
                const int type = item >> 12, b = item & 15;
                int a = (item >> 4) & 0xff;
                const CUtensorMap* ta = &tm.a[type];
                const CUtensorMap* tb = &tm.b[type];
                int kc = 0, kend = (type == T_F2) ? FF / 128 : DM / 128;
                bool gwait = false;
                if (type == T_OP) {
                    const int nch = 32 >> (a >> 5);
                    kc = ((a >> 2) & 7) * nch;
                    kend = kc + nch;
                    gwait = a < 32;
                    a &= 3;
                }
                if (type >= T_F2) {
                    const unsigned int* cnt = (type == T_F2) ? &g_hcnt[b] : &g_ocnt[b];
                    const unsigned int need = (type == T_F2) ? 2 * (FF / 128) : 2 * NH;
                    unsigned int v, spins = 0;
                    do {
                        asm volatile("ld.acquire.gpu.global.u32 %0, [%1];" : "=r"(v) : "l"(cnt) : "memory");
                    } while (v < need && ++spins < (1u << 24));
                    asm volatile("fence.proxy.async;" ::: "memory");
                }
                for (; kc < kend; kc++) {
                    if (gwait && kc == kend - 1) {
                        unsigned int v, spins = 0;
                        do {
                            asm volatile("ld.acquire.gpu.global.u32 %0, [%1];" : "=r"(v) : "l"(&g_gcnt[b * 4 + a]) : "memory");
                        } while (v < 2 && ++spins < (1u << 24));
                    }
                    mbar_wait(smem_u32(&sm.empty_k[stage]), phase ^ 1);
                    mbar_expect_tx(smem_u32(&sm.full_k[stage]), TILE_BYTES);
                    tma_load_3d(smem_u32(sm.k[stage]), ta, smem_u32(&sm.full_k[stage]), 0, kc * SEQ + b * 128, 0);
                    mbar_wait(smem_u32(&sm.empty_v[stage]), phase ^ 1);
                    mbar_expect_tx(smem_u32(&sm.full_v[stage]), TILE_BYTES);
                    tma_load_3d(smem_u32(sm.v[stage]), tb, smem_u32(&sm.full_v[stage]), 0, kc * 128, a * 2);
                    if (++stage == AT_STAGES) { stage = 0; phase ^= 1; }
                }
                if (type == T_ATT) {
                    for (int j = 0; j < 16; j++) {
                        mbar_wait(smem_u32(&sm.empty_k[stage]), phase ^ 1);
                        mbar_expect_tx(smem_u32(&sm.full_k[stage]), TILE_BYTES);
                        tma_load_3d(smem_u32(sm.k[stage]), &tm.k, smem_u32(&sm.full_k[stage]), 0, a * SEQ + j * 128, 0);
                        mbar_wait(smem_u32(&sm.empty_v[stage]), phase ^ 1);
                        mbar_expect_tx(smem_u32(&sm.full_v[stage]), TILE_BYTES);
                        tma_load_3d(smem_u32(sm.v[stage]), &tm.v, smem_u32(&sm.full_v[stage]), 0, a * SEQ + j * 128, 0);
                        if (++stage == AT_STAGES) { stage = 0; phase ^= 1; }
                    }
                }
            }
        }
    } else {
        reg_alloc<240>();
        const int cw = wg - 1;
        const int lane = tid & 31;
        const int warp_in_wg = (tid >> 5) & 3;
        const float c = 1.4426950408889634f;
        const uint32_t SCALE_HI2 = 0x3DB53DB5u, SCALE_LO2 = 0x371E371Eu;
        const uint32_t obase = smem_u32(sm.o) + cw * 16384;
        const int st_row = warp_in_wg * 16 + ((lane >> 3) & 1) * 8 + (lane & 7);

        const uint32_t dq = __shfl_sync(0xffffffffu, desc_lo(obase, 16), 0);
        const uint32_t dk0 = __shfl_sync(0xffffffffu, desc_lo(smem_u32(sm.k[0]), 16), 0);
        const uint32_t dv0 = dk0 - (1u << 16) + (1024u << 16) + AT_STAGES * (TILE_BYTES >> 4);

        PP(if (cw == 1) named_arrive(BAR_SCHED0 + 0, 256));

        int stage = 0;
        uint32_t phase = 0;
        uint32_t nst = 1;
        float S[64], O[64];
        uint32_t P[32];

        for (int it = 0; it < n_items; it++) {
            const int item = sched.item[blockIdx.x][it];
            const int type = item >> 12;
            const int lgp = (type == T_OP) ? ((item >> 9) & 7) : 0;
            const int nch = (type == T_F2) ? FF / 128 : (type == T_OP ? 32 >> lgp : DM / 128);
            {
                int prev = -1;
#pragma unroll 1
                for (int kc = 0; kc < nch; kc++) {
                    mbar_wait(smem_u32(&sm.full_k[stage]), phase);
                    mbar_wait(smem_u32(&sm.full_v[stage]), phase);
                    const uint64_t da = make_desc(smem_u32(sm.k[stage]) + cw * 64 * 128, 16, 1024);
                    const uint64_t db = make_desc(smem_u32(sm.v[stage]), 16384, 1024);
                    wgmma_fence();
#pragma unroll
                    for (int kk = 0; kk < 8; kk++) {
                        wgmma_ss_n128<1>(S, da + (uint64_t)(((kk >> 2) * 16384 + (kk & 3) * 32) >> 4),
                                         db + (uint64_t)((kk * 2048) >> 4), (kc | kk) != 0);
                    }
                    wgmma_commit();
                    wgmma_wait<1>();
                    if (prev >= 0 && lane == 0) {
                        mbar_arrive(smem_u32(&sm.empty_k[prev]));
                        mbar_arrive(smem_u32(&sm.empty_v[prev]));
                    }
                    prev = stage;
                    if (++stage == AT_STAGES) { stage = 0; phase ^= 1; }
                }
                if (type == T_OP && lgp == 0) {
                    const size_t off0 = (size_t)((item & 15) * 128 + cw * 64 + warp_in_wg * 16 + (lane >> 2)) * DM +
                                        ((item >> 4) & 3) * 128 + (lane & 3) * 2;
#pragma unroll
                    for (int i = 0; i < 16; i++) {
#pragma unroll
                        for (int hh = 0; hh < 2; hh++) {
                            const size_t off = off0 + (size_t)hh * 8 * DM + i * 8;
                            O[4 * i + 2 * hh] = __uint_as_float(__ldg(reinterpret_cast<const uint32_t*>(x + off)));
                            O[4 * i + 2 * hh + 1] = __uint_as_float(__ldcg(reinterpret_cast<const uint32_t*>(g_g + off)));
                        }
                    }
                }
                wgmma_wait<0>();
                if (lane == 0) {
                    mbar_arrive(smem_u32(&sm.empty_k[prev]));
                    mbar_arrive(smem_u32(&sm.empty_v[prev]));
                }
            }
            if (lgp != 0) {
                const int tile = (item & 15) * 4 + ((item >> 4) & 3);
                float4* part = g_part + (size_t)(tile * 2 + cw) * 16 * 128 + (tid & 127);
#pragma unroll
                for (int i = 0; i < 16; i++)
                    asm volatile("red.global.add.v4.f32 [%0], {%1, %2, %3, %4};" ::"l"(part + i * 128), "f"(S[4 * i]),
                                 "f"(S[4 * i + 1]), "f"(S[4 * i + 2]), "f"(S[4 * i + 3])
                                 : "memory");
                __threadfence();
                __syncwarp();
                unsigned int old = 0;
                if (lane == 0) old = atomicAdd(&g_tcnt[tile * 8 + cw * 4 + warp_in_wg], 1u);
                old = __shfl_sync(0xffffffffu, old, 0);
                if (old == (1u << lgp) - 1) {
                    if (lane == 0) {
                        unsigned int v, spins = 0;
                        do {
                            asm volatile("ld.acquire.gpu.global.u32 %0, [%1];" : "=r"(v) : "l"(&g_gcnt[tile]) : "memory");
                        } while (v < 2 && ++spins < (1u << 24));
                    }
                    __syncwarp();
                    __threadfence();
                    const size_t off0 = (size_t)((item & 15) * 128 + cw * 64 + warp_in_wg * 16 + (lane >> 2)) * DM +
                                        ((item >> 4) & 3) * 128 + (lane & 3) * 2;
#pragma unroll
                    for (int i = 0; i < 16; i++) {
                        const float4 sv = __ldcg(part + i * 128);
                        __stcg(part + i * 128, make_float4(0.f, 0.f, 0.f, 0.f));
#pragma unroll
                        for (int hh = 0; hh < 2; hh++) {
                            const size_t off = off0 + (size_t)hh * 8 * DM + i * 8;
                            const uint32_t xv = __ldg(reinterpret_cast<const uint32_t*>(x + off));
                            const uint32_t gv = __ldcg(reinterpret_cast<const uint32_t*>(g_g + off));
                            const float o0 = bf16lo(xv) + bf16_round(bf16_round(hh ? sv.z : sv.x) * bf16lo(gv));
                            const float o1 = bf16hi(xv) + bf16_round(bf16_round(hh ? sv.w : sv.y) * bf16hi(gv));
                            *reinterpret_cast<uint32_t*>(out + off) = pack_bf16(o0, o1);
                        }
                    }
                }
                continue;
            }
            if (type == T_OP) {
#pragma unroll
                for (int i = 0; i < 32; i++) {
                    const uint32_t xv = __float_as_uint(O[2 * i]), gv = __float_as_uint(O[2 * i + 1]);
                    S[2 * i] = bf16lo(xv) + bf16_round(bf16_round(S[2 * i]) * bf16lo(gv));
                    S[2 * i + 1] = bf16hi(xv) + bf16_round(bf16_round(S[2 * i + 1]) * bf16hi(gv));
                }
            } else if (type != T_ATT) {
#pragma unroll
                for (int i = 0; i < 64; i++) S[i] = silu_f(bf16_round(S[i]));
            }
            mbar_wait(smem_u32(&sm.st_free[cw]), nst);
            nst ^= 1;
#pragma unroll
            for (int i = 0; i < 16; i += 2) {
                const int cc = i + (lane >> 4);
                const uint32_t addr = obase + (cc >> 3) * 8192 + st_row * 128 + (((cc & 7) ^ (st_row & 7)) << 4);
                stmatrix_x4(addr, pack_bf16(S[4 * i], S[4 * i + 1]), pack_bf16(S[4 * i + 2], S[4 * i + 3]),
                            pack_bf16(S[4 * i + 4], S[4 * i + 5]), pack_bf16(S[4 * i + 6], S[4 * i + 7]));
            }
            fence_proxy_async();
            if (type != T_ATT) {
                named_arrive(BAR_ST0 + cw, 160);
                continue;
            }
            named_sync(BAR_EPI0 + cw, 128);
#pragma unroll
            for (int i = 0; i < 64; i++) O[i] = 0.f;

            float m0 = -INFINITY, m1 = -INFINITY, l0 = 0.f, l1 = 0.f, a0 = 0.f, a1 = 0.f;
            bool resc = false;
            const float TAU = 11.0f;
            const uint32_t fk0 = smem_u32(&sm.full_k[0]), fv0 = smem_u32(&sm.full_v[0]);
            const uint32_t ek0 = smem_u32(&sm.empty_k[0]), ev0 = smem_u32(&sm.empty_v[0]);

            uint32_t T[32];
            float n0, n1;
            auto softmax1 = [&]() {
#pragma unroll
                for (int i = 0; i < 32; i++) {
                    const uint32_t sb = pack_bf16(S[2 * i], S[2 * i + 1]);
                    T[i] = fma_bf16x2(sb, SCALE_HI2, mul_bf16x2(sb, SCALE_LO2));
                }
                uint32_t y0 = max_bf16x2(T[0], T[2]), y1 = max_bf16x2(T[1], T[3]);
#pragma unroll
                for (int i = 2; i < 16; i++) {
                    y0 = max_bf16x2(y0, T[2 * i]);
                    y1 = max_bf16x2(y1, T[2 * i + 1]);
                }
                float x0 = fmaxf(bf16lo(y0), bf16hi(y0));
                float x1 = fmaxf(bf16lo(y1), bf16hi(y1));
                x0 = fmaxf(x0, __shfl_xor_sync(0xffffffffu, x0, 1));
                x1 = fmaxf(x1, __shfl_xor_sync(0xffffffffu, x1, 1));
                x0 = fmaxf(x0, __shfl_xor_sync(0xffffffffu, x0, 2));
                x1 = fmaxf(x1, __shfl_xor_sync(0xffffffffu, x1, 2));
                resc = __any_sync(0xffffffffu, (x0 - m0 > TAU) || (x1 - m1 > TAU));
                x0 = resc ? fmaxf(x0, m0) : m0;
                x1 = resc ? fmaxf(x1, m1) : m1;
                a0 = ex2((m0 - x0) * c);
                a1 = ex2((m1 - x1) * c);
                m0 = x0;
                m1 = x1;
                n0 = -m0 * c;
                n1 = -m1 * c;
                while (n0 != n0) n0 = g_dummy;
            };
            auto softmax2 = [&]() {
                float s0 = 0.f, s1 = 0.f;
#pragma unroll
                for (int i = 0; i < 16; i++) {
                    const float e0 = ex2(fmaf(bf16lo(T[2 * i]), c, n0));
                    const float e1 = ex2(fmaf(bf16hi(T[2 * i]), c, n0));
                    const float e2 = ex2(fmaf(bf16lo(T[2 * i + 1]), c, n1));
                    const float e3 = ex2(fmaf(bf16hi(T[2 * i + 1]), c, n1));
                    s0 += e0 + e1;
                    s1 += e2 + e3;
                    P[2 * i] = pack_bf16(e0, e1);
                    P[2 * i + 1] = pack_bf16(e2, e3);
                }
                l0 = l0 * a0 + s0;
                l1 = l1 * a1 + s1;
            };
            auto issue_qk = [&](uint32_t dk) {
                wgmma_fence();
#pragma unroll
                for (int kk = 0; kk < 8; kk++)
                    wgmma_ss_lo<0>(S, dq + (((kk >> 2) * 8192 + (kk & 3) * 32) >> 4),
                                   dk + (((kk >> 2) * 16384 + (kk & 3) * 32) >> 4), kk != 0);
                wgmma_commit();
            };
            auto issue_pv = [&](uint32_t dv) {
                if (resc) {
#pragma unroll
                    for (int i = 0; i < 16; i++) {
                        O[4 * i] *= a0;
                        O[4 * i + 1] *= a0;
                        O[4 * i + 2] *= a1;
                        O[4 * i + 3] *= a1;
                    }
                }
                wgmma_fence();
#pragma unroll
                for (int kk = 0; kk < 8; kk++)
                    wgmma_rs_lo_tb(O, P[4 * kk], P[4 * kk + 1], P[4 * kk + 2], P[4 * kk + 3], dv + ((kk * 2048) >> 4));
                wgmma_commit();
            };

            int vstage = stage;
            uint32_t vphase = phase;
            bool okk, okv;
            {
                mbar_wait(fk0 + stage * 8, phase);
                PP(named_sync(BAR_SCHED0 + cw, 256));
                issue_qk(dk0 + stage * (TILE_BYTES >> 4));
                PP(named_arrive(BAR_SCHED0 + (cw ^ 1), 256));
                if (++stage == AT_STAGES) { stage = 0; phase ^= 1; }
                okk = mbar_try_wait(fk0 + stage * 8, phase);
                okv = mbar_try_wait(fv0 + vstage * 8, vphase);
                wgmma_wait<0>();
                if (lane == 0) mbar_arrive(ek0 + vstage * 8);
            }
            softmax1();
            softmax2();
            resc = false;

#pragma unroll 1
            for (int j = 1; j < 16; j++) {
                const int ust = __shfl_sync(0xffffffffu, stage, 0), uvs = __shfl_sync(0xffffffffu, vstage, 0);
                if (!okk) mbar_wait(fk0 + stage * 8, phase);
                if (!okv) mbar_wait(fv0 + vstage * 8, vphase);
                PP(named_sync(BAR_SCHED0 + cw, 256));
                issue_qk(dk0 + ust * (TILE_BYTES >> 4));
                issue_pv(dv0 + uvs * (TILE_BYTES >> 4));
                PP(named_arrive(BAR_SCHED0 + (cw ^ 1), 256));
                const int pv = vstage;
                vstage = stage;
                vphase = phase;
                if (++stage == AT_STAGES) { stage = 0; phase ^= 1; }
                okk = mbar_try_wait(fk0 + stage * 8, phase);
                okv = mbar_try_wait(fv0 + vstage * 8, vphase);
                wgmma_wait<1>();
                if (lane == 0) mbar_arrive(ek0 + vstage * 8);
                softmax1();
                wgmma_wait<0>();
                if (lane == 0) mbar_arrive(ev0 + pv * 8);
                softmax2();
            }
            if (!okv) mbar_wait(fv0 + vstage * 8, vphase);
            issue_pv(dv0 + vstage * (TILE_BYTES >> 4));
            wgmma_wait<0>();
            if (lane == 0) mbar_arrive(ev0 + vstage * 8);
            l0 += __shfl_xor_sync(0xffffffffu, l0, 1);
            l1 += __shfl_xor_sync(0xffffffffu, l1, 1);
            l0 += __shfl_xor_sync(0xffffffffu, l0, 2);
            l1 += __shfl_xor_sync(0xffffffffu, l1, 2);
            const float i0 = 1.0f / l0, i1 = 1.0f / l1;
            named_sync(BAR_EPI0 + cw, 128);
#pragma unroll
            for (int i = 0; i < 16; i += 2) {
                const int cc = i + (lane >> 4);
                const uint32_t addr = obase + (cc >> 3) * 8192 + st_row * 128 + (((cc & 7) ^ (st_row & 7)) << 4);
                stmatrix_x4(addr, pack_bf16(O[4 * i] * i0, O[4 * i + 1] * i0), pack_bf16(O[4 * i + 2] * i1, O[4 * i + 3] * i1),
                            pack_bf16(O[4 * i + 4] * i0, O[4 * i + 5] * i0), pack_bf16(O[4 * i + 6] * i1, O[4 * i + 7] * i1));
            }
            fence_proxy_async();
            named_arrive(BAR_ST0 + cw, 160);
        }
    }
}

typedef CUresult (*EncodeFn)(CUtensorMap*, CUtensorMapDataType, cuuint32_t, void*, const cuuint64_t*, const cuuint64_t*,
                             const cuuint32_t*, const cuuint32_t*, CUtensorMapInterleave, CUtensorMapSwizzle,
                             CUtensorMapL2promotion, CUtensorMapFloatOOBfill);

static CUtensorMap make_map(EncodeFn fn, const void* ptr, uint64_t rows, uint64_t cols, uint32_t box_rows, uint32_t box_blk) {
    CUtensorMap m;
    cuuint64_t dims[3] = {64, rows, cols / 64};
    cuuint64_t strides[2] = {cols * 2, 128};
    cuuint32_t box[3] = {64, box_rows, box_blk};
    cuuint32_t es[3] = {1, 1, 1};
    fn(&m, CU_TENSOR_MAP_DATA_TYPE_BFLOAT16, 3, const_cast<void*>(ptr), dims, strides, box, es, CU_TENSOR_MAP_INTERLEAVE_NONE,
       CU_TENSOR_MAP_SWIZZLE_128B, CU_TENSOR_MAP_L2_PROMOTION_L2_256B, CU_TENSOR_MAP_FLOAT_OOB_FILL_NONE);
    return m;
}

static double simulate(double T, Sched* out) {
    const double C_A = 54.8, C_F1 = 7.0, C_G = 19.8, C_CH = 1.15, E_OP = 3.5, E_SP = 2.5;
    const int NX = 16, NTAIL = 4, LGT = 3, N4 = NH * 16 - 3 * NUM_CTAS;
    const double C_OP = 32 * C_CH + E_OP, C_T = (32 >> LGT) * C_CH + E_SP;
    double fr[NUM_CTAS], odone[16] = {0}, hdone[16] = {0}, gdone[64] = {0};
    int natt[NUM_CTAS], ocnt[16] = {0}, hcnt[16] = {0};
    bool nofill[NUM_CTAS], wantg[NUM_CTAS], done[NUM_CTAS];
    for (int i = 0; i < NUM_CTAS; i++) {
        fr[i] = 2.5;
        natt[i] = i < N4 ? 4 : 3;
        nofill[i] = i >= N4 - NX;
        wantg[i] = i < 64;
        done[i] = false;
        out->count[i] = 0;
    }
    const int NOP = (16 - NTAIL) * 4, NT = NTAIL * 4 << LGT;
    int na = 0, n1 = 0, n2 = 0, n3 = 0, n4 = 0;
    double span = 0;
    for (;;) {
        int c = -1;
        for (int i = 0; i < NUM_CTAS; i++)
            if (!done[i] && (c < 0 || fr[i] < fr[c])) c = i;
        if (c < 0) break;
        const double t = fr[c], rem = natt[c] * C_A;
        const bool f1 = n1 < 224, g = n2 < 64, op = n3 < NOP, tl = n4 < NT;
        const bool gsched = g && hcnt[n2 >> 2] == 14, gready = gsched && hdone[n2 >> 2] <= t;
        const bool opok = op && ocnt[n3 >> 2] == NH && n3 < n2;
        char pick;
        if (natt[c] > 0) {
            if (!nofill[c] && wantg[c] && gready) pick = 'G';
            else if (!nofill[c] && f1 && t + C_F1 + (wantg[c] ? C_G : 0) + rem + C_T <= T) pick = 'F';
            else pick = 'A';
        } else {
            if (opok && nofill[c] && t + C_OP <= T + 3) pick = 'O';
            else if (f1) pick = 'F';
            else if (gsched) pick = 'G';
            else if (opok) pick = 'O';
            else if (tl && !g && ocnt[16 - NTAIL + (n4 >> (LGT + 2))] == NH) pick = 'T';
            else if (g || op || tl) { fr[c] += 0.5; continue; }
            else { done[c] = true; span = fr[c] > span ? fr[c] : span; continue; }
        }
        auto mx = [](double u, double v) { return u > v ? u : v; };
        int type, a, b;
        if (pick == 'F') {
            type = T_F1; a = n1 % 14; b = n1 / 14; n1++;
            fr[c] = t + C_F1; hcnt[b]++; hdone[b] = mx(hdone[b], fr[c]);
        } else if (pick == 'G') {
            type = T_F2; a = n2 & 3; b = n2 >> 2;
            fr[c] = mx(t, hdone[b]) + C_G; gdone[n2] = fr[c]; wantg[c] = false; n2++;
        } else if (pick == 'O') {
            type = T_OP; a = n3 & 3; b = n3 >> 2;
            fr[c] = mx(mx(t, odone[b]) + C_OP - E_OP, gdone[n3]) + E_OP; n3++;
        } else if (pick == 'T') {
            const int tile = NOP + (n4 >> LGT);
            type = T_OP; a = (tile & 3) | ((n4 & ((1 << LGT) - 1)) << 2) | (LGT << 5); b = tile >> 2;
            fr[c] = mx(mx(t, odone[b]) + C_T - E_SP, gdone[tile]) + E_SP; n4++;
        } else {
            type = T_ATT; a = na % NH; b = na / NH; na++; natt[c]--;
            fr[c] = t + C_A; ocnt[b]++; odone[b] = mx(odone[b], fr[c]);
        }
        if (out->count[c] >= MAX_ITEMS) return 1e30;
        out->item[c][out->count[c]++] = (uint16_t)((type << 12) | (a << 4) | b);
    }
    return span;
}
static void build_schedule(Sched& sched) {
    double best = 1e30, bestT = 260;
    for (double T = 230; T <= 290; T += 1.0) {
        const double m = simulate(T, &sched);
        if (m < best) { best = m; bestT = T; }
    }
    simulate(bestT, &sched);
}

extern "C" void kernel_launch(void* const* d_in, const int* in_sizes, int n_in, void* d_out, int out_size) {
    const bf16* x = (const bf16*)d_in[0];
    const bf16* kc = (const bf16*)d_in[1];
    const bf16* vc = (const bf16*)d_in[2];
    const bf16* wq = (const bf16*)d_in[3];
    const bf16* wo = (const bf16*)d_in[4];
    const bf16* w1 = (const bf16*)d_in[6];
    const bf16* w2 = (const bf16*)d_in[7];
    bf16* out = (bf16*)d_out;

    static EncodeFn fn = nullptr;
    static void *p_xn = nullptr, *p_h = nullptr, *p_o = nullptr, *p_g = nullptr;
    static Sched sched;
    if (!fn) {
        void* f = nullptr;
        cudaDriverEntryPointQueryResult st;
        cudaGetDriverEntryPoint("cuTensorMapEncodeTiled", &f, cudaEnableDefault, &st);
        fn = (EncodeFn)f;
        cudaGetSymbolAddress(&p_xn, g_xn);
        cudaGetSymbolAddress(&p_h, g_h);
        cudaGetSymbolAddress(&p_o, g_o);
        cudaGetSymbolAddress(&p_g, g_g);
        cudaFuncSetAttribute(attn_kernel, cudaFuncAttributeMaxDynamicSharedMemorySize, (int)sizeof(AttnSmem) + 1024);
        build_schedule(sched);
    }
    Maps tm;
    tm.a[T_ATT] = tm.a[T_F1] = make_map(fn, p_xn, (DM / 128) * SEQ, 128, 128, 2);
    tm.a[T_F2] = make_map(fn, p_h, (FF / 128) * SEQ, 128, 128, 2);
    tm.a[T_OP] = make_map(fn, p_o, NH * SEQ, 128, 128, 2);
    tm.b[T_ATT] = make_map(fn, wq, DM, NH * DH, 128, 2);
    tm.b[T_F1] = make_map(fn, w1, DM, FF, 128, 2);
    tm.b[T_F2] = make_map(fn, w2, FF, DM, 128, 2);
    tm.b[T_OP] = make_map(fn, wo, NH * DH, DM, 128, 2);
    tm.st[T_ATT] = make_map(fn, p_o, NH * SEQ, 128, 64, 2);
    tm.st[T_F1] = make_map(fn, p_h, (FF / 128) * SEQ, 128, 64, 2);
    tm.st[T_F2] = make_map(fn, p_g, SEQ, DM, 64, 2);
    tm.st[T_OP] = make_map(fn, out, SEQ, DM, 64, 2);
    tm.k = make_map(fn, kc, NH * SEQ, DH, 128, 2);
    tm.v = make_map(fn, vc, NH * SEQ, DH, 128, 2);

    ln_kernel<<<SEQ / 8, 256>>>(x);
    attn_kernel<<<NUM_CTAS, 384, sizeof(AttnSmem) + 1024>>>(tm, sched, x, out);
}
```

```cpp
#include <cuda_runtime.h>
#include <cuda_bf16.h>
#include <cuda.h>
#include <stdint.h>

typedef __nv_bfloat16 bf16;
#define PP(x) x

constexpr int SEQ = 2048, DM = 512, NH = 32, DH = 128, FF = 1792;

__device__ __align__(1024) bf16 g_xn[SEQ * DM];
__device__ __align__(1024) bf16 g_h[SEQ * FF];
__device__ __align__(1024) bf16 g_o[SEQ * NH * DH];
__device__ __align__(1024) bf16 g_g[SEQ * DM];
__device__ unsigned int g_hcnt[SEQ / 128];
__device__ float4 g_part[32 * 16 * 8 * 256];
__device__ unsigned int g_pcnt[128];
__device__ volatile float g_dummy;

__device__ __forceinline__ uint32_t smem_u32(const void* p) { return (uint32_t)__cvta_generic_to_shared(p); }

__device__ __forceinline__ void mbar_init(uint32_t bar, uint32_t count) {
    asm volatile("mbarrier.init.shared::cta.b64 [%0], %1;" ::"r"(bar), "r"(count) : "memory");
}
__device__ __forceinline__ void mbar_expect_tx(uint32_t bar, uint32_t bytes) {
    asm volatile("mbarrier.arrive.expect_tx.shared::cta.b64 _, [%0], %1;" ::"r"(bar), "r"(bytes) : "memory");
}
__device__ __forceinline__ void mbar_arrive(uint32_t bar) {
    asm volatile("mbarrier.arrive.shared::cta.b64 _, [%0];" ::"r"(bar) : "memory");
}
__device__ __forceinline__ bool mbar_try_wait(uint32_t bar, uint32_t parity) {
    uint32_t ok;
    asm volatile(
        "{\n.reg .pred p;\n"
        "mbarrier.test_wait.parity.shared::cta.b64 p, [%1], %2;\n"
        "selp.u32 %0, 1, 0, p;\n}\n"
        : "=r"(ok)
        : "r"(bar), "r"(parity)
        : "memory");
    return ok != 0;
}
__device__ __forceinline__ void mbar_wait(uint32_t bar, uint32_t parity) {
    asm volatile(
        "{\n.reg .pred P1;\n.reg .u32 n;\nmov.u32 n, 0;\n"
        "LAB_WAIT:\n"
        "mbarrier.try_wait.parity.shared::cta.b64 P1, [%0], %1;\n"
        "@P1 bra DONE;\n"
        "add.u32 n, n, 1;\n"
        "setp.lt.u32 P1, n, 4194304;\n"
        "@P1 bra LAB_WAIT;\n"
        "trap;\n"
        "DONE:\n}\n" ::"r"(bar), "r"(parity)
        : "memory");
}
__device__ __forceinline__ void tma_load_3d(uint32_t dst, const CUtensorMap* map, uint32_t bar, int c0, int c1, int c2) {
    asm volatile(
        "cp.async.bulk.tensor.3d.shared::cluster.global.mbarrier::complete_tx::bytes [%0], [%1, {%3, %4, %5}], [%2];"
        ::"r"(dst), "l"((uint64_t)map), "r"(bar), "r"(c0), "r"(c1), "r"(c2)
        : "memory");
}
__device__ __forceinline__ void tma_store_3d(const CUtensorMap* map, uint32_t src, int c0, int c1, int c2) {
    asm volatile("cp.async.bulk.tensor.3d.global.shared::cta.bulk_group [%0, {%2, %3, %4}], [%1];"
                 ::"l"((uint64_t)map), "r"(src), "r"(c0), "r"(c1), "r"(c2)
                 : "memory");
}
__device__ __forceinline__ void tma_commit() { asm volatile("cp.async.bulk.commit_group;" ::: "memory"); }
__device__ __forceinline__ void tma_wait_read0() { asm volatile("cp.async.bulk.wait_group.read 0;" ::: "memory"); }
__device__ __forceinline__ void tma_wait_all0() { asm volatile("cp.async.bulk.wait_group 0;" ::: "memory"); }
__device__ __forceinline__ void fence_proxy_async() { asm volatile("fence.proxy.async.shared::cta;" ::: "memory"); }
__device__ __forceinline__ void prefetch_tmap(const CUtensorMap* map) {
    asm volatile("prefetch.tensormap [%0];" ::"l"((uint64_t)map) : "memory");
}
__device__ __forceinline__ void named_sync(int id, int n) { asm volatile("bar.sync %0, %1;" ::"r"(id), "r"(n) : "memory"); }
__device__ __forceinline__ void named_arrive(int id, int n) { asm volatile("bar.arrive %0, %1;" ::"r"(id), "r"(n) : "memory"); }

__device__ __forceinline__ void wgmma_fence() { asm volatile("wgmma.fence.sync.aligned;" ::: "memory"); }
__device__ __forceinline__ void wgmma_commit() { asm volatile("wgmma.commit_group.sync.aligned;" ::: "memory"); }
template <int N>
__device__ __forceinline__ void wgmma_wait() { asm volatile("wgmma.wait_group.sync.aligned %0;" ::"n"(N) : "memory"); }

template <int R>
__device__ __forceinline__ void reg_alloc() { asm volatile("setmaxnreg.inc.sync.aligned.u32 %0;" ::"n"(R)); }
template <int R>
__device__ __forceinline__ void reg_dealloc() { asm volatile("setmaxnreg.dec.sync.aligned.u32 %0;" ::"n"(R)); }

__device__ __forceinline__ uint64_t make_desc(uint32_t saddr, uint32_t lbo_bytes, uint32_t sbo_bytes) {
    uint64_t d = 0;
    d |= (uint64_t)((saddr & 0x3FFFF) >> 4);
    d |= (uint64_t)((lbo_bytes >> 4) & 0x3FFF) << 16;
    d |= (uint64_t)((sbo_bytes >> 4) & 0x3FFF) << 32;
    d |= (uint64_t)1 << 62;
    return d;
}

__device__ __forceinline__ float ex2(float x) {
    float y;
    asm volatile("ex2.approx.ftz.f32 %0, %1;" : "=f"(y) : "f"(x));
    return y;
}
__device__ __forceinline__ uint32_t pack_bf16(float lo, float hi) {
    uint32_t r;
    asm("cvt.rn.bf16x2.f32 %0, %1, %2;" : "=r"(r) : "f"(hi), "f"(lo));
    return r;
}
__device__ __forceinline__ uint32_t mul_bf16x2(uint32_t a, uint32_t b) {
    uint32_t r;
    asm("mul.rn.bf16x2 %0, %1, %2;" : "=r"(r) : "r"(a), "r"(b));
    return r;
}
__device__ __forceinline__ uint32_t fma_bf16x2(uint32_t a, uint32_t b, uint32_t c) {
    uint32_t r;
    asm("fma.rn.bf16x2 %0, %1, %2, %3;" : "=r"(r) : "r"(a), "r"(b), "r"(c));
    return r;
}
__device__ __forceinline__ uint32_t max_bf16x2(uint32_t a, uint32_t b) {
    uint32_t r;
    asm("max.bf16x2 %0, %1, %2;" : "=r"(r) : "r"(a), "r"(b));
    return r;
}
__device__ __forceinline__ float bf16lo(uint32_t v) { return __uint_as_float(v << 16); }
__device__ __forceinline__ float bf16hi(uint32_t v) { return __uint_as_float(v & 0xffff0000u); }
__device__ __forceinline__ float bf16_round(float x) { return __bfloat162float(__float2bfloat16_rn(x)); }
__device__ __forceinline__ float silu_f(float x) {
    const float h = 0.5f * x;
    float t;
    asm("tanh.approx.f32 %0, %1;" : "=f"(t) : "f"(h));
    return fmaf(h, t, h);
}

__device__ __forceinline__ void stmatrix_x4(uint32_t addr, uint32_t r0, uint32_t r1, uint32_t r2, uint32_t r3) {
    asm volatile("stmatrix.sync.aligned.m8n8.x4.shared.b16 [%0], {%1, %2, %3, %4};"
                 ::"r"(addr), "r"(r0), "r"(r1), "r"(r2), "r"(r3)
                 : "memory");
}

#define ACC64(d) \
    "+f"(d[0]), "+f"(d[1]), "+f"(d[2]), "+f"(d[3]), "+f"(d[4]), "+f"(d[5]), "+f"(d[6]), "+f"(d[7]), \
    "+f"(d[8]), "+f"(d[9]), "+f"(d[10]), "+f"(d[11]), "+f"(d[12]), "+f"(d[13]), "+f"(d[14]), "+f"(d[15]), \
    "+f"(d[16]), "+f"(d[17]), "+f"(d[18]), "+f"(d[19]), "+f"(d[20]), "+f"(d[21]), "+f"(d[22]), "+f"(d[23]), \
    "+f"(d[24]), "+f"(d[25]), "+f"(d[26]), "+f"(d[27]), "+f"(d[28]), "+f"(d[29]), "+f"(d[30]), "+f"(d[31]), \
    "+f"(d[32]), "+f"(d[33]), "+f"(d[34]), "+f"(d[35]), "+f"(d[36]), "+f"(d[37]), "+f"(d[38]), "+f"(d[39]), \
    "+f"(d[40]), "+f"(d[41]), "+f"(d[42]), "+f"(d[43]), "+f"(d[44]), "+f"(d[45]), "+f"(d[46]), "+f"(d[47]), \
    "+f"(d[48]), "+f"(d[49]), "+f"(d[50]), "+f"(d[51]), "+f"(d[52]), "+f"(d[53]), "+f"(d[54]), "+f"(d[55]), \
    "+f"(d[56]), "+f"(d[57]), "+f"(d[58]), "+f"(d[59]), "+f"(d[60]), "+f"(d[61]), "+f"(d[62]), "+f"(d[63])

#define ACC64_STR \
    "{%0, %1, %2, %3, %4, %5, %6, %7, %8, %9, %10, %11, %12, %13, %14, %15, " \
    "%16, %17, %18, %19, %20, %21, %22, %23, %24, %25, %26, %27, %28, %29, %30, %31, " \
    "%32, %33, %34, %35, %36, %37, %38, %39, %40, %41, %42, %43, %44, %45, %46, %47, " \
    "%48, %49, %50, %51, %52, %53, %54, %55, %56, %57, %58, %59, %60, %61, %62, %63}"

template <int TB>
__device__ __forceinline__ void wgmma_ss_n128(float (&d)[64], uint64_t da, uint64_t db, int scale_d) {
    asm volatile(
        "{\n.reg .pred p;\nsetp.ne.b32 p, %66, 0;\n"
        "wgmma.mma_async.sync.aligned.m64n128k16.f32.bf16.bf16 " ACC64_STR ", %64, %65, p, 1, 1, 0, %67;\n}\n"
        : ACC64(d)
        : "l"(da), "l"(db), "r"(scale_d), "n"(TB));
}
template <int TB>
__device__ __forceinline__ void wgmma_rs_n128(float (&d)[64], uint32_t a0, uint32_t a1, uint32_t a2, uint32_t a3,
                                              uint64_t db, int scale_d) {
    asm volatile(
        "{\n.reg .pred p;\nsetp.ne.b32 p, %69, 0;\n"
        "wgmma.mma_async.sync.aligned.m64n128k16.f32.bf16.bf16 " ACC64_STR ", {%64, %65, %66, %67}, %68, p, 1, 1, %70;\n}\n"
        : ACC64(d)
        : "r"(a0), "r"(a1), "r"(a2), "r"(a3), "l"(db), "r"(scale_d), "n"(TB));
}

constexpr uint32_t DESC_HI = 0x40000040u;
__device__ __forceinline__ uint32_t desc_lo(uint32_t saddr, uint32_t lbo_bytes) {
    return ((saddr & 0x3FFFF) >> 4) | ((lbo_bytes >> 4) << 16);
}
template <int TB>
__device__ __forceinline__ void wgmma_ss_lo(float (&d)[64], uint32_t da, uint32_t db, int scale_d) {
    asm volatile(
        "{\n.reg .pred p;\n.reg .b64 xa, xb;\nsetp.ne.b32 p, %66, 0;\n"
        "mov.b64 xa, {%64, %68};\nmov.b64 xb, {%65, %68};\n"
        "wgmma.mma_async.sync.aligned.m64n128k16.f32.bf16.bf16 " ACC64_STR ", xa, xb, p, 1, 1, 0, %67;\n}\n"
        : ACC64(d)
        : "r"(da), "r"(db), "r"(scale_d), "n"(TB), "r"(DESC_HI));
}
__device__ __forceinline__ void wgmma_rs_lo_tb(float (&d)[64], uint32_t a0, uint32_t a1, uint32_t a2, uint32_t a3, uint32_t db) {
    asm volatile(
        "{\n.reg .b64 xb;\nmov.b64 xb, {%68, %69};\n"
        "wgmma.mma_async.sync.aligned.m64n128k16.f32.bf16.bf16 " ACC64_STR ", {%64, %65, %66, %67}, xb, 1, 1, 1, 1;\n}\n"
        : ACC64(d)
        : "r"(a0), "r"(a1), "r"(a2), "r"(a3), "r"(db), "r"(DESC_HI));
}

__device__ __forceinline__ void wgmma_rs_n8(float (&d)[4], uint32_t a0, uint32_t a1, uint32_t a2, uint32_t a3, uint32_t db) {
    asm volatile(
        "{\n.reg .b64 xb;\nmov.b64 xb, {%8, %9};\n"
        "wgmma.mma_async.sync.aligned.m64n8k16.f32.bf16.bf16 {%0, %1, %2, %3}, {%4, %5, %6, %7}, xb, 1, 1, 1, 0;\n}\n"
        : "+f"(d[0]), "+f"(d[1]), "+f"(d[2]), "+f"(d[3])
        : "r"(a0), "r"(a1), "r"(a2), "r"(a3), "r"(db), "r"(8u));
}

__global__ void __launch_bounds__(256) ln_kernel(const bf16* __restrict__ x) {
    int warp = threadIdx.x >> 5, lane = threadIdx.x & 31;
    int row = blockIdx.x * 8 + warp;
    if (blockIdx.x == 0 && threadIdx.x < SEQ / 128) g_hcnt[threadIdx.x] = 0;
    if (blockIdx.x == 1 && threadIdx.x < 128) g_pcnt[threadIdx.x] = 0;
    const uint4* src = reinterpret_cast<const uint4*>(x + (size_t)row * DM);
    uint4 v[2];
    v[0] = src[lane];
    v[1] = src[lane + 32];
    float f[16];
#pragma unroll
    for (int i = 0; i < 2; i++) {
        const __nv_bfloat162* p = reinterpret_cast<const __nv_bfloat162*>(&v[i]);
#pragma unroll
        for (int j = 0; j < 4; j++) {
            float2 t = __bfloat1622float2(p[j]);
            f[i * 8 + j * 2] = t.x;
            f[i * 8 + j * 2 + 1] = t.y;
        }
    }
    float s = 0.f;
#pragma unroll
    for (int i = 0; i < 16; i++) s += f[i];
#pragma unroll
    for (int o = 16; o > 0; o >>= 1) s += __shfl_xor_sync(0xffffffffu, s, o);
    float mean = s * (1.0f / DM);
    float q = 0.f;
#pragma unroll
    for (int i = 0; i < 16; i++) {
        float d = f[i] - mean;
        q += d * d;
    }
#pragma unroll
    for (int o = 16; o > 0; o >>= 1) q += __shfl_xor_sync(0xffffffffu, q, o);
    float var_b = bf16_round(q * (1.0f / DM));
    float mean_b = bf16_round(mean);
    float den = bf16_round(sqrtf(bf16_round(var_b + 1e-5f)));
    uint4 o[2];
#pragma unroll
    for (int i = 0; i < 2; i++) {
        uint32_t* p = reinterpret_cast<uint32_t*>(&o[i]);
#pragma unroll
        for (int j = 0; j < 4; j++) {
            float a = bf16_round(f[i * 8 + j * 2] - mean_b) / den;
            float b = bf16_round(f[i * 8 + j * 2 + 1] - mean_b) / den;
            p[j] = pack_bf16(a, b);
        }
    }
    uint4* dst = reinterpret_cast<uint4*>(g_xn + (size_t)row * DM);
    dst[lane] = o[0];
    dst[lane + 32] = o[1];
}

constexpr int AT_STAGES = 3;
constexpr int TILE_BYTES = 128 * 128 * 2;
struct __align__(1024) AttnSmem {
    uint8_t k[AT_STAGES][TILE_BYTES];
    uint8_t v[AT_STAGES][TILE_BYTES];
    uint8_t o[TILE_BYTES];
    uint64_t full_k[AT_STAGES], full_v[AT_STAGES], empty_k[AT_STAGES], empty_v[AT_STAGES];
    uint64_t st_free[2];
    uint64_t redo_bar;
    uint32_t redo;
    __align__(128) uint32_t ones[128];
};

#define FAST_BIAS (-40.0f)
constexpr int NUM_CTAS = 132;
constexpr int MAX_ITEMS = 12;
enum { T_ATT = 0, T_F1 = 1, T_F2 = 2 };
struct Sched {
    uint16_t item[NUM_CTAS][MAX_ITEMS];
    uint8_t count[NUM_CTAS];
};

__global__ void __launch_bounds__(384, 1)
attn_kernel(const __grid_constant__ CUtensorMap tm_xn, const __grid_constant__ CUtensorMap tm_wq,
            const __grid_constant__ CUtensorMap tm_k, const __grid_constant__ CUtensorMap tm_v,
            const __grid_constant__ CUtensorMap tm_o, const __grid_constant__ CUtensorMap tm_w1,
            const __grid_constant__ CUtensorMap tm_hst, const __grid_constant__ CUtensorMap tm_hld,
            const __grid_constant__ CUtensorMap tm_w2, const __grid_constant__ CUtensorMap tm_gst,
            const __grid_constant__ Sched sched) {
    extern __shared__ uint8_t smem_raw[];
    AttnSmem& sm = *reinterpret_cast<AttnSmem*>((reinterpret_cast<uintptr_t>(smem_raw) + 1023) & ~uintptr_t(1023));
    const int tid = threadIdx.x;
    const int wg = __shfl_sync(0xffffffffu, tid >> 7, 0);
    const int n_items = sched.count[blockIdx.x];

    if (tid == 0) {
#pragma unroll
        for (int s = 0; s < AT_STAGES; s++) {
            mbar_init(smem_u32(&sm.full_k[s]), 1);
            mbar_init(smem_u32(&sm.full_v[s]), 1);
            mbar_init(smem_u32(&sm.empty_k[s]), 8);
            mbar_init(smem_u32(&sm.empty_v[s]), 8);
        }
        mbar_init(smem_u32(&sm.st_free[0]), 1);
        mbar_init(smem_u32(&sm.st_free[1]), 1);
        mbar_init(smem_u32(&sm.redo_bar), 8);
        sm.redo = 0;
        asm volatile("fence.mbarrier_init.release.cluster;" ::: "memory");
    }
    if (tid < 128) {
        sm.ones[tid] = 0x3F803F80u;
        fence_proxy_async();
    }
    __syncthreads();
    int it = 0;
    uint32_t rmask = 0;
    bool redo = false;
    auto next_item = [&]() -> bool {
        if (!redo) {
            if (++it < n_items) return true;
            mbar_wait(smem_u32(&sm.redo_bar), 0);
            rmask = *reinterpret_cast<volatile uint32_t*>(&sm.redo);
            redo = true;
        }
        if (!rmask) return false;
        it = __ffs(rmask) - 1;
        rmask &= rmask - 1;
        return true;
    };
    constexpr int BAR_SCHED0 = 1, BAR_EPI0 = 3, BAR_ST0 = 5;

    if (wg == 0) {
        reg_dealloc<24>();
        if (tid >= 32 && tid < 96) {
            const int cw = (tid >> 5) - 1;
            const uint32_t obase = smem_u32(sm.o) + cw * 16384;
            do {
                const int item = sched.item[blockIdx.x][it];
                const int type = item >> 12, a = (item >> 4) & 0xff, b = item & 15;
                named_sync(BAR_ST0 + cw, 160);
                if ((tid & 31) == 0) {
                    if (redo) tma_wait_all0();
                    tma_store_3d(type == T_ATT ? &tm_o : (type == T_F1 ? &tm_hst : &tm_gst), obase, 0, b * 128 + cw * 64, a * 2);
                    tma_commit();
                    tma_wait_read0();
                    mbar_arrive(smem_u32(&sm.st_free[cw]));
                    if (type == T_F1) {
                        tma_wait_all0();
                        asm volatile("fence.proxy.async;" ::: "memory");
                        __threadfence();
                        atomicAdd(&g_hcnt[b], 1u);
                    }
                }
                __syncwarp();
            } while (next_item());
            if ((tid & 31) == 0) tma_wait_all0();
        }
        if (tid == 0) {
            int stage = 0;
            uint32_t phase = 0;
            do {
                const int item = sched.item[blockIdx.x][it];
                const int type = item >> 12, a = (item >> 4) & 0xff, b = item & 15;
                const CUtensorMap* ta = (type == T_F2) ? &tm_hld : &tm_xn;
                const CUtensorMap* tb = (type == T_ATT) ? &tm_wq : (type == T_F1 ? &tm_w1 : &tm_w2);
                const int nch = (type == T_F2) ? FF / 128 : DM / 128;
                if (type == T_F2) {
                    unsigned int v, spins = 0;
                    do {
                        asm volatile("ld.acquire.gpu.global.u32 %0, [%1];" : "=r"(v) : "l"(&g_hcnt[b]) : "memory");
                    } while (v < 2 * (FF / 128) && ++spins < (1u << 24));
                    asm volatile("fence.proxy.async;" ::: "memory");
                }
                for (int kc = 0; kc < nch; kc++) {
                    mbar_wait(smem_u32(&sm.empty_k[stage]), phase ^ 1);
                    mbar_expect_tx(smem_u32(&sm.full_k[stage]), TILE_BYTES);
                    tma_load_3d(smem_u32(sm.k[stage]), ta, smem_u32(&sm.full_k[stage]), 0, b * 128, kc * 2);
                    mbar_wait(smem_u32(&sm.empty_v[stage]), phase ^ 1);
                    mbar_expect_tx(smem_u32(&sm.full_v[stage]), TILE_BYTES);
                    tma_load_3d(smem_u32(sm.v[stage]), tb, smem_u32(&sm.full_v[stage]), 0, kc * 128, a * 2);
                    if (++stage == AT_STAGES) { stage = 0; phase ^= 1; }
                }
                if (type == T_ATT) {
                    for (int j = 0; j < 16; j++) {
                        mbar_wait(smem_u32(&sm.empty_k[stage]), phase ^ 1);
                        mbar_expect_tx(smem_u32(&sm.full_k[stage]), TILE_BYTES);
                        tma_load_3d(smem_u32(sm.k[stage]), &tm_k, smem_u32(&sm.full_k[stage]), 0, a * SEQ + j * 128, 0);
                        mbar_wait(smem_u32(&sm.empty_v[stage]), phase ^ 1);
                        mbar_expect_tx(smem_u32(&sm.full_v[stage]), TILE_BYTES);
                        tma_load_3d(smem_u32(sm.v[stage]), &tm_v, smem_u32(&sm.full_v[stage]), 0, a * SEQ + j * 128, 0);
                        if (++stage == AT_STAGES) { stage = 0; phase ^= 1; }
                    }
                }
            } while (next_item());
        }
    } else {
        reg_alloc<240>();
        const int cw = wg - 1;
        const int lane = tid & 31;
        const int warp_in_wg = (tid >> 5) & 3;
        const float c = 1.4426950408889634f;
        const uint32_t SCALE_HI2 = 0x3DB53DB5u, SCALE_LO2 = 0x371E371Eu;
        const uint32_t obase = smem_u32(sm.o) + cw * 16384;
        const int st_row = warp_in_wg * 16 + ((lane >> 3) & 1) * 8 + (lane & 7);

        const uint32_t dq = __shfl_sync(0xffffffffu, desc_lo(obase, 16), 0);
        const uint32_t dk0 = __shfl_sync(0xffffffffu, desc_lo(smem_u32(sm.k[0]), 16), 0);
        const uint32_t dv0 = dk0 - (1u << 16) + (1024u << 16) + AT_STAGES * (TILE_BYTES >> 4);

        PP(if (cw == 1) named_arrive(BAR_SCHED0 + 0, 256));

        int stage = 0;
        uint32_t phase = 0;
        float S[64], O[64];
        uint32_t P[32], P2[32];
        uint32_t cnt = 0;
        const uint32_t dones = __shfl_sync(0xffffffffu, desc_lo(smem_u32(sm.ones), 128), 0);

        for (;;) {
            const int item = sched.item[blockIdx.x][it];
            const int type = item >> 12;
            const int nch = (type == T_F2) ? FF / 128 : DM / 128;
            {
                int prev = -1;
#pragma unroll 1
                for (int kc = 0; kc < nch; kc++) {
                    mbar_wait(smem_u32(&sm.full_k[stage]), phase);
                    mbar_wait(smem_u32(&sm.full_v[stage]), phase);
                    const uint64_t da = make_desc(smem_u32(sm.k[stage]) + cw * 64 * 128, 16, 1024);
                    const uint64_t db = make_desc(smem_u32(sm.v[stage]), 16384, 1024);
                    wgmma_fence();
#pragma unroll
                    for (int kk = 0; kk < 8; kk++) {
                        wgmma_ss_n128<1>(S, da + (uint64_t)(((kk >> 2) * 16384 + (kk & 3) * 32) >> 4),
                                         db + (uint64_t)((kk * 2048) >> 4), (kc | kk) != 0);
                    }
                    wgmma_commit();
                    wgmma_wait<1>();
                    if (prev >= 0 && lane == 0) {
                        mbar_arrive(smem_u32(&sm.empty_k[prev]));
                        mbar_arrive(smem_u32(&sm.empty_v[prev]));
                    }
                    prev = stage;
                    if (++stage == AT_STAGES) { stage = 0; phase ^= 1; }
                }
                wgmma_wait<0>();
                if (lane == 0) {
                    mbar_arrive(smem_u32(&sm.empty_k[prev]));
                    mbar_arrive(smem_u32(&sm.empty_v[prev]));
                }
            }
            if (type != T_ATT) {
#pragma unroll
                for (int i = 0; i < 64; i++) S[i] = silu_f(bf16_round(S[i]));
            }
            mbar_wait(smem_u32(&sm.st_free[cw]), (cnt & 1) ^ 1);
            cnt++;
#pragma unroll
            for (int i = 0; i < 16; i += 2) {
                const int cc = i + (lane >> 4);
                const uint32_t addr = obase + (cc >> 3) * 8192 + st_row * 128 + (((cc & 7) ^ (st_row & 7)) << 4);
                stmatrix_x4(addr, pack_bf16(S[4 * i], S[4 * i + 1]), pack_bf16(S[4 * i + 2], S[4 * i + 3]),
                            pack_bf16(S[4 * i + 4], S[4 * i + 5]), pack_bf16(S[4 * i + 6], S[4 * i + 7]));
            }
            fence_proxy_async();
            if (type != T_ATT) {
                named_arrive(BAR_ST0 + cw, 160);
            } else {
            named_sync(BAR_EPI0 + cw, 128);
#pragma unroll
            for (int i = 0; i < 64; i++) O[i] = 0.f;

            const uint32_t fk0 = smem_u32(&sm.full_k[0]), fv0 = smem_u32(&sm.full_v[0]);
            const uint32_t ek0 = smem_u32(&sm.empty_k[0]), ev0 = smem_u32(&sm.empty_v[0]);
            float i0, i1;

            auto issue_qk = [&](uint32_t dk) {
                wgmma_fence();
#pragma unroll
                for (int kk = 0; kk < 8; kk++)
                    wgmma_ss_lo<0>(S, dq + (((kk >> 2) * 8192 + (kk & 3) * 32) >> 4),
                                   dk + (((kk >> 2) * 16384 + (kk & 3) * 32) >> 4), kk != 0);
                wgmma_commit();
            };
            auto scores_max = [&](uint32_t (&T)[32], float& x0, float& x1) {
#pragma unroll
                for (int i = 0; i < 32; i++) {
                    const uint32_t sb = pack_bf16(S[2 * i], S[2 * i + 1]);
                    T[i] = fma_bf16x2(sb, SCALE_HI2, mul_bf16x2(sb, SCALE_LO2));
                }
                uint32_t y0 = max_bf16x2(T[0], T[2]), y1 = max_bf16x2(T[1], T[3]);
#pragma unroll
                for (int i = 2; i < 16; i++) {
                    y0 = max_bf16x2(y0, T[2 * i]);
                    y1 = max_bf16x2(y1, T[2 * i + 1]);
                }
                x0 = fmaxf(bf16lo(y0), bf16hi(y0));
                x1 = fmaxf(bf16lo(y1), bf16hi(y1));
                x0 = fmaxf(x0, __shfl_xor_sync(0xffffffffu, x0, 1));
                x1 = fmaxf(x1, __shfl_xor_sync(0xffffffffu, x1, 1));
                x0 = fmaxf(x0, __shfl_xor_sync(0xffffffffu, x0, 2));
                x1 = fmaxf(x1, __shfl_xor_sync(0xffffffffu, x1, 2));
            };

            int vstage = stage;
            uint32_t vphase = phase;
            bool okk, okv;
            {
                mbar_wait(fk0 + stage * 8, phase);
                PP(named_sync(BAR_SCHED0 + cw, 256));
                issue_qk(dk0 + stage * (TILE_BYTES >> 4));
                PP(named_arrive(BAR_SCHED0 + (cw ^ 1), 256));
                if (++stage == AT_STAGES) { stage = 0; phase ^= 1; }
                okk = mbar_try_wait(fk0 + stage * 8, phase);
                okv = mbar_try_wait(fv0 + vstage * 8, vphase);
                wgmma_wait<0>();
                if (lane == 0) mbar_arrive(ek0 + vstage * 8);
            }

            if (!redo) {
                float L[4] = {0.f, 0.f, 0.f, 0.f};
                float n0, n1;
                {
                    float x0, x1;
                    scores_max(P2, x0, x1);
                    n0 = fmaf(-x0, c, FAST_BIAS);
                    n1 = fmaf(-x1, c, FAST_BIAS);
#pragma unroll
                    for (int i = 0; i < 16; i++) {
                        const float e0 = ex2(fmaf(bf16lo(P2[2 * i]), c, n0));
                        const float e1 = ex2(fmaf(bf16hi(P2[2 * i]), c, n0));
                        const float e2 = ex2(fmaf(bf16lo(P2[2 * i + 1]), c, n1));
                        const float e3 = ex2(fmaf(bf16hi(P2[2 * i + 1]), c, n1));
                        P[2 * i] = pack_bf16(e0, e1);
                        P[2 * i + 1] = pack_bf16(e2, e3);
                    }
                }
                auto issue_pv = [&](uint32_t (&Pc)[32], uint32_t dv) {
                    wgmma_fence();
#pragma unroll
                    for (int kk = 0; kk < 8; kk++) {
                        wgmma_rs_lo_tb(O, Pc[4 * kk], Pc[4 * kk + 1], Pc[4 * kk + 2], Pc[4 * kk + 3], dv + ((kk * 2048) >> 4));
                        wgmma_rs_n8(L, Pc[4 * kk], Pc[4 * kk + 1], Pc[4 * kk + 2], Pc[4 * kk + 3], dones);
                    }
                    wgmma_commit();
                };
                auto expo = [&](uint32_t (&Pn)[32], int i_lo, int i_hi) {
#pragma unroll
                    for (int i = i_lo; i < i_hi; i++) {
                        const uint32_t sa = pack_bf16(S[4 * i], S[4 * i + 1]), sb = pack_bf16(S[4 * i + 2], S[4 * i + 3]);
                        const uint32_t ta = fma_bf16x2(sa, SCALE_HI2, mul_bf16x2(sa, SCALE_LO2));
                        const uint32_t tb = fma_bf16x2(sb, SCALE_HI2, mul_bf16x2(sb, SCALE_LO2));
                        const float e0 = ex2(fmaf(bf16lo(ta), c, n0));
                        const float e1 = ex2(fmaf(bf16hi(ta), c, n0));
                        const float e2 = ex2(fmaf(bf16lo(tb), c, n1));
                        float e3 = ex2(fmaf(bf16hi(tb), c, n1));
                        if (i == i_hi - 1 && i_hi < 16) while (e3 < 0.f) e3 = g_dummy;
                        Pn[2 * i] = pack_bf16(e0, e1);
                        Pn[2 * i + 1] = pack_bf16(e2, e3);
                    }
                };
                auto step = [&](uint32_t (&Pc)[32], uint32_t (&Pn)[32]) {
                    const int ust = __shfl_sync(0xffffffffu, stage, 0), uvs = __shfl_sync(0xffffffffu, vstage, 0);
                    if (!okk) mbar_wait(fk0 + stage * 8, phase);
                    if (!okv) mbar_wait(fv0 + vstage * 8, vphase);
                    PP(named_sync(BAR_SCHED0 + cw, 256));
                    issue_qk(dk0 + ust * (TILE_BYTES >> 4));
                    issue_pv(Pc, dv0 + uvs * (TILE_BYTES >> 4));
                    PP(named_arrive(BAR_SCHED0 + (cw ^ 1), 256));
                    const int pv = vstage;
                    vstage = stage;
                    vphase = phase;
                    if (++stage == AT_STAGES) { stage = 0; phase ^= 1; }
                    okk = mbar_try_wait(fk0 + stage * 8, phase);
                    okv = mbar_try_wait(fv0 + vstage * 8, vphase);
                    wgmma_wait<1>();
                    if (lane == 0) mbar_arrive(ek0 + vstage * 8);
                    expo(Pn, 0, 8);
                    wgmma_wait<0>();
                    if (lane == 0) mbar_arrive(ev0 + pv * 8);
                    expo(Pn, 8, 16);
                };
#pragma unroll 1
                for (int j = 0; j < 7; j++) {
                    step(P, P2);
                    step(P2, P);
                }
                step(P, P2);
                if (!okv) mbar_wait(fv0 + vstage * 8, vphase);
                issue_pv(P2, dv0 + vstage * (TILE_BYTES >> 4));
                wgmma_wait<0>();
                if (lane == 0) mbar_arrive(ev0 + vstage * 8);
                float z = fmaf(L[0], 0.f, L[2] * 0.f);
#pragma unroll
                for (int i = 0; i < 64; i++) z = fmaf(O[i], 0.f, z);
                if (__any_sync(0xffffffffu, z != 0.f) && lane == 0) atomicOr(&sm.redo, 1u << it);
                i0 = 1.0f / L[0];
                i1 = 1.0f / L[2];
            } else {
                float m0 = -INFINITY, m1 = -INFINITY, l0 = 0.f, l1 = 0.f, a0 = 0.f, a1 = 0.f;
                bool resc = false;
                const float TAU = 11.0f;
                float n0, n1;
                auto softmax1 = [&]() {
                    float x0, x1;
                    scores_max(P2, x0, x1);
                    resc = __any_sync(0xffffffffu, (x0 - m0 > TAU) || (x1 - m1 > TAU));
                    x0 = resc ? fmaxf(x0, m0) : m0;
                    x1 = resc ? fmaxf(x1, m1) : m1;
                    a0 = ex2((m0 - x0) * c);
                    a1 = ex2((m1 - x1) * c);
                    m0 = x0;
                    m1 = x1;
                    n0 = -m0 * c;
                    n1 = -m1 * c;
                };
                auto softmax2 = [&]() {
                    float s0 = 0.f, s1 = 0.f;
#pragma unroll
                    for (int i = 0; i < 16; i++) {
                        const float e0 = ex2(fmaf(bf16lo(P2[2 * i]), c, n0));
                        const float e1 = ex2(fmaf(bf16hi(P2[2 * i]), c, n0));
                        const float e2 = ex2(fmaf(bf16lo(P2[2 * i + 1]), c, n1));
                        const float e3 = ex2(fmaf(bf16hi(P2[2 * i + 1]), c, n1));
                        s0 += e0 + e1;
                        s1 += e2 + e3;
                        P[2 * i] = pack_bf16(e0, e1);
                        P[2 * i + 1] = pack_bf16(e2, e3);
                    }
                    l0 = l0 * a0 + s0;
                    l1 = l1 * a1 + s1;
                };
                auto issue_pv = [&](uint32_t dv) {
                    if (resc) {
#pragma unroll
                        for (int i = 0; i < 16; i++) {
                            O[4 * i] *= a0;
                            O[4 * i + 1] *= a0;
                            O[4 * i + 2] *= a1;
                            O[4 * i + 3] *= a1;
                        }
                    }
                    wgmma_fence();
#pragma unroll
                    for (int kk = 0; kk < 8; kk++)
                        wgmma_rs_lo_tb(O, P[4 * kk], P[4 * kk + 1], P[4 * kk + 2], P[4 * kk + 3], dv + ((kk * 2048) >> 4));
                    wgmma_commit();
                };
                softmax1();
                softmax2();
                resc = false;
#pragma unroll 1
                for (int j = 1; j < 16; j++) {
                    mbar_wait(fk0 + stage * 8, phase);
                    mbar_wait(fv0 + vstage * 8, vphase);
                    PP(named_sync(BAR_SCHED0 + cw, 256));
                    issue_qk(dk0 + stage * (TILE_BYTES >> 4));
                    issue_pv(dv0 + vstage * (TILE_BYTES >> 4));
                    PP(named_arrive(BAR_SCHED0 + (cw ^ 1), 256));
                    const int pv = vstage;
                    vstage = stage;
                    vphase = phase;
                    if (++stage == AT_STAGES) { stage = 0; phase ^= 1; }
                    wgmma_wait<0>();
                    if (lane == 0) {
                        mbar_arrive(ek0 + vstage * 8);
                        mbar_arrive(ev0 + pv * 8);
                    }
                    softmax1();
                    softmax2();
                }
                mbar_wait(fv0 + vstage * 8, vphase);
                issue_pv(dv0 + vstage * (TILE_BYTES >> 4));
                wgmma_wait<0>();
                if (lane == 0) mbar_arrive(ev0 + vstage * 8);
                l0 += __shfl_xor_sync(0xffffffffu, l0, 1);
                l1 += __shfl_xor_sync(0xffffffffu, l1, 1);
                l0 += __shfl_xor_sync(0xffffffffu, l0, 2);
                l1 += __shfl_xor_sync(0xffffffffu, l1, 2);
                i0 = 1.0f / l0;
                i1 = 1.0f / l1;
            }
            named_sync(BAR_EPI0 + cw, 128);
#pragma unroll
            for (int i = 0; i < 16; i += 2) {
                const int cc = i + (lane >> 4);
                const uint32_t addr = obase + (cc >> 3) * 8192 + st_row * 128 + (((cc & 7) ^ (st_row & 7)) << 4);
                stmatrix_x4(addr, pack_bf16(O[4 * i] * i0, O[4 * i + 1] * i0), pack_bf16(O[4 * i + 2] * i1, O[4 * i + 3] * i1),
                            pack_bf16(O[4 * i + 4] * i0, O[4 * i + 5] * i0), pack_bf16(O[4 * i + 6] * i1, O[4 * i + 7] * i1));
            }
            fence_proxy_async();
            named_arrive(BAR_ST0 + cw, 160);
            }
            if (!redo && it + 1 == n_items) {
                __syncwarp();
                if (lane == 0) mbar_arrive(smem_u32(&sm.redo_bar));
            }
            if (!next_item()) break;
        }
    }
}

constexpr int OP_STAGES = 4;
constexpr int OP_KSPLIT = 4;
struct __align__(1024) OpSmem {
    uint8_t a[OP_STAGES][128 * 64 * 2];
    uint8_t b[OP_STAGES][64 * 256 * 2];
    uint64_t full[OP_STAGES], empty[OP_STAGES];
};

#define ACC8(d, o) "+f"(d[o]), "+f"(d[o + 1]), "+f"(d[o + 2]), "+f"(d[o + 3]), "+f"(d[o + 4]), "+f"(d[o + 5]), "+f"(d[o + 6]), "+f"(d[o + 7])
__device__ __forceinline__ void wgmma_ss_n256_tb(float (&d)[128], uint64_t da, uint64_t db, int scale_d) {
    asm volatile(
        "{\n.reg .pred p;\nsetp.ne.b32 p, %130, 0;\n"
        "wgmma.mma_async.sync.aligned.m64n256k16.f32.bf16.bf16 "
        "{%0, %1, %2, %3, %4, %5, %6, %7, %8, %9, %10, %11, %12, %13, %14, %15, "
        "%16, %17, %18, %19, %20, %21, %22, %23, %24, %25, %26, %27, %28, %29, %30, %31, "
        "%32, %33, %34, %35, %36, %37, %38, %39, %40, %41, %42, %43, %44, %45, %46, %47, "
        "%48, %49, %50, %51, %52, %53, %54, %55, %56, %57, %58, %59, %60, %61, %62, %63, "
        "%64, %65, %66, %67, %68, %69, %70, %71, %72, %73, %74, %75, %76, %77, %78, %79, "
        "%80, %81, %82, %83, %84, %85, %86, %87, %88, %89, %90, %91, %92, %93, %94, %95, "
        "%96, %97, %98, %99, %100, %101, %102, %103, %104, %105, %106, %107, %108, %109, %110, %111, "
        "%112, %113, %114, %115, %116, %117, %118, %119, %120, %121, %122, %123, %124, %125, %126, %127}, "
        "%128, %129, p, 1, 1, 0, 1;\n}\n"
        : ACC8(d, 0), ACC8(d, 8), ACC8(d, 16), ACC8(d, 24), ACC8(d, 32), ACC8(d, 40), ACC8(d, 48), ACC8(d, 56),
          ACC8(d, 64), ACC8(d, 72), ACC8(d, 80), ACC8(d, 88), ACC8(d, 96), ACC8(d, 104), ACC8(d, 112), ACC8(d, 120)
        : "l"(da), "l"(db), "r"(scale_d));
}
__device__ __forceinline__ void cluster_sync_all() {
    asm volatile("barrier.cluster.arrive.release.aligned;\nbarrier.cluster.wait.acquire.aligned;" ::: "memory");
}

__global__ void __launch_bounds__(384, 1)
oproj_kernel(const __grid_constant__ CUtensorMap tm_o, const __grid_constant__ CUtensorMap tm_wo,
             const bf16* __restrict__ x, bf16* __restrict__ out) {
    extern __shared__ uint8_t smem_raw[];
    OpSmem& sm = *reinterpret_cast<OpSmem*>((reinterpret_cast<uintptr_t>(smem_raw) + 1023) & ~uintptr_t(1023));
    const int tid = threadIdx.x, wg = tid >> 7;
    const int kr = blockIdx.x;
    const int n0 = blockIdx.y * 256, m0 = blockIdx.z * 128;
    const int tile = blockIdx.y + 2 * blockIdx.z;
    constexpr int KT = NH * DH / OP_KSPLIT / 64;
    if (tid == 0) {
        for (int s = 0; s < OP_STAGES; s++) {
            mbar_init(smem_u32(&sm.full[s]), 1);
            mbar_init(smem_u32(&sm.empty[s]), 8);
        }
        asm volatile("fence.mbarrier_init.release.cluster;" ::: "memory");
    }
    __syncthreads();
    if (wg == 0) {
        reg_dealloc<40>();
        if (tid == 0) {
            int stage = 0;
            uint32_t phase = 0;
            for (int kt = 0; kt < KT; kt++) {
                const int kg = kr * KT + kt;
                mbar_wait(smem_u32(&sm.empty[stage]), phase ^ 1);
                mbar_expect_tx(smem_u32(&sm.full[stage]), 49152);
                tma_load_3d(smem_u32(sm.a[stage]), &tm_o, smem_u32(&sm.full[stage]), 0, m0, kg);
                tma_load_3d(smem_u32(sm.b[stage]), &tm_wo, smem_u32(&sm.full[stage]), 0, kg * 64, n0 >> 6);
                if (++stage == OP_STAGES) { stage = 0; phase ^= 1; }
            }
        }
    } else {
        reg_alloc<232>();
        const int cw = wg - 1, lane = tid & 31, warp_in_wg = (tid >> 5) & 3;
        const int ct = tid - 128;
        float acc[128];
        const int r0 = m0 + cw * 64 + warp_in_wg * 16 + (lane >> 2);
        uint32_t xv[16], gv[16];
#pragma unroll
        for (int j = 0; j < 8; j++) {
#pragma unroll
            for (int hh = 0; hh < 2; hh++) {
                const size_t off = (size_t)(r0 + hh * 8) * DM + n0 + kr * 64 + j * 8 + (lane & 3) * 2;
                xv[2 * j + hh] = *reinterpret_cast<const uint32_t*>(x + off);
                gv[2 * j + hh] = *reinterpret_cast<const uint32_t*>(g_g + off);
            }
        }
        int stage = 0, prev = -1;
        uint32_t phase = 0;
#pragma unroll 1
        for (int kt = 0; kt < KT; kt++) {
            mbar_wait(smem_u32(&sm.full[stage]), phase);
            const uint64_t da = make_desc(smem_u32(sm.a[stage]) + cw * 64 * 128, 16, 1024);
            const uint64_t db = make_desc(smem_u32(sm.b[stage]), 8192, 1024);
            wgmma_fence();
#pragma unroll
            for (int kk = 0; kk < 4; kk++)
                wgmma_ss_n256_tb(acc, da + (uint64_t)((kk * 32) >> 4), db + (uint64_t)((kk * 2048) >> 4), (kt | kk) != 0);
            wgmma_commit();
            wgmma_wait<1>();
            if (prev >= 0 && lane == 0) mbar_arrive(smem_u32(&sm.empty[prev]));
            prev = stage;
            if (++stage == OP_STAGES) { stage = 0; phase ^= 1; }
        }
        wgmma_wait<0>();
        float4* part = g_part + (size_t)tile * (OP_KSPLIT * OP_KSPLIT * 8 * 256);
#pragma unroll
        for (int d = 0; d < OP_KSPLIT; d++) {
            if (d == kr) continue;
#pragma unroll
            for (int j = 0; j < 8; j++)
                __stcg(part + ((d * OP_KSPLIT + kr) * 8 + j) * 256 + ct,
                       make_float4(acc[(8 * d + j) * 4], acc[(8 * d + j) * 4 + 1], acc[(8 * d + j) * 4 + 2], acc[(8 * d + j) * 4 + 3]));
        }
        __threadfence();
        named_sync(1, 256);
        if (ct < OP_KSPLIT && ct != kr)
            asm volatile("red.release.gpu.global.add.u32 [%0], 1;" ::"l"(&g_pcnt[tile * OP_KSPLIT + ct]) : "memory");
        float r[32];
#pragma unroll
        for (int d = 0; d < OP_KSPLIT; d++) {
            if (d == kr) {
#pragma unroll
                for (int i = 0; i < 32; i++) r[i] = acc[32 * d + i];
            }
        }
        if (ct == 0) {
            unsigned int v, spins = 0;
            do {
                asm volatile("ld.acquire.gpu.global.u32 %0, [%1];" : "=r"(v) : "l"(&g_pcnt[tile * OP_KSPLIT + kr]) : "memory");
            } while (v < OP_KSPLIT - 1 && ++spins < (1u << 24));
        }
        named_sync(1, 256);
#pragma unroll
        for (int sr = 0; sr < OP_KSPLIT; sr++) {
            if (sr == kr) continue;
#pragma unroll
            for (int j = 0; j < 8; j++) {
                const float4 v = __ldcg(part + ((kr * OP_KSPLIT + sr) * 8 + j) * 256 + ct);
                r[4 * j] += v.x;
                r[4 * j + 1] += v.y;
                r[4 * j + 2] += v.z;
                r[4 * j + 3] += v.w;
            }
        }
#pragma unroll
        for (int j = 0; j < 8; j++) {
#pragma unroll
            for (int hh = 0; hh < 2; hh++) {
                const size_t off = (size_t)(r0 + hh * 8) * DM + n0 + kr * 64 + j * 8 + (lane & 3) * 2;
                const float s0 = bf16_round(r[4 * j + 2 * hh]), s1 = bf16_round(r[4 * j + 2 * hh + 1]);
                const float o0 = bf16lo(xv[2 * j + hh]) + bf16_round(s0 * bf16lo(gv[2 * j + hh]));
                const float o1 = bf16hi(xv[2 * j + hh]) + bf16_round(s1 * bf16hi(gv[2 * j + hh]));
                *reinterpret_cast<uint32_t*>(out + off) = pack_bf16(o0, o1);
            }
        }
    }
}

typedef CUresult (*EncodeFn)(CUtensorMap*, CUtensorMapDataType, cuuint32_t, void*, const cuuint64_t*, const cuuint64_t*,
                             const cuuint32_t*, const cuuint32_t*, CUtensorMapInterleave, CUtensorMapSwizzle,
                             CUtensorMapL2promotion, CUtensorMapFloatOOBfill);

static CUtensorMap make_map(EncodeFn fn, const void* ptr, uint64_t rows, uint64_t cols, uint32_t box_rows, uint32_t box_blk) {
    CUtensorMap m;
    cuuint64_t dims[3] = {64, rows, cols / 64};
    cuuint64_t strides[2] = {cols * 2, 128};
    cuuint32_t box[3] = {64, box_rows, box_blk};
    cuuint32_t es[3] = {1, 1, 1};
    fn(&m, CU_TENSOR_MAP_DATA_TYPE_BFLOAT16, 3, const_cast<void*>(ptr), dims, strides, box, es, CU_TENSOR_MAP_INTERLEAVE_NONE,
       CU_TENSOR_MAP_SWIZZLE_128B, CU_TENSOR_MAP_L2_PROMOTION_L2_256B, CU_TENSOR_MAP_FLOAT_OOB_FILL_NONE);
    return m;
}

extern "C" void kernel_launch(void* const* d_in, const int* in_sizes, int n_in, void* d_out, int out_size) {
    const bf16* x = (const bf16*)d_in[0];
    const bf16* kc = (const bf16*)d_in[1];
    const bf16* vc = (const bf16*)d_in[2];
    const bf16* wq = (const bf16*)d_in[3];
    const bf16* wo = (const bf16*)d_in[4];
    const bf16* w1 = (const bf16*)d_in[6];
    const bf16* w2 = (const bf16*)d_in[7];
    bf16* out = (bf16*)d_out;

    static EncodeFn fn = nullptr;
    static void *p_xn = nullptr, *p_h = nullptr, *p_o = nullptr, *p_g = nullptr;
    static Sched sched;
    if (!fn) {
        void* f = nullptr;
        cudaDriverEntryPointQueryResult st;
        cudaGetDriverEntryPoint("cuTensorMapEncodeTiled", &f, cudaEnableDefault, &st);
        fn = (EncodeFn)f;
        cudaGetSymbolAddress(&p_xn, g_xn);
        cudaGetSymbolAddress(&p_h, g_h);
        cudaGetSymbolAddress(&p_o, g_o);
        cudaGetSymbolAddress(&p_g, g_g);
        cudaFuncSetAttribute(attn_kernel, cudaFuncAttributeMaxDynamicSharedMemorySize, (int)sizeof(AttnSmem) + 1024);
        cudaFuncSetAttribute(oproj_kernel, cudaFuncAttributeMaxDynamicSharedMemorySize, (int)sizeof(OpSmem) + 1024);
        static uint16_t f1[NUM_CTAS][MAX_ITEMS], at[NUM_CTAS][MAX_ITEMS], f2[NUM_CTAS][MAX_ITEMS];
        static int n1[NUM_CTAS], na[NUM_CTAS], n2[NUM_CTAS];
        static double load[NUM_CTAS];
        const double C_ATT = 58.0, C_F1 = 6.5, C_F2 = 19.5;
        for (int i = 0; i < NUM_CTAS; i++) { n1[i] = na[i] = n2[i] = 0; load[i] = 0; }
        for (int t = 0; t < NH * 16; t++) {
            int cta = t % NUM_CTAS;
            at[cta][na[cta]++] = (uint16_t)((T_ATT << 12) | ((t >> 4) << 4) | (t & 15));
            load[cta] += C_ATT;
        }
        auto least = [&]() { int bi = 0; for (int i = 1; i < NUM_CTAS; i++) if (load[i] < load[bi]) bi = i; return bi; };
        for (int t = 0; t < 64; t++) {
            int cta = least();
            f2[cta][n2[cta]++] = (uint16_t)((T_F2 << 12) | ((t & 3) << 4) | (t >> 2));
            load[cta] += C_F2;
        }
        for (int t = 0; t < 224; t++) {
            int cta = least();
            f1[cta][n1[cta]++] = (uint16_t)((T_F1 << 12) | ((t % 14) << 4) | (t / 14));
            load[cta] += C_F1;
        }
        for (int i = 0; i < NUM_CTAS; i++) {
            int n = 0;
            for (int j = 0; j < n1[i]; j++) sched.item[i][n++] = f1[i][j];
            for (int j = 0; j < na[i]; j++) sched.item[i][n++] = at[i][j];
            for (int j = 0; j < n2[i]; j++) sched.item[i][n++] = f2[i][j];
            sched.count[i] = (uint8_t)n;
        }
    }
    CUtensorMap tm_xn_at = make_map(fn, p_xn, SEQ, DM, 128, 2);
    CUtensorMap tm_wq = make_map(fn, wq, DM, NH * DH, 128, 2);
    CUtensorMap tm_k = make_map(fn, kc, NH * SEQ, DH, 128, 2);
    CUtensorMap tm_v = make_map(fn, vc, NH * SEQ, DH, 128, 2);
    CUtensorMap tm_o_st = make_map(fn, p_o, SEQ, NH * DH, 64, 2);
    CUtensorMap tm_w1 = make_map(fn, w1, DM, FF, 128, 2);
    CUtensorMap tm_h_st = make_map(fn, p_h, SEQ, FF, 64, 2);
    CUtensorMap tm_h_ld = make_map(fn, p_h, SEQ, FF, 128, 2);
    CUtensorMap tm_w2 = make_map(fn, w2, FF, DM, 128, 2);
    CUtensorMap tm_g_st = make_map(fn, p_g, SEQ, DM, 64, 2);
    CUtensorMap tm_o_g = make_map(fn, p_o, SEQ, NH * DH, 128, 1);
    CUtensorMap tm_wo = make_map(fn, wo, NH * DH, DM, 64, 4);

    ln_kernel<<<SEQ / 8, 256>>>(x);
    attn_kernel<<<NUM_CTAS, 384, sizeof(AttnSmem) + 1024>>>(tm_xn_at, tm_wq, tm_k, tm_v, tm_o_st, tm_w1, tm_h_st, tm_h_ld,
                                                            tm_w2, tm_g_st, sched);
    oproj_kernel<<<dim3(OP_KSPLIT, DM / 256, SEQ / 128), 384, sizeof(OpSmem) + 1024>>>(tm_o_g, tm_wo, x, out);
}
```

```cpp
#include <cuda_runtime.h>
#include <cuda_bf16.h>
#include <cuda.h>
#include <stdint.h>

typedef __nv_bfloat16 bf16;
#define PP(x) x

constexpr int SEQ = 2048, DM = 512, NH = 32, DH = 128, FF = 1792;

__device__ __align__(1024) bf16 g_xn[SEQ * DM];
__device__ __align__(1024) bf16 g_h[SEQ * FF];
__device__ __align__(1024) bf16 g_o[SEQ * NH * DH];
__device__ __align__(1024) bf16 g_g[SEQ * DM];
constexpr int C_H = 0, C_O = 16, C_G = C_O + 64, C_CLAIM = C_G + 64, C_P = C_CLAIM + 32, C_TICKET = C_P + 128;
__device__ unsigned int g_cnt[512];
__device__ float4 g_part[32 * 16 * 8 * 256];
__device__ volatile float g_dummy;

__device__ __forceinline__ uint32_t smem_u32(const void* p) { return (uint32_t)__cvta_generic_to_shared(p); }

__device__ __forceinline__ void mbar_init(uint32_t bar, uint32_t count) {
    asm volatile("mbarrier.init.shared::cta.b64 [%0], %1;" ::"r"(bar), "r"(count) : "memory");
}
__device__ __forceinline__ void mbar_expect_tx(uint32_t bar, uint32_t bytes) {
    asm volatile("mbarrier.arrive.expect_tx.shared::cta.b64 _, [%0], %1;" ::"r"(bar), "r"(bytes) : "memory");
}
__device__ __forceinline__ void mbar_arrive(uint32_t bar) {
    asm volatile("mbarrier.arrive.shared::cta.b64 _, [%0];" ::"r"(bar) : "memory");
}
__device__ __forceinline__ bool mbar_try_wait(uint32_t bar, uint32_t parity) {
    uint32_t ok;
    asm volatile(
        "{\n.reg .pred p;\n"
        "mbarrier.test_wait.parity.shared::cta.b64 p, [%1], %2;\n"
        "selp.u32 %0, 1, 0, p;\n}\n"
        : "=r"(ok)
        : "r"(bar), "r"(parity)
        : "memory");
    return ok != 0;
}
__device__ __forceinline__ void mbar_wait(uint32_t bar, uint32_t parity) {
    asm volatile(
        "{\n.reg .pred P1;\n.reg .u32 n;\nmov.u32 n, 0;\n"
        "LAB_WAIT:\n"
        "mbarrier.try_wait.parity.shared::cta.b64 P1, [%0], %1;\n"
        "@P1 bra DONE;\n"
        "add.u32 n, n, 1;\n"
        "setp.lt.u32 P1, n, 4194304;\n"
        "@P1 bra LAB_WAIT;\n"
        "trap;\n"
        "DONE:\n}\n" ::"r"(bar), "r"(parity)
        : "memory");
}
__device__ __forceinline__ void tma_load_3d(uint32_t dst, const CUtensorMap* map, uint32_t bar, int c0, int c1, int c2) {
    asm volatile(
        "cp.async.bulk.tensor.3d.shared::cluster.global.mbarrier::complete_tx::bytes [%0], [%1, {%3, %4, %5}], [%2];"
        ::"r"(dst), "l"((uint64_t)map), "r"(bar), "r"(c0), "r"(c1), "r"(c2)
        : "memory");
}
__device__ __forceinline__ void tma_store_3d(const CUtensorMap* map, uint32_t src, int c0, int c1, int c2) {
    asm volatile("cp.async.bulk.tensor.3d.global.shared::cta.bulk_group [%0, {%2, %3, %4}], [%1];"
                 ::"l"((uint64_t)map), "r"(src), "r"(c0), "r"(c1), "r"(c2)
                 : "memory");
}
__device__ __forceinline__ void tma_commit() { asm volatile("cp.async.bulk.commit_group;" ::: "memory"); }
__device__ __forceinline__ void tma_wait_read0() { asm volatile("cp.async.bulk.wait_group.read 0;" ::: "memory"); }
__device__ __forceinline__ void tma_wait_all0() { asm volatile("cp.async.bulk.wait_group 0;" ::: "memory"); }
__device__ __forceinline__ void fence_proxy_async() { asm volatile("fence.proxy.async.shared::cta;" ::: "memory"); }
__device__ __forceinline__ void prefetch_tmap(const CUtensorMap* map) {
    asm volatile("prefetch.tensormap [%0];" ::"l"((uint64_t)map) : "memory");
}
__device__ __forceinline__ void pdl_wait() { asm volatile("griddepcontrol.wait;" ::: "memory"); }
__device__ __forceinline__ void pdl_launch() { asm volatile("griddepcontrol.launch_dependents;" ::: "memory"); }
__device__ __forceinline__ void named_sync(int id, int n) { asm volatile("bar.sync %0, %1;" ::"r"(id), "r"(n) : "memory"); }
__device__ __forceinline__ void named_arrive(int id, int n) { asm volatile("bar.arrive %0, %1;" ::"r"(id), "r"(n) : "memory"); }

__device__ __forceinline__ void wgmma_fence() { asm volatile("wgmma.fence.sync.aligned;" ::: "memory"); }
__device__ __forceinline__ void wgmma_commit() { asm volatile("wgmma.commit_group.sync.aligned;" ::: "memory"); }
template <int N>
__device__ __forceinline__ void wgmma_wait() { asm volatile("wgmma.wait_group.sync.aligned %0;" ::"n"(N) : "memory"); }

template <int R>
__device__ __forceinline__ void reg_alloc() { asm volatile("setmaxnreg.inc.sync.aligned.u32 %0;" ::"n"(R)); }
template <int R>
__device__ __forceinline__ void reg_dealloc() { asm volatile("setmaxnreg.dec.sync.aligned.u32 %0;" ::"n"(R)); }

__device__ __forceinline__ uint64_t make_desc(uint32_t saddr, uint32_t lbo_bytes, uint32_t sbo_bytes) {
    uint64_t d = 0;
    d |= (uint64_t)((saddr & 0x3FFFF) >> 4);
    d |= (uint64_t)((lbo_bytes >> 4) & 0x3FFF) << 16;
    d |= (uint64_t)((sbo_bytes >> 4) & 0x3FFF) << 32;
    d |= (uint64_t)1 << 62;
    return d;
}

__device__ __forceinline__ float ex2(float x) {
    float y;
    asm volatile("ex2.approx.ftz.f32 %0, %1;" : "=f"(y) : "f"(x));
    return y;
}
__device__ __forceinline__ uint32_t pack_bf16(float lo, float hi) {
    uint32_t r;
    asm("cvt.rn.bf16x2.f32 %0, %1, %2;" : "=r"(r) : "f"(hi), "f"(lo));
    return r;
}
__device__ __forceinline__ uint32_t mul_bf16x2(uint32_t a, uint32_t b) {
    uint32_t r;
    asm("mul.rn.bf16x2 %0, %1, %2;" : "=r"(r) : "r"(a), "r"(b));
    return r;
}
__device__ __forceinline__ uint32_t fma_bf16x2(uint32_t a, uint32_t b, uint32_t c) {
    uint32_t r;
    asm("fma.rn.bf16x2 %0, %1, %2, %3;" : "=r"(r) : "r"(a), "r"(b), "r"(c));
    return r;
}
__device__ __forceinline__ uint32_t max_bf16x2(uint32_t a, uint32_t b) {
    uint32_t r;
    asm("max.bf16x2 %0, %1, %2;" : "=r"(r) : "r"(a), "r"(b));
    return r;
}
__device__ __forceinline__ float bf16lo(uint32_t v) { return __uint_as_float(v << 16); }
__device__ __forceinline__ float bf16hi(uint32_t v) { return __uint_as_float(v & 0xffff0000u); }
__device__ __forceinline__ float bf16_round(float x) { return __bfloat162float(__float2bfloat16_rn(x)); }
__device__ __forceinline__ float silu_f(float x) {
    const float h = 0.5f * x;
    float t;
    asm("tanh.approx.f32 %0, %1;" : "=f"(t) : "f"(h));
    return fmaf(h, t, h);
}

__device__ __forceinline__ void stmatrix_x4(uint32_t addr, uint32_t r0, uint32_t r1, uint32_t r2, uint32_t r3) {
    asm volatile("stmatrix.sync.aligned.m8n8.x4.shared.b16 [%0], {%1, %2, %3, %4};"
                 ::"r"(addr), "r"(r0), "r"(r1), "r"(r2), "r"(r3)
                 : "memory");
}

#define ACC64(d) \
    "+f"(d[0]), "+f"(d[1]), "+f"(d[2]), "+f"(d[3]), "+f"(d[4]), "+f"(d[5]), "+f"(d[6]), "+f"(d[7]), \
    "+f"(d[8]), "+f"(d[9]), "+f"(d[10]), "+f"(d[11]), "+f"(d[12]), "+f"(d[13]), "+f"(d[14]), "+f"(d[15]), \
    "+f"(d[16]), "+f"(d[17]), "+f"(d[18]), "+f"(d[19]), "+f"(d[20]), "+f"(d[21]), "+f"(d[22]), "+f"(d[23]), \
    "+f"(d[24]), "+f"(d[25]), "+f"(d[26]), "+f"(d[27]), "+f"(d[28]), "+f"(d[29]), "+f"(d[30]), "+f"(d[31]), \
    "+f"(d[32]), "+f"(d[33]), "+f"(d[34]), "+f"(d[35]), "+f"(d[36]), "+f"(d[37]), "+f"(d[38]), "+f"(d[39]), \
    "+f"(d[40]), "+f"(d[41]), "+f"(d[42]), "+f"(d[43]), "+f"(d[44]), "+f"(d[45]), "+f"(d[46]), "+f"(d[47]), \
    "+f"(d[48]), "+f"(d[49]), "+f"(d[50]), "+f"(d[51]), "+f"(d[52]), "+f"(d[53]), "+f"(d[54]), "+f"(d[55]), \
    "+f"(d[56]), "+f"(d[57]), "+f"(d[58]), "+f"(d[59]), "+f"(d[60]), "+f"(d[61]), "+f"(d[62]), "+f"(d[63])

#define ACC64_STR \
    "{%0, %1, %2, %3, %4, %5, %6, %7, %8, %9, %10, %11, %12, %13, %14, %15, " \
    "%16, %17, %18, %19, %20, %21, %22, %23, %24, %25, %26, %27, %28, %29, %30, %31, " \
    "%32, %33, %34, %35, %36, %37, %38, %39, %40, %41, %42, %43, %44, %45, %46, %47, " \
    "%48, %49, %50, %51, %52, %53, %54, %55, %56, %57, %58, %59, %60, %61, %62, %63}"

template <int TB>
__device__ __forceinline__ void wgmma_ss_n128(float (&d)[64], uint64_t da, uint64_t db, int scale_d) {
    asm volatile(
        "{\n.reg .pred p;\nsetp.ne.b32 p, %66, 0;\n"
        "wgmma.mma_async.sync.aligned.m64n128k16.f32.bf16.bf16 " ACC64_STR ", %64, %65, p, 1, 1, 0, %67;\n}\n"
        : ACC64(d)
        : "l"(da), "l"(db), "r"(scale_d), "n"(TB));
}
template <int TB>
__device__ __forceinline__ void wgmma_rs_n128(float (&d)[64], uint32_t a0, uint32_t a1, uint32_t a2, uint32_t a3,
                                              uint64_t db, int scale_d) {
    asm volatile(
        "{\n.reg .pred p;\nsetp.ne.b32 p, %69, 0;\n"
        "wgmma.mma_async.sync.aligned.m64n128k16.f32.bf16.bf16 " ACC64_STR ", {%64, %65, %66, %67}, %68, p, 1, 1, %70;\n}\n"
        : ACC64(d)
        : "r"(a0), "r"(a1), "r"(a2), "r"(a3), "l"(db), "r"(scale_d), "n"(TB));
}

constexpr uint32_t DESC_HI = 0x40000040u;
__device__ __forceinline__ uint32_t desc_lo(uint32_t saddr, uint32_t lbo_bytes) {
    return ((saddr & 0x3FFFF) >> 4) | ((lbo_bytes >> 4) << 16);
}
template <int TB>
__device__ __forceinline__ void wgmma_ss_lo(float (&d)[64], uint32_t da, uint32_t db, int scale_d) {
    asm volatile(
        "{\n.reg .pred p;\n.reg .b64 xa, xb;\nsetp.ne.b32 p, %66, 0;\n"
        "mov.b64 xa, {%64, %68};\nmov.b64 xb, {%65, %68};\n"
        "wgmma.mma_async.sync.aligned.m64n128k16.f32.bf16.bf16 " ACC64_STR ", xa, xb, p, 1, 1, 0, %67;\n}\n"
        : ACC64(d)
        : "r"(da), "r"(db), "r"(scale_d), "n"(TB), "r"(DESC_HI));
}
__device__ __forceinline__ void wgmma_rs_lo_tb(float (&d)[64], uint32_t a0, uint32_t a1, uint32_t a2, uint32_t a3, uint32_t db) {
    asm volatile(
        "{\n.reg .b64 xb;\nmov.b64 xb, {%68, %69};\n"
        "wgmma.mma_async.sync.aligned.m64n128k16.f32.bf16.bf16 " ACC64_STR ", {%64, %65, %66, %67}, xb, 1, 1, 1, 1;\n}\n"
        : ACC64(d)
        : "r"(a0), "r"(a1), "r"(a2), "r"(a3), "r"(db), "r"(DESC_HI));
}

#define ACC8(d, o) "+f"(d[o]), "+f"(d[o + 1]), "+f"(d[o + 2]), "+f"(d[o + 3]), "+f"(d[o + 4]), "+f"(d[o + 5]), "+f"(d[o + 6]), "+f"(d[o + 7])
__device__ __forceinline__ void wgmma_rs_n64(float (&d)[64], uint32_t a0, uint32_t a1, uint32_t a2, uint32_t a3, uint32_t db) {
    asm volatile(
        "{\n.reg .b64 xb;\nmov.b64 xb, {%36, %37};\n"
        "wgmma.mma_async.sync.aligned.m64n64k16.f32.bf16.bf16 "
        "{%0, %1, %2, %3, %4, %5, %6, %7, %8, %9, %10, %11, %12, %13, %14, %15, "
        "%16, %17, %18, %19, %20, %21, %22, %23, %24, %25, %26, %27, %28, %29, %30, %31}, "
        "{%32, %33, %34, %35}, xb, 1, 1, 1, 1;\n}\n"
        : ACC8(d, 0), ACC8(d, 8), ACC8(d, 16), ACC8(d, 24)
        : "r"(a0), "r"(a1), "r"(a2), "r"(a3), "r"(db), "r"(DESC_HI));
}
__device__ __forceinline__ void wgmma_rs_n72(float (&d)[64], float (&l)[4], uint32_t a0, uint32_t a1, uint32_t a2, uint32_t a3, uint32_t db) {
    asm volatile(
        "{\n.reg .b64 xb;\nmov.b64 xb, {%40, %41};\n"
        "wgmma.mma_async.sync.aligned.m64n72k16.f32.bf16.bf16 "
        "{%0, %1, %2, %3, %4, %5, %6, %7, %8, %9, %10, %11, %12, %13, %14, %15, "
        "%16, %17, %18, %19, %20, %21, %22, %23, %24, %25, %26, %27, %28, %29, %30, %31, %32, %33, %34, %35}, "
        "{%36, %37, %38, %39}, xb, 1, 1, 1, 1;\n}\n"
        : ACC8(d, 32), ACC8(d, 40), ACC8(d, 48), ACC8(d, 56), "+f"(l[0]), "+f"(l[1]), "+f"(l[2]), "+f"(l[3])
        : "r"(a0), "r"(a1), "r"(a2), "r"(a3), "r"(db), "r"(DESC_HI));
}

__device__ __forceinline__ void wgmma_ss_n256_tb(float (&d)[128], uint64_t da, uint64_t db, int scale_d) {
    asm volatile(
        "{\n.reg .pred p;\nsetp.ne.b32 p, %130, 0;\n"
        "wgmma.mma_async.sync.aligned.m64n256k16.f32.bf16.bf16 "
        "{%0, %1, %2, %3, %4, %5, %6, %7, %8, %9, %10, %11, %12, %13, %14, %15, "
        "%16, %17, %18, %19, %20, %21, %22, %23, %24, %25, %26, %27, %28, %29, %30, %31, "
        "%32, %33, %34, %35, %36, %37, %38, %39, %40, %41, %42, %43, %44, %45, %46, %47, "
        "%48, %49, %50, %51, %52, %53, %54, %55, %56, %57, %58, %59, %60, %61, %62, %63, "
        "%64, %65, %66, %67, %68, %69, %70, %71, %72, %73, %74, %75, %76, %77, %78, %79, "
        "%80, %81, %82, %83, %84, %85, %86, %87, %88, %89, %90, %91, %92, %93, %94, %95, "
        "%96, %97, %98, %99, %100, %101, %102, %103, %104, %105, %106, %107, %108, %109, %110, %111, "
        "%112, %113, %114, %115, %116, %117, %118, %119, %120, %121, %122, %123, %124, %125, %126, %127}, "
        "%128, %129, p, 1, 1, 0, 1;\n}\n"
        : ACC8(d, 0), ACC8(d, 8), ACC8(d, 16), ACC8(d, 24), ACC8(d, 32), ACC8(d, 40), ACC8(d, 48), ACC8(d, 56),
          ACC8(d, 64), ACC8(d, 72), ACC8(d, 80), ACC8(d, 88), ACC8(d, 96), ACC8(d, 104), ACC8(d, 112), ACC8(d, 120)
        : "l"(da), "l"(db), "r"(scale_d));
}

__global__ void __launch_bounds__(256) ln_kernel(const bf16* __restrict__ x) {
    pdl_launch();
    int warp = threadIdx.x >> 5, lane = threadIdx.x & 31;
    int row = blockIdx.x * 8 + warp;
    if (blockIdx.x < 2) g_cnt[blockIdx.x * 256 + threadIdx.x] = 0;
    const uint4* src = reinterpret_cast<const uint4*>(x + (size_t)row * DM);
    uint4 v[2];
    v[0] = src[lane];
    v[1] = src[lane + 32];
    float f[16];
#pragma unroll
    for (int i = 0; i < 2; i++) {
        const __nv_bfloat162* p = reinterpret_cast<const __nv_bfloat162*>(&v[i]);
#pragma unroll
        for (int j = 0; j < 4; j++) {
            float2 t = __bfloat1622float2(p[j]);
            f[i * 8 + j * 2] = t.x;
            f[i * 8 + j * 2 + 1] = t.y;
        }
    }
    float s = 0.f;
#pragma unroll
    for (int i = 0; i < 16; i++) s += f[i];
#pragma unroll
    for (int o = 16; o > 0; o >>= 1) s += __shfl_xor_sync(0xffffffffu, s, o);
    float mean = s * (1.0f / DM);
    float q = 0.f;
#pragma unroll
    for (int i = 0; i < 16; i++) {
        float d = f[i] - mean;
        q += d * d;
    }
#pragma unroll
    for (int o = 16; o > 0; o >>= 1) q += __shfl_xor_sync(0xffffffffu, q, o);
    float var_b = bf16_round(q * (1.0f / DM));
    float mean_b = bf16_round(mean);
    float den = bf16_round(sqrtf(bf16_round(var_b + 1e-5f)));
    uint4 o[2];
#pragma unroll
    for (int i = 0; i < 2; i++) {
        uint32_t* p = reinterpret_cast<uint32_t*>(&o[i]);
#pragma unroll
        for (int j = 0; j < 4; j++) {
            float a = bf16_round(f[i * 8 + j * 2] - mean_b) / den;
            float b = bf16_round(f[i * 8 + j * 2 + 1] - mean_b) / den;
            p[j] = pack_bf16(a, b);
        }
    }
    uint4* dst = reinterpret_cast<uint4*>(g_xn + (size_t)row * DM);
    dst[lane] = o[0];
    dst[lane + 32] = o[1];
}

constexpr int AT_STAGES = 3;
constexpr int TILE_BYTES = 128 * 128 * 2;
constexpr int OP_STAGES = 4, OP_KSPLIT = 4, OP_KT = NH * DH / 64;
struct __align__(1024) AttnSmem {
    uint8_t k[AT_STAGES][TILE_BYTES];
    uint8_t v[AT_STAGES][TILE_BYTES];
    uint8_t o[TILE_BYTES];
    uint32_t ones0[4];
    uint64_t full_k[AT_STAGES], full_v[AT_STAGES], empty_k[AT_STAGES], empty_v[AT_STAGES];
    uint64_t st_free[2];
    uint64_t redo_bar;
    uint32_t redo;
    uint32_t pad0;
    uint32_t ones1[4];
    uint64_t op_full[OP_STAGES], op_empty[OP_STAGES];
    uint32_t op_last[OP_STAGES], ticket, pad1[11];
    uint32_t ones2[(2048 - 288) / 4];
};

#define EXPO(x) x
#define N8(x) x
#define PPK 8
#define FAST_BIAS (-40.0f)
constexpr int NUM_CTAS = 132;
constexpr int MAX_ITEMS = 12;
enum { T_ATT = 0, T_F1 = 1, T_F2 = 2 };
struct Sched {
    uint16_t item[NUM_CTAS][MAX_ITEMS];
    uint8_t count[NUM_CTAS];
};

__global__ void __launch_bounds__(384, 1)
attn_kernel(const __grid_constant__ CUtensorMap tm_xn, const __grid_constant__ CUtensorMap tm_wq,
            const __grid_constant__ CUtensorMap tm_k, const __grid_constant__ CUtensorMap tm_v,
            const __grid_constant__ CUtensorMap tm_o, const __grid_constant__ CUtensorMap tm_w1,
            const __grid_constant__ CUtensorMap tm_hst, const __grid_constant__ CUtensorMap tm_hld,
            const __grid_constant__ CUtensorMap tm_w2, const __grid_constant__ CUtensorMap tm_gst,
            const __grid_constant__ CUtensorMap tm_old, const __grid_constant__ CUtensorMap tm_wo,
            const bf16* __restrict__ x, bf16* __restrict__ out, const __grid_constant__ Sched sched) {
    extern __shared__ uint8_t smem_raw[];
    AttnSmem& sm = *reinterpret_cast<AttnSmem*>((reinterpret_cast<uintptr_t>(smem_raw) + 1023) & ~uintptr_t(1023));
    const int tid = threadIdx.x;
    const int wg = __shfl_sync(0xffffffffu, tid >> 7, 0);
    const int n_items = sched.count[blockIdx.x];
    if (tid == 32) {
        prefetch_tmap(&tm_xn); prefetch_tmap(&tm_wq); prefetch_tmap(&tm_k); prefetch_tmap(&tm_v); prefetch_tmap(&tm_o);
        prefetch_tmap(&tm_w1); prefetch_tmap(&tm_hst); prefetch_tmap(&tm_hld); prefetch_tmap(&tm_w2); prefetch_tmap(&tm_gst);
        prefetch_tmap(&tm_old); prefetch_tmap(&tm_wo);
    }

    if (tid == 0) {
#pragma unroll
        for (int s = 0; s < AT_STAGES; s++) {
            mbar_init(smem_u32(&sm.full_k[s]), 1);
            mbar_init(smem_u32(&sm.full_v[s]), 1);
            mbar_init(smem_u32(&sm.empty_k[s]), 8);
            mbar_init(smem_u32(&sm.empty_v[s]), 8);
        }
        mbar_init(smem_u32(&sm.st_free[0]), 1);
        mbar_init(smem_u32(&sm.st_free[1]), 1);
        mbar_init(smem_u32(&sm.redo_bar), 8);
#pragma unroll
        for (int s = 0; s < OP_STAGES; s++) {
            mbar_init(smem_u32(&sm.op_full[s]), 1);
            mbar_init(smem_u32(&sm.op_empty[s]), 8);
        }
        sm.redo = 0;
        asm volatile("fence.mbarrier_init.release.cluster;" ::: "memory");
    }
    if (tid < 64) {
        const int r = tid >> 2;
        sm.ones0[(r >> 3) * 256 + (r & 7) * 36 + (tid & 3)] = 0x3F803F80u;
        fence_proxy_async();
    }
    __syncthreads();
    pdl_wait();
    int it = 0;
    uint32_t rmask = 0;
    bool redo = false;
    auto next_item = [&]() -> bool {
        if (!redo) {
            if (++it < n_items) return true;
            mbar_wait(smem_u32(&sm.redo_bar), 0);
            rmask = *reinterpret_cast<volatile uint32_t*>(&sm.redo);
            rmask = (rmask | (rmask >> 16)) & 0xffffu;
            redo = true;
        }
        if (!rmask) return false;
        it = __ffs(rmask) - 1;
        rmask &= rmask - 1;
        return true;
    };
    constexpr int BAR_SCHED0 = 1, BAR_EPI0 = 3, BAR_ST0 = 5, BAR_OP = 7;

    if (wg == 0) {
        reg_dealloc<40>();
        if (tid >= 32 && tid < 96) {
            const int cw = (tid >> 5) - 1;
            const uint32_t obase = smem_u32(sm.o) + cw * 16384;
            do {
                const int item = sched.item[blockIdx.x][it];
                const int type = item >> 12, a = (item >> 4) & 0xff, b = item & 15;
                named_sync(BAR_ST0 + cw, 160);
                if ((tid & 31) == 0) {
                    if (redo) tma_wait_all0();
                    tma_store_3d(type == T_ATT ? &tm_o : (type == T_F1 ? &tm_hst : &tm_gst), obase, 0, b * 128 + cw * 64, a * 2);
                    tma_commit();
                    tma_wait_read0();
                    mbar_arrive(smem_u32(&sm.st_free[cw]));
                    const bool bad = (*reinterpret_cast<volatile uint32_t*>(&sm.redo) >> (16 * cw + it)) & 1;
                    if (bad == redo) {
                        tma_wait_all0();
                        asm volatile("fence.proxy.async;" ::: "memory");
                        __threadfence();
                        atomicAdd(&g_cnt[type == T_ATT ? C_O + b * 4 + (a >> 3) : (type == T_F1 ? C_H + b : C_G + b * 4 + a)], 1u);
                    }
                }
                __syncwarp();
            } while (next_item());
            if ((tid & 31) == 0) tma_wait_all0();
        }
        if (tid == 0) {
            int stage = 0;
            uint32_t phase = 0;
            unsigned int ticket = 0, n1 = 0, gok = 0;
            do {
                const int item = sched.item[blockIdx.x][it];
                const int type = item >> 12, a = (item >> 4) & 0xff, b = item & 15;
                const CUtensorMap* ta = (type == T_F2) ? &tm_hld : &tm_xn;
                const CUtensorMap* tb = (type == T_ATT) ? &tm_wq : (type == T_F1 ? &tm_w1 : &tm_w2);
                const int nch = (type == T_F2) ? FF / 128 : DM / 128;
                if (type == T_F2) {
                    unsigned int v, spins = 0;
                    do {
                        asm volatile("ld.acquire.gpu.global.u32 %0, [%1];" : "=r"(v) : "l"(&g_cnt[C_H + b]) : "memory");
                    } while (v < 2 * (FF / 128) && ++spins < (1u << 24));
                    asm volatile("fence.proxy.async;" ::: "memory");
                }
                for (int kc = 0; kc < nch; kc++) {
                    mbar_wait(smem_u32(&sm.empty_k[stage]), phase ^ 1);
                    mbar_expect_tx(smem_u32(&sm.full_k[stage]), TILE_BYTES);
                    tma_load_3d(smem_u32(sm.k[stage]), ta, smem_u32(&sm.full_k[stage]), 0, b * 128, kc * 2);
                    mbar_wait(smem_u32(&sm.empty_v[stage]), phase ^ 1);
                    mbar_expect_tx(smem_u32(&sm.full_v[stage]), TILE_BYTES);
                    tma_load_3d(smem_u32(sm.v[stage]), tb, smem_u32(&sm.full_v[stage]), 0, kc * 128, a * 2);
                    if (++stage == AT_STAGES) { stage = 0; phase ^= 1; }
                }
                if (type == T_ATT) {
                    for (int j = 0; j < 16; j++) {
                        mbar_wait(smem_u32(&sm.empty_k[stage]), phase ^ 1);
                        mbar_expect_tx(smem_u32(&sm.full_k[stage]), TILE_BYTES);
                        tma_load_3d(smem_u32(sm.k[stage]), &tm_k, smem_u32(&sm.full_k[stage]), 0, a * SEQ + j * 128, 0);
                        mbar_wait(smem_u32(&sm.empty_v[stage]), phase ^ 1);
                        mbar_expect_tx(smem_u32(&sm.full_v[stage]), TILE_BYTES);
                        tma_load_3d(smem_u32(sm.v[stage]), &tm_v, smem_u32(&sm.full_v[stage]), 0, a * SEQ + j * 128, 0);
                        if (++stage == AT_STAGES) { stage = 0; phase ^= 1; }
                    }
                }
                if (!redo && it + 1 == n_items) {
                    ticket = atomicAdd(&g_cnt[C_TICKET], 1u);
                    n1 = atomicAdd(&g_cnt[C_CLAIM + (ticket & 31)], ticket < 32 * OP_KSPLIT ? 2u : 0u) + OP_KSPLIT;
                    for (; gok < 4; gok++) {
                        unsigned int v;
                        asm volatile("ld.acquire.gpu.global.u32 %0, [%1];" : "=r"(v) : "l"(&g_cnt[C_O + ((ticket & 31) >> 1) * 4 + gok]) : "memory");
                        if (v < 16) break;
                    }
                    asm volatile("fence.proxy.async;" ::: "memory");
                }
            } while (next_item());
            for (int s = 0; s < AT_STAGES; s++) {
                mbar_wait(smem_u32(&sm.empty_k[stage]), phase ^ 1);
                mbar_wait(smem_u32(&sm.empty_v[stage]), phase ^ 1);
                if (++stage == AT_STAGES) { stage = 0; phase ^= 1; }
            }
            *reinterpret_cast<volatile uint32_t*>(&sm.ticket) = ticket;
            if (ticket >= 32 * OP_KSPLIT) {
                mbar_arrive(smem_u32(&sm.op_full[0]));
            } else {
                const int tile = ticket & 31, mb = tile >> 1;
                stage = 0;
                phase = 0;
                unsigned int kg = ticket >> 5, n2 = n1 + 1;
                while (kg < OP_KT) {
                    const unsigned int n3 = atomicAdd(&g_cnt[C_CLAIM + tile], 1u) + OP_KSPLIT;
                    while ((kg >> 4) >= gok) {
                        unsigned int v, spins = 0;
                        do {
                            asm volatile("ld.acquire.gpu.global.u32 %0, [%1];" : "=r"(v) : "l"(&g_cnt[C_O + mb * 4 + gok]) : "memory");
                        } while (v < 16 && ++spins < (1u << 24));
                        gok++;
                        asm volatile("fence.proxy.async;" ::: "memory");
                    }
                    const uint32_t buf = smem_u32(sm.k[0]) + stage * 49152, fb = smem_u32(&sm.op_full[stage]);
                    mbar_wait(smem_u32(&sm.op_empty[stage]), phase ^ 1);
                    *reinterpret_cast<volatile uint32_t*>(&sm.op_last[stage]) = n1 >= OP_KT;
                    mbar_expect_tx(fb, 49152);
                    tma_load_3d(buf, &tm_old, fb, 0, mb * 128, kg);
                    tma_load_3d(buf + 16384, &tm_wo, fb, 0, kg * 64, (tile & 1) * 4);
                    if (++stage == OP_STAGES) { stage = 0; phase ^= 1; }
                    kg = n1;
                    n1 = n2;
                    n2 = n3;
                }
            }
        }
    } else {
        reg_alloc<232>();
        const int cw = wg - 1;
        const int lane = tid & 31;
        const int warp_in_wg = (tid >> 5) & 3;
        const float c = 1.4426950408889634f;
        const uint32_t SCALE_HI2 = 0x3DB53DB5u, SCALE_LO2 = 0x371E371Eu;
        const uint32_t obase = smem_u32(sm.o) + cw * 16384;
        const int st_row = warp_in_wg * 16 + ((lane >> 3) & 1) * 8 + (lane & 7);

        const uint32_t dq = __shfl_sync(0xffffffffu, desc_lo(obase, 16), 0);
        const uint32_t dk0 = __shfl_sync(0xffffffffu, desc_lo(smem_u32(sm.k[0]), 16), 0);
        const uint32_t dv0 = dk0 - (1u << 16) + (1024u << 16) + AT_STAGES * (TILE_BYTES >> 4);

        PP(if (cw == 1) named_arrive(BAR_SCHED0 + 0, 256));

        int stage = 0;
        uint32_t phase = 0;
        float S[64];
        uint32_t P[32], P2[32];
        uint32_t cnt = 0;
        const uint32_t dw0 = __shfl_sync(0xffffffffu, desc_lo(smem_u32(sm.v[0]) + 16384, smem_u32(sm.ones0) - smem_u32(sm.v[0]) - 16384), 0);
        constexpr uint32_t DW_K = 128u - (128u << 16), DW_ST = 2048u - (2048u << 16);

        const uint32_t fk0 = smem_u32(&sm.full_k[0]), fv0 = smem_u32(&sm.full_v[0]);
        const uint32_t ek0 = smem_u32(&sm.empty_k[0]), ev0 = smem_u32(&sm.empty_v[0]);
        int vstage = 0;
        uint32_t vphase = 0;
        bool okk = false, okv = false;

        auto gemm_chunk = [&](bool acc, bool real) {
            if (real) {
                mbar_wait(fk0 + stage * 8, phase);
                mbar_wait(fv0 + stage * 8, phase);
            }
            const uint64_t da = make_desc(smem_u32(sm.k[stage]) + cw * 64 * 128, 16, 1024);
            const uint64_t db = make_desc(smem_u32(sm.v[stage]), 16384, 1024);
            wgmma_fence();
#pragma unroll
            for (int kk = 0; kk < 8; kk++) {
                wgmma_ss_n128<1>(S, da + (uint64_t)(((kk >> 2) * 16384 + (kk & 3) * 32) >> 4),
                                 db + (uint64_t)((kk * 2048) >> 4), acc || kk != 0);
            }
            wgmma_commit();
        };
        auto gemm_rest = [&](int nch) {
            int prev = stage;
            if (++stage == AT_STAGES) { stage = 0; phase ^= 1; }
#pragma unroll 1
            for (int kc = 1; kc < nch; kc++) {
                gemm_chunk(true, true);
                wgmma_wait<1>();
                if (lane == 0) {
                    mbar_arrive(ek0 + prev * 8);
                    mbar_arrive(ev0 + prev * 8);
                }
                prev = stage;
                if (++stage == AT_STAGES) { stage = 0; phase ^= 1; }
            }
            wgmma_wait<0>();
            if (lane == 0) {
                mbar_arrive(ek0 + prev * 8);
                mbar_arrive(ev0 + prev * 8);
            }
#pragma unroll
            for (int i = 0; i < 32; i++) P[i] = pack_bf16(S[2 * i], S[2 * i + 1]);
        };
        auto stage_p = [&]() {
            mbar_wait(smem_u32(&sm.st_free[cw]), (cnt & 1) ^ 1);
            cnt++;
#pragma unroll
            for (int i = 0; i < 16; i += 2) {
                const int cc = i + (lane >> 4);
                const uint32_t addr = obase + (cc >> 3) * 8192 + st_row * 128 + (((cc & 7) ^ (st_row & 7)) << 4);
                stmatrix_x4(addr, P[2 * i], P[2 * i + 1], P[2 * i + 2], P[2 * i + 3]);
            }
            fence_proxy_async();
        };
        auto issue_qk = [&](uint32_t dk) {
            wgmma_fence();
#pragma unroll
            for (int kk = 0; kk < 8; kk++)
                wgmma_ss_lo<0>(S, dq + (((kk >> 2) * 8192 + (kk & 3) * 32) >> 4),
                               dk + (((kk >> 2) * 16384 + (kk & 3) * 32) >> 4), kk != 0);
            wgmma_commit();
        };
        auto issue_pv = [&](float (&O)[64], float (&L)[4], uint32_t (&Pc)[32], int vs) {
            const uint32_t dv = dv0 + vs * (TILE_BYTES >> 4), dw = dw0 + vs * DW_ST;
            wgmma_fence();
#pragma unroll
            for (int kk = 0; kk < 8; kk++) {
                wgmma_rs_n64(O, Pc[4 * kk], Pc[4 * kk + 1], Pc[4 * kk + 2], Pc[4 * kk + 3], dv + ((kk * 2048) >> 4));
                wgmma_rs_n72(O, L, Pc[4 * kk], Pc[4 * kk + 1], Pc[4 * kk + 2], Pc[4 * kk + 3], dw + kk * DW_K);
            }
            wgmma_commit();
        };
        auto epilogue = [&](float (&O)[64], float (&L)[4]) {
            const float i0 = 1.0f / L[0], i1 = 1.0f / L[2];
            named_sync(BAR_EPI0 + cw, 128);
#pragma unroll
            for (int i = 0; i < 16; i += 2) {
                const int cc = i + (lane >> 4);
                const uint32_t addr = obase + (cc >> 3) * 8192 + st_row * 128 + (((cc & 7) ^ (st_row & 7)) << 4);
                stmatrix_x4(addr, pack_bf16(O[4 * i] * i0, O[4 * i + 1] * i0), pack_bf16(O[4 * i + 2] * i1, O[4 * i + 3] * i1),
                            pack_bf16(O[4 * i + 4] * i0, O[4 * i + 5] * i0), pack_bf16(O[4 * i + 6] * i1, O[4 * i + 7] * i1));
            }
            fence_proxy_async();
            named_arrive(BAR_ST0 + cw, 160);
        };
        auto scores_max = [&](uint32_t (&T)[32], float& x0, float& x1) {
#pragma unroll
            for (int i = 0; i < 32; i++) {
                const uint32_t sb = pack_bf16(S[2 * i], S[2 * i + 1]);
                T[i] = fma_bf16x2(sb, SCALE_HI2, mul_bf16x2(sb, SCALE_LO2));
            }
            uint32_t y0 = max_bf16x2(T[0], T[2]), y1 = max_bf16x2(T[1], T[3]);
#pragma unroll
            for (int i = 2; i < 16; i++) {
                y0 = max_bf16x2(y0, T[2 * i]);
                y1 = max_bf16x2(y1, T[2 * i + 1]);
            }
            x0 = fmaxf(bf16lo(y0), bf16hi(y0));
            x1 = fmaxf(bf16lo(y1), bf16hi(y1));
            x0 = fmaxf(x0, __shfl_xor_sync(0xffffffffu, x0, 1));
            x1 = fmaxf(x1, __shfl_xor_sync(0xffffffffu, x1, 1));
            x0 = fmaxf(x0, __shfl_xor_sync(0xffffffffu, x0, 2));
            x1 = fmaxf(x1, __shfl_xor_sync(0xffffffffu, x1, 2));
        };
        auto first_block = [&]() {
            stage_p();
            named_sync(BAR_EPI0 + cw, 128);
            vstage = stage;
            vphase = phase;
            mbar_wait(fk0 + stage * 8, phase);
            PP(named_sync(BAR_SCHED0 + cw, 256));
            issue_qk(dk0 + stage * (TILE_BYTES >> 4));
            PP(named_arrive(BAR_SCHED0 + (cw ^ 1), 256));
            if (++stage == AT_STAGES) { stage = 0; phase ^= 1; }
            okk = mbar_try_wait(fk0 + stage * 8, phase);
            okv = mbar_try_wait(fv0 + vstage * 8, vphase);
            wgmma_wait<0>();
            if (lane == 0) mbar_arrive(ek0 + vstage * 8);
        };

        gemm_chunk(false, true);
#pragma unroll 1
        for (; it < n_items; it++) {
            const int item = sched.item[blockIdx.x][it];
            const int type = item >> 12;
            const bool has_next = it + 1 < n_items;
            gemm_rest((type == T_F2) ? FF / 128 : DM / 128);
            if (type != T_ATT) {
                gemm_chunk(false, has_next);
#pragma unroll
                for (int i = 0; i < 32; i++) P[i] = pack_bf16(silu_f(bf16lo(P[i])), silu_f(bf16hi(P[i])));
                stage_p();
                named_arrive(BAR_ST0 + cw, 160);
            } else {
                first_block();
                float O[64], L[4] = {0.f, 0.f, 0.f, 0.f};
#pragma unroll
                for (int i = 0; i < 64; i++) O[i] = 0.f;
                float n0, n1;
                {
                    float x0, x1;
                    scores_max(P2, x0, x1);
                    n0 = fmaf(-x0, c, FAST_BIAS);
                    n1 = fmaf(-x1, c, FAST_BIAS);
#pragma unroll
                    for (int i = 0; i < 16; i++) {
                        const float e0 = ex2(fmaf(bf16lo(P2[2 * i]), c, n0));
                        const float e1 = ex2(fmaf(bf16hi(P2[2 * i]), c, n0));
                        const float e2 = ex2(fmaf(bf16lo(P2[2 * i + 1]), c, n1));
                        const float e3 = ex2(fmaf(bf16hi(P2[2 * i + 1]), c, n1));
                        P[2 * i] = pack_bf16(e0, e1);
                        P[2 * i + 1] = pack_bf16(e2, e3);
                    }
                }
                auto expo = [&](uint32_t (&Pn)[32], int i_lo, int i_hi) {
#pragma unroll
                    for (int i = i_lo; i < i_hi; i++) {
                        const uint32_t sa = pack_bf16(S[4 * i], S[4 * i + 1]), sb = pack_bf16(S[4 * i + 2], S[4 * i + 3]);
                        const uint32_t ta = fma_bf16x2(sa, SCALE_HI2, mul_bf16x2(sa, SCALE_LO2));
                        const uint32_t tb = fma_bf16x2(sb, SCALE_HI2, mul_bf16x2(sb, SCALE_LO2));
                        const float e0 = ex2(fmaf(bf16lo(ta), c, n0));
                        const float e1 = ex2(fmaf(bf16hi(ta), c, n0));
                        const float e2 = ex2(fmaf(bf16lo(tb), c, n1));
                        float e3 = ex2(fmaf(bf16hi(tb), c, n1));
                        if (i == i_hi - 1 && i_hi < 16) while (e3 < 0.f) e3 = g_dummy;
                        Pn[2 * i] = pack_bf16(e0, e1);
                        Pn[2 * i + 1] = pack_bf16(e2, e3);
                    }
                };
                auto step = [&](uint32_t (&Pc)[32], uint32_t (&Pn)[32]) {
                    const int ust = __shfl_sync(0xffffffffu, stage, 0), uvs = __shfl_sync(0xffffffffu, vstage, 0);
                    if (!okk) mbar_wait(fk0 + stage * 8, phase);
                    if (!okv) mbar_wait(fv0 + vstage * 8, vphase);
                    PP(named_sync(BAR_SCHED0 + cw, 256));
                    issue_qk(dk0 + ust * (TILE_BYTES >> 4));
                    issue_pv(O, L, Pc, uvs);
                    PP(named_arrive(BAR_SCHED0 + (cw ^ 1), 256));
                    const int pv = vstage;
                    vstage = stage;
                    vphase = phase;
                    if (++stage == AT_STAGES) { stage = 0; phase ^= 1; }
                    okk = mbar_try_wait(fk0 + stage * 8, phase);
                    okv = mbar_try_wait(fv0 + vstage * 8, vphase);
                    wgmma_wait<1>();
                    if (lane == 0) mbar_arrive(ek0 + vstage * 8);
                    EXPO(expo(Pn, 0, 8));
                    wgmma_wait<0>();
                    if (lane == 0) mbar_arrive(ev0 + pv * 8);
                    EXPO(expo(Pn, 8, 16));
                };
#pragma unroll 1
                for (int j = 0; j < 7; j++) {
                    step(P, P2);
                    step(P2, P);
                }
                step(P, P2);
                if (!okv) mbar_wait(fv0 + vstage * 8, vphase);
                issue_pv(O, L, P2, vstage);
                gemm_chunk(false, has_next);
                wgmma_wait<1>();
                if (lane == 0) mbar_arrive(ev0 + vstage * 8);
                float z = fmaf(L[0], 0.f, L[2] * 0.f);
#pragma unroll
                for (int i = 0; i < 64; i++) z = fmaf(O[i], 0.f, z);
                if (__any_sync(0xffffffffu, z != 0.f) && lane == 0) atomicOr(&sm.redo, 1u << (16 * cw + it));
                epilogue(O, L);
            }
        }
        wgmma_wait<0>();
        __syncwarp();
        if (lane == 0) mbar_arrive(smem_u32(&sm.redo_bar));
        mbar_wait(smem_u32(&sm.redo_bar), 0);
        rmask = *reinterpret_cast<volatile uint32_t*>(&sm.redo);
        rmask = (rmask | (rmask >> 16)) & 0xffffu;
#pragma unroll 1
        for (; rmask; rmask &= rmask - 1) {
            gemm_chunk(false, true);
            gemm_rest(DM / 128);
            first_block();
            float O[64], L[4] = {0.f, 0.f, 0.f, 0.f};
#pragma unroll
            for (int i = 0; i < 64; i++) O[i] = 0.f;
            float m0 = -INFINITY, m1 = -INFINITY;
#pragma unroll 1
            for (int j = 0; j < 16; j++) {
                float x0, x1;
                scores_max(P2, x0, x1);
                x0 = fmaxf(x0, m0);
                x1 = fmaxf(x1, m1);
                const float a0 = ex2((m0 - x0) * c), a1 = ex2((m1 - x1) * c);
                m0 = x0;
                m1 = x1;
                const float n0 = -m0 * c, n1 = -m1 * c;
#pragma unroll
                for (int i = 0; i < 16; i++) {
                    const float e0 = ex2(fmaf(bf16lo(P2[2 * i]), c, n0));
                    const float e1 = ex2(fmaf(bf16hi(P2[2 * i]), c, n0));
                    const float e2 = ex2(fmaf(bf16lo(P2[2 * i + 1]), c, n1));
                    const float e3 = ex2(fmaf(bf16hi(P2[2 * i + 1]), c, n1));
                    P[2 * i] = pack_bf16(e0, e1);
                    P[2 * i + 1] = pack_bf16(e2, e3);
                    O[4 * i] *= a0;
                    O[4 * i + 1] *= a0;
                    O[4 * i + 2] *= a1;
                    O[4 * i + 3] *= a1;
                }
                L[0] *= a0;
                L[1] *= a0;
                L[2] *= a1;
                L[3] *= a1;
                mbar_wait(fv0 + vstage * 8, vphase);
                issue_pv(O, L, P, vstage);
                wgmma_wait<0>();
                if (lane == 0) mbar_arrive(ev0 + vstage * 8);
                if (j < 15) {
                    mbar_wait(fk0 + stage * 8, phase);
                    issue_qk(dk0 + stage * (TILE_BYTES >> 4));
                    wgmma_wait<0>();
                    if (lane == 0) mbar_arrive(ek0 + stage * 8);
                    vstage = stage;
                    vphase = phase;
                    if (++stage == AT_STAGES) { stage = 0; phase ^= 1; }
                }
            }
            epilogue(O, L);
        }
        mbar_wait(smem_u32(&sm.op_full[0]), 0);
        const unsigned int ticket = *reinterpret_cast<volatile uint32_t*>(&sm.ticket);
        if (ticket < 32 * OP_KSPLIT) {
            const int kr = ticket >> 5, tile = ticket & 31;
            const int n0 = (tile & 1) * 256, mb = tile >> 1;
            const int ct = tid - 128;
            float acc[128];
            const int r0 = mb * 128 + cw * 64 + warp_in_wg * 16 + (lane >> 2);
            uint32_t xv[16], gv[16];
#pragma unroll
            for (int j = 0; j < 8; j++) {
#pragma unroll
                for (int hh = 0; hh < 2; hh++) {
                    const size_t off = (size_t)(r0 + hh * 8) * DM + n0 + kr * 64 + j * 8 + (lane & 3) * 2;
                    xv[2 * j + hh] = *reinterpret_cast<const uint32_t*>(x + off);
                }
            }
            int prev = -1;
            uint32_t last = 0;
            stage = 0;
            phase = 0;
#pragma unroll 1
            for (int kt = 0; !last; kt++) {
                mbar_wait(smem_u32(&sm.op_full[stage]), phase);
                last = *reinterpret_cast<volatile uint32_t*>(&sm.op_last[stage]);
                const uint32_t buf = smem_u32(sm.k[0]) + stage * 49152;
                const uint64_t da = make_desc(buf + cw * 64 * 128, 16, 1024);
                const uint64_t db = make_desc(buf + 16384, 8192, 1024);
                wgmma_fence();
#pragma unroll
                for (int kk = 0; kk < 4; kk++)
                    wgmma_ss_n256_tb(acc, da + (uint64_t)((kk * 32) >> 4), db + (uint64_t)((kk * 2048) >> 4), (kt | kk) != 0);
                wgmma_commit();
                wgmma_wait<1>();
                if (prev >= 0 && lane == 0) mbar_arrive(smem_u32(&sm.op_empty[prev]));
                prev = stage;
                if (++stage == OP_STAGES) { stage = 0; phase ^= 1; }
            }
            wgmma_wait<0>();
            float4* part = g_part + (size_t)tile * (OP_KSPLIT * OP_KSPLIT * 8 * 256);
#pragma unroll
            for (int d = 0; d < OP_KSPLIT; d++) {
                if (d == kr) continue;
#pragma unroll
                for (int j = 0; j < 8; j++)
                    __stcg(part + ((d * OP_KSPLIT + kr) * 8 + j) * 256 + ct,
                           make_float4(acc[(8 * d + j) * 4], acc[(8 * d + j) * 4 + 1], acc[(8 * d + j) * 4 + 2], acc[(8 * d + j) * 4 + 3]));
            }
            __threadfence();
            named_sync(BAR_OP, 256);
            if (ct < OP_KSPLIT && ct != kr)
                asm volatile("red.release.gpu.global.add.u32 [%0], 1;" ::"l"(&g_cnt[C_P + tile * OP_KSPLIT + ct]) : "memory");
            float r[32];
#pragma unroll
            for (int d = 0; d < OP_KSPLIT; d++) {
                if (d == kr) {
#pragma unroll
                    for (int i = 0; i < 32; i++) r[i] = acc[32 * d + i];
                }
            }
            if (ct < 2) {
                const unsigned int* cp = ct == 0 ? &g_cnt[C_P + tile * OP_KSPLIT + kr] : &g_cnt[C_G + mb * 4 + ((n0 + kr * 64) >> 7)];
                const unsigned int need = ct == 0 ? OP_KSPLIT - 1 : 2;
                unsigned int v, spins = 0;
                do {
                    asm volatile("ld.acquire.gpu.global.u32 %0, [%1];" : "=r"(v) : "l"(cp) : "memory");
                } while (v < need && ++spins < (1u << 24));
            }
            named_sync(BAR_OP, 256);
#pragma unroll
            for (int j = 0; j < 8; j++) {
#pragma unroll
                for (int hh = 0; hh < 2; hh++) {
                    const size_t off = (size_t)(r0 + hh * 8) * DM + n0 + kr * 64 + j * 8 + (lane & 3) * 2;
                    gv[2 * j + hh] = __ldcg(reinterpret_cast<const uint32_t*>(g_g + off));
                }
            }
#pragma unroll
            for (int sr = 0; sr < OP_KSPLIT; sr++) {
                if (sr == kr) continue;
#pragma unroll
                for (int j = 0; j < 8; j++) {
                    const float4 v = __ldcg(part + ((kr * OP_KSPLIT + sr) * 8 + j) * 256 + ct);
                    r[4 * j] += v.x;
                    r[4 * j + 1] += v.y;
                    r[4 * j + 2] += v.z;
                    r[4 * j + 3] += v.w;
                }
            }
#pragma unroll
            for (int j = 0; j < 8; j++) {
#pragma unroll
                for (int hh = 0; hh < 2; hh++) {
                    const size_t off = (size_t)(r0 + hh * 8) * DM + n0 + kr * 64 + j * 8 + (lane & 3) * 2;
                    const float s0 = bf16_round(r[4 * j + 2 * hh]), s1 = bf16_round(r[4 * j + 2 * hh + 1]);
                    const float o0 = bf16lo(xv[2 * j + hh]) + bf16_round(s0 * bf16lo(gv[2 * j + hh]));
                    const float o1 = bf16hi(xv[2 * j + hh]) + bf16_round(s1 * bf16hi(gv[2 * j + hh]));
                    *reinterpret_cast<uint32_t*>(out + off) = pack_bf16(o0, o1);
                }
            }
        }
    }
}

typedef CUresult (*EncodeFn)(CUtensorMap*, CUtensorMapDataType, cuuint32_t, void*, const cuuint64_t*, const cuuint64_t*,
                             const cuuint32_t*, const cuuint32_t*, CUtensorMapInterleave, CUtensorMapSwizzle,
                             CUtensorMapL2promotion, CUtensorMapFloatOOBfill);

static CUtensorMap make_map(EncodeFn fn, const void* ptr, uint64_t rows, uint64_t cols, uint32_t box_rows, uint32_t box_blk) {
    CUtensorMap m;
    cuuint64_t dims[3] = {64, rows, cols / 64};
    cuuint64_t strides[2] = {cols * 2, 128};
    cuuint32_t box[3] = {64, box_rows, box_blk};
    cuuint32_t es[3] = {1, 1, 1};
    fn(&m, CU_TENSOR_MAP_DATA_TYPE_BFLOAT16, 3, const_cast<void*>(ptr), dims, strides, box, es, CU_TENSOR_MAP_INTERLEAVE_NONE,
       CU_TENSOR_MAP_SWIZZLE_128B, CU_TENSOR_MAP_L2_PROMOTION_L2_256B, CU_TENSOR_MAP_FLOAT_OOB_FILL_NONE);
    return m;
}

extern "C" void kernel_launch(void* const* d_in, const int* in_sizes, int n_in, void* d_out, int out_size) {
    const bf16* x = (const bf16*)d_in[0];
    const bf16* kc = (const bf16*)d_in[1];
    const bf16* vc = (const bf16*)d_in[2];
    const bf16* wq = (const bf16*)d_in[3];
    const bf16* wo = (const bf16*)d_in[4];
    const bf16* w1 = (const bf16*)d_in[6];
    const bf16* w2 = (const bf16*)d_in[7];
    bf16* out = (bf16*)d_out;

    static EncodeFn fn = nullptr;
    static void *p_xn = nullptr, *p_h = nullptr, *p_o = nullptr, *p_g = nullptr;
    static Sched sched;
    if (!fn) {
        void* f = nullptr;
        cudaDriverEntryPointQueryResult st;
        cudaGetDriverEntryPoint("cuTensorMapEncodeTiled", &f, cudaEnableDefault, &st);
        fn = (EncodeFn)f;
        cudaGetSymbolAddress(&p_xn, g_xn);
        cudaGetSymbolAddress(&p_h, g_h);
        cudaGetSymbolAddress(&p_o, g_o);
        cudaGetSymbolAddress(&p_g, g_g);
        cudaFuncSetAttribute(attn_kernel, cudaFuncAttributeMaxDynamicSharedMemorySize, (int)sizeof(AttnSmem) + 1024);
        int t1 = 0, t2 = 0;
        for (int i = 0; i < NUM_CTAS; i++) {
            const int n1 = i < 40 ? 0 : (i < 116 ? 2 : (i < 124 ? 3 : 6));
            const int n2 = i < 40 ? 1 : (i < 116 ? 0 : (i < 124 ? 2 : 1));
            int n = 0;
            for (int j = 0; j < n1; j++, t1++) sched.item[i][n++] = (uint16_t)((T_F1 << 12) | ((t1 % 14) << 4) | (t1 / 14));
            for (int t = i; t < NH * 16; t += NUM_CTAS) sched.item[i][n++] = (uint16_t)((T_ATT << 12) | ((t >> 4) << 4) | (t & 15));
            for (int j = 0; j < n2; j++, t2++) sched.item[i][n++] = (uint16_t)((T_F2 << 12) | ((t2 & 3) << 4) | (t2 >> 2));
            sched.count[i] = (uint8_t)n;
        }
    }
    CUtensorMap tm_xn_at = make_map(fn, p_xn, SEQ, DM, 128, 2);
    CUtensorMap tm_wq = make_map(fn, wq, DM, NH * DH, 128, 2);
    CUtensorMap tm_k = make_map(fn, kc, NH * SEQ, DH, 128, 2);
    CUtensorMap tm_v = make_map(fn, vc, NH * SEQ, DH, 128, 2);
    CUtensorMap tm_o_st = make_map(fn, p_o, SEQ, NH * DH, 64, 2);
    CUtensorMap tm_w1 = make_map(fn, w1, DM, FF, 128, 2);
    CUtensorMap tm_h_st = make_map(fn, p_h, SEQ, FF, 64, 2);
    CUtensorMap tm_h_ld = make_map(fn, p_h, SEQ, FF, 128, 2);
    CUtensorMap tm_w2 = make_map(fn, w2, FF, DM, 128, 2);
    CUtensorMap tm_g_st = make_map(fn, p_g, SEQ, DM, 64, 2);
    CUtensorMap tm_o_g = make_map(fn, p_o, SEQ, NH * DH, 128, 1);
    CUtensorMap tm_wo = make_map(fn, wo, NH * DH, DM, 64, 4);

    ln_kernel<<<SEQ / 8, 256>>>(x);
    cudaLaunchAttribute pdl[1];
    pdl[0].id = cudaLaunchAttributeProgrammaticStreamSerialization;
    pdl[0].val.programmaticStreamSerializationAllowed = 1;
    cudaLaunchConfig_t cfg = {};
    cfg.gridDim = dim3(NUM_CTAS);
    cfg.blockDim = dim3(384);
    cfg.dynamicSmemBytes = sizeof(AttnSmem) + 1024;
    cfg.stream = cudaStreamPerThread;
    cfg.attrs = pdl;
    cfg.numAttrs = 1;
    cudaLaunchKernelEx(&cfg, attn_kernel, tm_xn_at, tm_wq, tm_k, tm_v, tm_o_st, tm_w1, tm_h_st, tm_h_ld, tm_w2, tm_g_st, tm_o_g,
                       tm_wo, x, out, sched);
}
```

```cpp
#include <cuda_runtime.h>
#include <cuda_bf16.h>
#include <cuda.h>
#include <stdint.h>

typedef __nv_bfloat16 bf16;
#define PP(x) x

constexpr int SEQ = 2048, DM = 512, NH = 32, DH = 128, FF = 1792;

__device__ __align__(1024) bf16 g_xn[SEQ * DM];
__device__ __align__(1024) bf16 g_h[SEQ * FF];
__device__ __align__(1024) bf16 g_o[SEQ * NH * DH];
__device__ __align__(1024) bf16 g_g[SEQ * DM];
constexpr int C_H = 0, C_G = 16, C_P = C_G + 64, C_BAD = C_P + 64, C_RED = C_BAD + 16;
__device__ unsigned int g_cnt[256];
__device__ unsigned long long g_mask[16];
constexpr int OPE_N = 2, OPE_H = 12, OPF_H = NH - OPE_N * OPE_H;
__device__ float4 g_part[OPE_N * 64 * 16 * 256];
__device__ volatile float g_dummy;

__device__ __forceinline__ uint32_t smem_u32(const void* p) { return (uint32_t)__cvta_generic_to_shared(p); }

__device__ __forceinline__ void mbar_init(uint32_t bar, uint32_t count) {
    asm volatile("mbarrier.init.shared::cta.b64 [%0], %1;" ::"r"(bar), "r"(count) : "memory");
}
__device__ __forceinline__ void mbar_expect_tx(uint32_t bar, uint32_t bytes) {
    asm volatile("mbarrier.arrive.expect_tx.shared::cta.b64 _, [%0], %1;" ::"r"(bar), "r"(bytes) : "memory");
}
__device__ __forceinline__ void mbar_arrive(uint32_t bar) {
    asm volatile("mbarrier.arrive.shared::cta.b64 _, [%0];" ::"r"(bar) : "memory");
}
__device__ __forceinline__ bool mbar_try_wait(uint32_t bar, uint32_t parity) {
    uint32_t ok;
    asm volatile(
        "{\n.reg .pred p;\n"
        "mbarrier.test_wait.parity.shared::cta.b64 p, [%1], %2;\n"
        "selp.u32 %0, 1, 0, p;\n}\n"
        : "=r"(ok)
        : "r"(bar), "r"(parity)
        : "memory");
    return ok != 0;
}
__device__ __forceinline__ void mbar_wait(uint32_t bar, uint32_t parity) {
    asm volatile(
        "{\n.reg .pred P1;\n.reg .u32 n;\nmov.u32 n, 0;\n"
        "LAB_WAIT:\n"
        "mbarrier.try_wait.parity.shared::cta.b64 P1, [%0], %1;\n"
        "@P1 bra DONE;\n"
        "add.u32 n, n, 1;\n"
        "setp.lt.u32 P1, n, 4194304;\n"
        "@P1 bra LAB_WAIT;\n"
        "trap;\n"
        "DONE:\n}\n" ::"r"(bar), "r"(parity)
        : "memory");
}
__device__ __forceinline__ void tma_load_3d(uint32_t dst, const CUtensorMap* map, uint32_t bar, int c0, int c1, int c2) {
    asm volatile(
        "cp.async.bulk.tensor.3d.shared::cluster.global.mbarrier::complete_tx::bytes [%0], [%1, {%3, %4, %5}], [%2];"
        ::"r"(dst), "l"((uint64_t)map), "r"(bar), "r"(c0), "r"(c1), "r"(c2)
        : "memory");
}
__device__ __forceinline__ void tma_store_3d(const CUtensorMap* map, uint32_t src, int c0, int c1, int c2) {
    asm volatile("cp.async.bulk.tensor.3d.global.shared::cta.bulk_group [%0, {%2, %3, %4}], [%1];"
                 ::"l"((uint64_t)map), "r"(src), "r"(c0), "r"(c1), "r"(c2)
                 : "memory");
}
__device__ __forceinline__ void tma_commit() { asm volatile("cp.async.bulk.commit_group;" ::: "memory"); }
__device__ __forceinline__ void tma_wait_read0() { asm volatile("cp.async.bulk.wait_group.read 0;" ::: "memory"); }
__device__ __forceinline__ void tma_wait_all0() { asm volatile("cp.async.bulk.wait_group 0;" ::: "memory"); }
__device__ __forceinline__ void fence_proxy_async() { asm volatile("fence.proxy.async.shared::cta;" ::: "memory"); }
__device__ __forceinline__ void prefetch_tmap(const CUtensorMap* map) {
    asm volatile("prefetch.tensormap [%0];" ::"l"((uint64_t)map) : "memory");
}
__device__ __forceinline__ void pdl_wait() { asm volatile("griddepcontrol.wait;" ::: "memory"); }
__device__ __forceinline__ void pdl_launch() { asm volatile("griddepcontrol.launch_dependents;" ::: "memory"); }
__device__ __forceinline__ void named_sync(int id, int n) { asm volatile("bar.sync %0, %1;" ::"r"(id), "r"(n) : "memory"); }
__device__ __forceinline__ void named_arrive(int id, int n) { asm volatile("bar.arrive %0, %1;" ::"r"(id), "r"(n) : "memory"); }

__device__ __forceinline__ void wgmma_fence() { asm volatile("wgmma.fence.sync.aligned;" ::: "memory"); }
__device__ __forceinline__ void wgmma_commit() { asm volatile("wgmma.commit_group.sync.aligned;" ::: "memory"); }
template <int N>
__device__ __forceinline__ void wgmma_wait() { asm volatile("wgmma.wait_group.sync.aligned %0;" ::"n"(N) : "memory"); }

template <int R>
__device__ __forceinline__ void reg_alloc() { asm volatile("setmaxnreg.inc.sync.aligned.u32 %0;" ::"n"(R)); }
template <int R>
__device__ __forceinline__ void reg_dealloc() { asm volatile("setmaxnreg.dec.sync.aligned.u32 %0;" ::"n"(R)); }

__device__ __forceinline__ uint64_t make_desc(uint32_t saddr, uint32_t lbo_bytes, uint32_t sbo_bytes) {
    uint64_t d = 0;
    d |= (uint64_t)((saddr & 0x3FFFF) >> 4);
    d |= (uint64_t)((lbo_bytes >> 4) & 0x3FFF) << 16;
    d |= (uint64_t)((sbo_bytes >> 4) & 0x3FFF) << 32;
    d |= (uint64_t)1 << 62;
    return d;
}

__device__ __forceinline__ float ex2(float x) {
    float y;
    asm volatile("ex2.approx.ftz.f32 %0, %1;" : "=f"(y) : "f"(x));
    return y;
}
__device__ __forceinline__ uint32_t pack_bf16(float lo, float hi) {
    uint32_t r;
    asm("cvt.rn.bf16x2.f32 %0, %1, %2;" : "=r"(r) : "f"(hi), "f"(lo));
    return r;
}
__device__ __forceinline__ uint32_t mul_bf16x2(uint32_t a, uint32_t b) {
    uint32_t r;
    asm("mul.rn.bf16x2 %0, %1, %2;" : "=r"(r) : "r"(a), "r"(b));
    return r;
}
__device__ __forceinline__ uint32_t add_bf16x2(uint32_t a, uint32_t b) {
    uint32_t r;
    asm("add.rn.bf16x2 %0, %1, %2;" : "=r"(r) : "r"(a), "r"(b));
    return r;
}
__device__ __forceinline__ unsigned int ld_acq(const unsigned int* p) {
    unsigned int v;
    asm volatile("ld.acquire.gpu.global.u32 %0, [%1];" : "=r"(v) : "l"(p) : "memory");
    return v;
}
__device__ __forceinline__ unsigned long long ld_acq64(const unsigned long long* p) {
    unsigned long long v;
    asm volatile("ld.acquire.gpu.global.u64 %0, [%1];" : "=l"(v) : "l"(p) : "memory");
    return v;
}
__device__ __forceinline__ uint32_t fma_bf16x2(uint32_t a, uint32_t b, uint32_t c) {
    uint32_t r;
    asm("fma.rn.bf16x2 %0, %1, %2, %3;" : "=r"(r) : "r"(a), "r"(b), "r"(c));
    return r;
}
__device__ __forceinline__ uint32_t max_bf16x2(uint32_t a, uint32_t b) {
    uint32_t r;
    asm("max.bf16x2 %0, %1, %2;" : "=r"(r) : "r"(a), "r"(b));
    return r;
}
__device__ __forceinline__ float bf16lo(uint32_t v) { return __uint_as_float(v << 16); }
__device__ __forceinline__ float bf16hi(uint32_t v) { return __uint_as_float(v & 0xffff0000u); }
__device__ __forceinline__ float bf16_round(float x) { return __bfloat162float(__float2bfloat16_rn(x)); }
__device__ __forceinline__ float silu_f(float x) {
    const float h = 0.5f * x;
    float t;
    asm("tanh.approx.f32 %0, %1;" : "=f"(t) : "f"(h));
    return fmaf(h, t, h);
}

__device__ __forceinline__ void stmatrix_x4(uint32_t addr, uint32_t r0, uint32_t r1, uint32_t r2, uint32_t r3) {
    asm volatile("stmatrix.sync.aligned.m8n8.x4.shared.b16 [%0], {%1, %2, %3, %4};"
                 ::"r"(addr), "r"(r0), "r"(r1), "r"(r2), "r"(r3)
                 : "memory");
}

#define ACC64(d) \
    "+f"(d[0]), "+f"(d[1]), "+f"(d[2]), "+f"(d[3]), "+f"(d[4]), "+f"(d[5]), "+f"(d[6]), "+f"(d[7]), \
    "+f"(d[8]), "+f"(d[9]), "+f"(d[10]), "+f"(d[11]), "+f"(d[12]), "+f"(d[13]), "+f"(d[14]), "+f"(d[15]), \
    "+f"(d[16]), "+f"(d[17]), "+f"(d[18]), "+f"(d[19]), "+f"(d[20]), "+f"(d[21]), "+f"(d[22]), "+f"(d[23]), \
    "+f"(d[24]), "+f"(d[25]), "+f"(d[26]), "+f"(d[27]), "+f"(d[28]), "+f"(d[29]), "+f"(d[30]), "+f"(d[31]), \
    "+f"(d[32]), "+f"(d[33]), "+f"(d[34]), "+f"(d[35]), "+f"(d[36]), "+f"(d[37]), "+f"(d[38]), "+f"(d[39]), \
    "+f"(d[40]), "+f"(d[41]), "+f"(d[42]), "+f"(d[43]), "+f"(d[44]), "+f"(d[45]), "+f"(d[46]), "+f"(d[47]), \
    "+f"(d[48]), "+f"(d[49]), "+f"(d[50]), "+f"(d[51]), "+f"(d[52]), "+f"(d[53]), "+f"(d[54]), "+f"(d[55]), \
    "+f"(d[56]), "+f"(d[57]), "+f"(d[58]), "+f"(d[59]), "+f"(d[60]), "+f"(d[61]), "+f"(d[62]), "+f"(d[63])

#define ACC64_STR \
    "{%0, %1, %2, %3, %4, %5, %6, %7, %8, %9, %10, %11, %12, %13, %14, %15, " \
    "%16, %17, %18, %19, %20, %21, %22, %23, %24, %25, %26, %27, %28, %29, %30, %31, " \
    "%32, %33, %34, %35, %36, %37, %38, %39, %40, %41, %42, %43, %44, %45, %46, %47, " \
    "%48, %49, %50, %51, %52, %53, %54, %55, %56, %57, %58, %59, %60, %61, %62, %63}"

template <int TB>
__device__ __forceinline__ void wgmma_ss_n128(float (&d)[64], uint64_t da, uint64_t db, int scale_d) {
    asm volatile(
        "{\n.reg .pred p;\nsetp.ne.b32 p, %66, 0;\n"
        "wgmma.mma_async.sync.aligned.m64n128k16.f32.bf16.bf16 " ACC64_STR ", %64, %65, p, 1, 1, 0, %67;\n}\n"
        : ACC64(d)
        : "l"(da), "l"(db), "r"(scale_d), "n"(TB));
}
template <int TB>
__device__ __forceinline__ void wgmma_rs_n128(float (&d)[64], uint32_t a0, uint32_t a1, uint32_t a2, uint32_t a3,
                                              uint64_t db, int scale_d) {
    asm volatile(
        "{\n.reg .pred p;\nsetp.ne.b32 p, %69, 0;\n"
        "wgmma.mma_async.sync.aligned.m64n128k16.f32.bf16.bf16 " ACC64_STR ", {%64, %65, %66, %67}, %68, p, 1, 1, %70;\n}\n"
        : ACC64(d)
        : "r"(a0), "r"(a1), "r"(a2), "r"(a3), "l"(db), "r"(scale_d), "n"(TB));
}

constexpr uint32_t DESC_HI = 0x40000040u;
__device__ __forceinline__ uint32_t desc_lo(uint32_t saddr, uint32_t lbo_bytes) {
    return ((saddr & 0x3FFFF) >> 4) | ((lbo_bytes >> 4) << 16);
}
template <int TB>
__device__ __forceinline__ void wgmma_ss_lo(float (&d)[64], uint32_t da, uint32_t db, int scale_d) {
    asm volatile(
        "{\n.reg .pred p;\n.reg .b64 xa, xb;\nsetp.ne.b32 p, %66, 0;\n"
        "mov.b64 xa, {%64, %68};\nmov.b64 xb, {%65, %68};\n"
        "wgmma.mma_async.sync.aligned.m64n128k16.f32.bf16.bf16 " ACC64_STR ", xa, xb, p, 1, 1, 0, %67;\n}\n"
        : ACC64(d)
        : "r"(da), "r"(db), "r"(scale_d), "n"(TB), "r"(DESC_HI));
}
__device__ __forceinline__ void wgmma_rs_lo_tb(float (&d)[64], uint32_t a0, uint32_t a1, uint32_t a2, uint32_t a3, uint32_t db) {
    asm volatile(
        "{\n.reg .b64 xb;\nmov.b64 xb, {%68, %69};\n"
        "wgmma.mma_async.sync.aligned.m64n128k16.f32.bf16.bf16 " ACC64_STR ", {%64, %65, %66, %67}, xb, 1, 1, 1, 1;\n}\n"
        : ACC64(d)
        : "r"(a0), "r"(a1), "r"(a2), "r"(a3), "r"(db), "r"(DESC_HI));
}

#define ACC8(d, o) "+f"(d[o]), "+f"(d[o + 1]), "+f"(d[o + 2]), "+f"(d[o + 3]), "+f"(d[o + 4]), "+f"(d[o + 5]), "+f"(d[o + 6]), "+f"(d[o + 7])
__device__ __forceinline__ void wgmma_rs_n64(float (&d)[64], uint32_t a0, uint32_t a1, uint32_t a2, uint32_t a3, uint32_t db) {
    asm volatile(
        "{\n.reg .b64 xb;\nmov.b64 xb, {%36, %37};\n"
        "wgmma.mma_async.sync.aligned.m64n64k16.f32.bf16.bf16 "
        "{%0, %1, %2, %3, %4, %5, %6, %7, %8, %9, %10, %11, %12, %13, %14, %15, "
        "%16, %17, %18, %19, %20, %21, %22, %23, %24, %25, %26, %27, %28, %29, %30, %31}, "
        "{%32, %33, %34, %35}, xb, 1, 1, 1, 1;\n}\n"
        : ACC8(d, 0), ACC8(d, 8), ACC8(d, 16), ACC8(d, 24)
        : "r"(a0), "r"(a1), "r"(a2), "r"(a3), "r"(db), "r"(DESC_HI));
}
__device__ __forceinline__ void wgmma_rs_n72(float (&d)[64], float (&l)[4], uint32_t a0, uint32_t a1, uint32_t a2, uint32_t a3, uint32_t db) {
    asm volatile(
        "{\n.reg .b64 xb;\nmov.b64 xb, {%40, %41};\n"
        "wgmma.mma_async.sync.aligned.m64n72k16.f32.bf16.bf16 "
        "{%0, %1, %2, %3, %4, %5, %6, %7, %8, %9, %10, %11, %12, %13, %14, %15, "
        "%16, %17, %18, %19, %20, %21, %22, %23, %24, %25, %26, %27, %28, %29, %30, %31, %32, %33, %34, %35}, "
        "{%36, %37, %38, %39}, xb, 1, 1, 1, 1;\n}\n"
        : ACC8(d, 32), ACC8(d, 40), ACC8(d, 48), ACC8(d, 56), "+f"(l[0]), "+f"(l[1]), "+f"(l[2]), "+f"(l[3])
        : "r"(a0), "r"(a1), "r"(a2), "r"(a3), "r"(db), "r"(DESC_HI));
}

__global__ void __launch_bounds__(256) ln_kernel(const bf16* __restrict__ x) {
    pdl_launch();
    int warp = threadIdx.x >> 5, lane = threadIdx.x & 31;
    int row = blockIdx.x * 8 + warp;
    if (blockIdx.x == 0) g_cnt[threadIdx.x] = 0;
    if (blockIdx.x == 1 && threadIdx.x < 16) g_mask[threadIdx.x] = 0;
    const uint4* src = reinterpret_cast<const uint4*>(x + (size_t)row * DM);
    uint4 v[2];
    v[0] = src[lane];
    v[1] = src[lane + 32];
    float f[16];
#pragma unroll
    for (int i = 0; i < 2; i++) {
        const __nv_bfloat162* p = reinterpret_cast<const __nv_bfloat162*>(&v[i]);
#pragma unroll
        for (int j = 0; j < 4; j++) {
            float2 t = __bfloat1622float2(p[j]);
            f[i * 8 + j * 2] = t.x;
            f[i * 8 + j * 2 + 1] = t.y;
        }
    }
    float s = 0.f;
#pragma unroll
    for (int i = 0; i < 16; i++) s += f[i];
#pragma unroll
    for (int o = 16; o > 0; o >>= 1) s += __shfl_xor_sync(0xffffffffu, s, o);
    float mean = s * (1.0f / DM);
    float q = 0.f;
#pragma unroll
    for (int i = 0; i < 16; i++) {
        float d = f[i] - mean;
        q += d * d;
    }
#pragma unroll
    for (int o = 16; o > 0; o >>= 1) q += __shfl_xor_sync(0xffffffffu, q, o);
    float var_b = bf16_round(q * (1.0f / DM));
    float mean_b = bf16_round(mean);
    float den = bf16_round(sqrtf(bf16_round(var_b + 1e-5f)));
    uint4 o[2];
#pragma unroll
    for (int i = 0; i < 2; i++) {
        uint32_t* p = reinterpret_cast<uint32_t*>(&o[i]);
#pragma unroll
        for (int j = 0; j < 4; j++) {
            float a = bf16_round(f[i * 8 + j * 2] - mean_b) / den;
            float b = bf16_round(f[i * 8 + j * 2 + 1] - mean_b) / den;
            p[j] = pack_bf16(a, b);
        }
    }
    uint4* dst = reinterpret_cast<uint4*>(g_xn + (size_t)row * DM);
    dst[lane] = o[0];
    dst[lane + 32] = o[1];
}

constexpr int AT_STAGES = 3;
constexpr int TILE_BYTES = 128 * 128 * 2;
struct __align__(1024) AttnSmem {
    uint8_t k[AT_STAGES][TILE_BYTES];
    uint8_t v[AT_STAGES][TILE_BYTES];
    uint8_t o[TILE_BYTES];
    uint32_t ones0[4];
    uint64_t full_k[AT_STAGES], full_v[AT_STAGES], empty_k[AT_STAGES], empty_v[AT_STAGES];
    uint64_t st_free[2];
    uint64_t redo_bar;
    uint32_t redo;
    uint32_t pad0;
    uint32_t ones1[4];
    uint64_t fin_bar[4];
    uint32_t pad1[24];
    uint32_t ones2[(2048 - 288) / 4];
};

#define EXPO(x) x
#define N8(x) x
#define PPK 8
#define FAST_BIAS (-40.0f)
constexpr int NUM_CTAS = 132;
constexpr int MAX_ITEMS = 12;
enum { T_ATT = 0, T_F1 = 1, T_F2 = 2, T_OPE = 3, T_OPF = 4 };
struct Sched {
    uint16_t item[NUM_CTAS][MAX_ITEMS];
    uint8_t count[NUM_CTAS];
};

__global__ void __launch_bounds__(384, 1)
attn_kernel(const __grid_constant__ CUtensorMap tm_xn, const __grid_constant__ CUtensorMap tm_wq,
            const __grid_constant__ CUtensorMap tm_k, const __grid_constant__ CUtensorMap tm_v,
            const __grid_constant__ CUtensorMap tm_o, const __grid_constant__ CUtensorMap tm_w1,
            const __grid_constant__ CUtensorMap tm_hst, const __grid_constant__ CUtensorMap tm_hld,
            const __grid_constant__ CUtensorMap tm_w2, const __grid_constant__ CUtensorMap tm_gst,
            const __grid_constant__ CUtensorMap tm_old, const __grid_constant__ CUtensorMap tm_wo,
            const bf16* __restrict__ x, bf16* __restrict__ out, const __grid_constant__ Sched sched) {
    extern __shared__ uint8_t smem_raw[];
    AttnSmem& sm = *reinterpret_cast<AttnSmem*>((reinterpret_cast<uintptr_t>(smem_raw) + 1023) & ~uintptr_t(1023));
    const int tid = threadIdx.x;
    const int wg = __shfl_sync(0xffffffffu, tid >> 7, 0);
    const int n_items = sched.count[blockIdx.x];
    if (tid == 32) {
        prefetch_tmap(&tm_xn); prefetch_tmap(&tm_wq); prefetch_tmap(&tm_k); prefetch_tmap(&tm_v); prefetch_tmap(&tm_o);
        prefetch_tmap(&tm_w1); prefetch_tmap(&tm_hst); prefetch_tmap(&tm_hld); prefetch_tmap(&tm_w2); prefetch_tmap(&tm_gst);
        prefetch_tmap(&tm_old); prefetch_tmap(&tm_wo);
    }

    if (tid == 0) {
#pragma unroll
        for (int s = 0; s < AT_STAGES; s++) {
            mbar_init(smem_u32(&sm.full_k[s]), 1);
            mbar_init(smem_u32(&sm.full_v[s]), 1);
            mbar_init(smem_u32(&sm.empty_k[s]), 8);
            mbar_init(smem_u32(&sm.empty_v[s]), 8);
        }
        mbar_init(smem_u32(&sm.st_free[0]), 1);
        mbar_init(smem_u32(&sm.st_free[1]), 1);
        mbar_init(smem_u32(&sm.redo_bar), 8);
#pragma unroll
        for (int s = 0; s < 4; s++) mbar_init(smem_u32(&sm.fin_bar[s]), 1);
        sm.redo = 0;
        asm volatile("fence.mbarrier_init.release.cluster;" ::: "memory");
    }
    if (tid < 64) {
        const int r = tid >> 2;
        sm.ones0[(r >> 3) * 256 + (r & 7) * 36 + (tid & 3)] = 0x3F803F80u;
        fence_proxy_async();
    }
    __syncthreads();
    pdl_wait();
    int it = 0;
    uint32_t rmask = 0;
    bool redo = false;
    auto next_item = [&]() -> bool {
        if (!redo) {
            if (++it < n_items) return true;
            mbar_wait(smem_u32(&sm.redo_bar), 0);
            rmask = *reinterpret_cast<volatile uint32_t*>(&sm.redo);
            rmask = (rmask | (rmask >> 16)) & 0xffffu;
            redo = true;
        }
        if (!rmask) return false;
        it = __ffs(rmask) - 1;
        rmask &= rmask - 1;
        return true;
    };
    constexpr int BAR_SCHED0 = 1, BAR_EPI0 = 3, BAR_ST0 = 5;

    if (wg == 0) {
        reg_dealloc<40>();
        if (tid >= 32 && tid < 96) {
            const int cw = (tid >> 5) - 1;
            const uint32_t obase = smem_u32(sm.o) + cw * 16384;
            do {
                const int item = sched.item[blockIdx.x][it];
                const int type = item >> 12, a = (item >> 4) & 0xff, b = item & 15;
                if (type == T_OPF) continue;
                named_sync(BAR_ST0 + cw, 160);
                if ((tid & 31) == 0) {
                    if (type == T_OPE) {
                        __threadfence();
                        atomicAdd(&g_cnt[C_P + b * 4 + (a & 3)], 1u);
                    } else {
                        if (redo) tma_wait_all0();
                        tma_store_3d(type == T_ATT ? &tm_o : (type == T_F1 ? &tm_hst : &tm_gst), obase, 0, b * 128 + cw * 64, a * 2);
                        tma_commit();
                        tma_wait_read0();
                        mbar_arrive(smem_u32(&sm.st_free[cw]));
                        const bool bad = (*reinterpret_cast<volatile uint32_t*>(&sm.redo) >> (16 * cw + it)) & 1;
                        if (bad && !redo) atomicAdd(&g_cnt[C_BAD + b], 1u);
                        tma_wait_all0();
                        asm volatile("fence.proxy.async;" ::: "memory");
                        __threadfence();
                        if (type != T_ATT) atomicAdd(&g_cnt[type == T_F1 ? C_H + b : C_G + b * 4 + a], 1u);
                        else if (!redo) atomicOr(&g_mask[b], 1ull << (2 * a + cw));
                        else if (bad) atomicAdd(&g_cnt[C_RED + b], 1u);
                    }
                }
                __syncwarp();
            } while (next_item());
            if ((tid & 31) == 0) tma_wait_all0();
        }
        if (tid == 96) {
            int ord = 0;
            for (int i = 0; i < n_items; i++) {
                const int item = sched.item[blockIdx.x][i];
                const int a = (item >> 4) & 0xff, b = item & 15;
                if ((item >> 12) != T_OPF) continue;
                unsigned int spins = 0;
                while (ld_acq64(&g_mask[b]) != ~0ull && ++spins < (1u << 24)) {}
                while (ld_acq(&g_cnt[C_P + b * 4 + a]) < 2 * OPE_N && ++spins < (1u << 24)) {}
                while (ld_acq(&g_cnt[C_G + b * 4 + a]) < 2 && ++spins < (1u << 24)) {}
                if (ld_acq(&g_cnt[C_BAD + b])) atomicOr(&sm.redo, 1u << i);
                mbar_arrive(smem_u32(&sm.fin_bar[ord++]));
            }
        }
        if (tid == 0) {
            int stage = 0;
            uint32_t phase = 0;
            do {
                const int item = sched.item[blockIdx.x][it];
                const int type = item >> 12, a = (item >> 4) & 0xff, b = item & 15;
                const CUtensorMap* ta = type >= T_OPE ? &tm_old : (type == T_F2 ? &tm_hld : &tm_xn);
                const CUtensorMap* tb = type >= T_OPE ? &tm_wo : (type == T_ATT ? &tm_wq : (type == T_F1 ? &tm_w1 : &tm_w2));
                int nch = DM / 128, kc0 = 0, nb = a;
                unsigned long long need = 0, mask = 0;
                unsigned int spins = 0;
                if (type == T_F2) {
                    nch = FF / 128;
                    while (ld_acq(&g_cnt[C_H + b]) < 2 * (FF / 128) && ++spins < (1u << 24)) {}
                    asm volatile("fence.proxy.async;" ::: "memory");
                } else if (type == T_OPE) {
                    nch = OPE_H;
                    kc0 = (a >> 2) * OPE_H;
                    nb = a & 3;
                    need = 3ull << (2 * kc0);
                } else if (type == T_OPF) {
                    if (!redo) {
                        nch = OPF_H;
                        kc0 = NH - OPF_H;
                        need = 3ull << (2 * kc0);
                    } else {
                        nch = NH;
                        const unsigned int nbad = ld_acq(&g_cnt[C_BAD + b]);
                        while (ld_acq(&g_cnt[C_RED + b]) < nbad && ++spins < (1u << 24)) {}
                        asm volatile("fence.proxy.async;" ::: "memory");
                    }
                }
                for (int kc = kc0; kc < kc0 + nch; kc++) {
                    if ((mask & need) != need) {
                        do mask = ld_acq64(&g_mask[b]); while ((mask & need) != need && ++spins < (1u << 24));
                        asm volatile("fence.proxy.async;" ::: "memory");
                    }
                    need <<= 2;
                    mbar_wait(smem_u32(&sm.empty_k[stage]), phase ^ 1);
                    mbar_expect_tx(smem_u32(&sm.full_k[stage]), TILE_BYTES);
                    tma_load_3d(smem_u32(sm.k[stage]), ta, smem_u32(&sm.full_k[stage]), 0, b * 128, kc * 2);
                    mbar_wait(smem_u32(&sm.empty_v[stage]), phase ^ 1);
                    mbar_expect_tx(smem_u32(&sm.full_v[stage]), TILE_BYTES);
                    tma_load_3d(smem_u32(sm.v[stage]), tb, smem_u32(&sm.full_v[stage]), 0, kc * 128, nb * 2);
                    if (++stage == AT_STAGES) { stage = 0; phase ^= 1; }
                }
                if (type == T_ATT) {
                    for (int j = 0; j < 16; j++) {
                        mbar_wait(smem_u32(&sm.empty_k[stage]), phase ^ 1);
                        mbar_expect_tx(smem_u32(&sm.full_k[stage]), TILE_BYTES);
                        tma_load_3d(smem_u32(sm.k[stage]), &tm_k, smem_u32(&sm.full_k[stage]), 0, a * SEQ + j * 128, 0);
                        mbar_wait(smem_u32(&sm.empty_v[stage]), phase ^ 1);
                        mbar_expect_tx(smem_u32(&sm.full_v[stage]), TILE_BYTES);
                        tma_load_3d(smem_u32(sm.v[stage]), &tm_v, smem_u32(&sm.full_v[stage]), 0, a * SEQ + j * 128, 0);
                        if (++stage == AT_STAGES) { stage = 0; phase ^= 1; }
                    }
                }
            } while (next_item());
        }
    } else {
        reg_alloc<232>();
        const int cw = wg - 1;
        const int lane = tid & 31;
        const int warp_in_wg = (tid >> 5) & 3;
        const float c = 1.4426950408889634f;
        const uint32_t SCALE_HI2 = 0x3DB53DB5u, SCALE_LO2 = 0x371E371Eu;
        const uint32_t obase = smem_u32(sm.o) + cw * 16384;
        const int st_row = warp_in_wg * 16 + ((lane >> 3) & 1) * 8 + (lane & 7);

        const uint32_t dq = __shfl_sync(0xffffffffu, desc_lo(obase, 16), 0);
        const uint32_t dk0 = __shfl_sync(0xffffffffu, desc_lo(smem_u32(sm.k[0]), 16), 0);
        const uint32_t dv0 = dk0 - (1u << 16) + (1024u << 16) + AT_STAGES * (TILE_BYTES >> 4);

        PP(if (cw == 1) named_arrive(BAR_SCHED0 + 0, 256));

        int stage = 0;
        uint32_t phase = 0;
        float S[64];
        uint32_t P[32], P2[32];
        uint32_t cnt = 0;
        const uint32_t dw0 = __shfl_sync(0xffffffffu, desc_lo(smem_u32(sm.v[0]) + 16384, smem_u32(sm.ones0) - smem_u32(sm.v[0]) - 16384), 0);
        constexpr uint32_t DW_K = 128u - (128u << 16), DW_ST = 2048u - (2048u << 16);

        const uint32_t fk0 = smem_u32(&sm.full_k[0]), fv0 = smem_u32(&sm.full_v[0]);
        const uint32_t ek0 = smem_u32(&sm.empty_k[0]), ev0 = smem_u32(&sm.empty_v[0]);
        int vstage = 0;
        uint32_t vphase = 0;
        bool okk = false, okv = false;

        auto gemm_chunk = [&](bool acc, bool real) {
            if (real) {
                mbar_wait(fk0 + stage * 8, phase);
                mbar_wait(fv0 + stage * 8, phase);
            }
            const uint64_t da = make_desc(smem_u32(sm.k[stage]) + cw * 64 * 128, 16, 1024);
            const uint64_t db = make_desc(smem_u32(sm.v[stage]), 16384, 1024);
            wgmma_fence();
#pragma unroll
            for (int kk = 0; kk < 8; kk++) {
                wgmma_ss_n128<1>(S, da + (uint64_t)(((kk >> 2) * 16384 + (kk & 3) * 32) >> 4),
                                 db + (uint64_t)((kk * 2048) >> 4), acc || kk != 0);
            }
            wgmma_commit();
        };
        auto gemm_rest = [&](int nch) {
            int prev = stage;
            if (++stage == AT_STAGES) { stage = 0; phase ^= 1; }
#pragma unroll 1
            for (int kc = 1; kc < nch; kc++) {
                gemm_chunk(true, true);
                wgmma_wait<1>();
                if (lane == 0) {
                    mbar_arrive(ek0 + prev * 8);
                    mbar_arrive(ev0 + prev * 8);
                }
                prev = stage;
                if (++stage == AT_STAGES) { stage = 0; phase ^= 1; }
            }
            wgmma_wait<0>();
            if (lane == 0) {
                mbar_arrive(ek0 + prev * 8);
                mbar_arrive(ev0 + prev * 8);
            }
        };
        auto pack_p = [&]() {
#pragma unroll
            for (int i = 0; i < 32; i++) P[i] = pack_bf16(S[2 * i], S[2 * i + 1]);
        };
        auto final_epi = [&](float (&T)[64], int mb, int nb) {
            mbar_wait(smem_u32(&sm.st_free[cw]), (cnt & 1) ^ 1);
#pragma unroll
            for (int i = 0; i < 16; i += 2) {
                const int cc = i + (lane >> 4);
                const uint32_t addr = obase + (cc >> 3) * 8192 + st_row * 128 + (((cc & 7) ^ (st_row & 7)) << 4);
                stmatrix_x4(addr, pack_bf16(T[4 * i], T[4 * i + 1]), pack_bf16(T[4 * i + 2], T[4 * i + 3]),
                            pack_bf16(T[4 * i + 4], T[4 * i + 5]), pack_bf16(T[4 * i + 6], T[4 * i + 7]));
            }
            const int t = tid & 127, ch = t & 15, row0 = t >> 4;
            const size_t off = (size_t)(mb * 128 + cw * 64 + row0) * DM + nb * 128 + ch * 8;
            uint4 xv[8], gv[8];
#pragma unroll
            for (int i = 0; i < 8; i++) {
                xv[i] = *reinterpret_cast<const uint4*>(x + off + (size_t)i * 8 * DM);
                gv[i] = __ldcg(reinterpret_cast<const uint4*>(g_g + off + (size_t)i * 8 * DM));
            }
            named_sync(BAR_EPI0 + cw, 128);
            const uint32_t sa = obase + (ch >> 3) * 8192 + row0 * 128 + (((ch & 7) ^ row0) << 4);
#pragma unroll
            for (int i = 0; i < 8; i++) {
                uint4 sv;
                asm volatile("ld.shared.v4.u32 {%0, %1, %2, %3}, [%4];" : "=r"(sv.x), "=r"(sv.y), "=r"(sv.z), "=r"(sv.w) : "r"(sa + i * 1024));
                sv.x = add_bf16x2(xv[i].x, mul_bf16x2(sv.x, gv[i].x));
                sv.y = add_bf16x2(xv[i].y, mul_bf16x2(sv.y, gv[i].y));
                sv.z = add_bf16x2(xv[i].z, mul_bf16x2(sv.z, gv[i].z));
                sv.w = add_bf16x2(xv[i].w, mul_bf16x2(sv.w, gv[i].w));
                *reinterpret_cast<uint4*>(out + off + (size_t)i * 8 * DM) = sv;
            }
            named_sync(BAR_EPI0 + cw, 128);
        };
        auto stage_p = [&]() {
            mbar_wait(smem_u32(&sm.st_free[cw]), (cnt & 1) ^ 1);
            cnt++;
#pragma unroll
            for (int i = 0; i < 16; i += 2) {
                const int cc = i + (lane >> 4);
                const uint32_t addr = obase + (cc >> 3) * 8192 + st_row * 128 + (((cc & 7) ^ (st_row & 7)) << 4);
                stmatrix_x4(addr, P[2 * i], P[2 * i + 1], P[2 * i + 2], P[2 * i + 3]);
            }
            fence_proxy_async();
        };
        auto issue_qk = [&](uint32_t dk) {
            wgmma_fence();
#pragma unroll
            for (int kk = 0; kk < 8; kk++)
                wgmma_ss_lo<0>(S, dq + (((kk >> 2) * 8192 + (kk & 3) * 32) >> 4),
                               dk + (((kk >> 2) * 16384 + (kk & 3) * 32) >> 4), kk != 0);
            wgmma_commit();
        };
        auto issue_pv = [&](float (&O)[64], float (&L)[4], uint32_t (&Pc)[32], int vs) {
            const uint32_t dv = dv0 + vs * (TILE_BYTES >> 4), dw = dw0 + vs * DW_ST;
            wgmma_fence();
#pragma unroll
            for (int kk = 0; kk < 8; kk++) {
                wgmma_rs_n64(O, Pc[4 * kk], Pc[4 * kk + 1], Pc[4 * kk + 2], Pc[4 * kk + 3], dv + ((kk * 2048) >> 4));
                wgmma_rs_n72(O, L, Pc[4 * kk], Pc[4 * kk + 1], Pc[4 * kk + 2], Pc[4 * kk + 3], dw + kk * DW_K);
            }
            wgmma_commit();
        };
        auto epilogue = [&](float (&O)[64], float (&L)[4]) {
            const float i0 = 1.0f / L[0], i1 = 1.0f / L[2];
            named_sync(BAR_EPI0 + cw, 128);
#pragma unroll
            for (int i = 0; i < 16; i += 2) {
                const int cc = i + (lane >> 4);
                const uint32_t addr = obase + (cc >> 3) * 8192 + st_row * 128 + (((cc & 7) ^ (st_row & 7)) << 4);
                stmatrix_x4(addr, pack_bf16(O[4 * i] * i0, O[4 * i + 1] * i0), pack_bf16(O[4 * i + 2] * i1, O[4 * i + 3] * i1),
                            pack_bf16(O[4 * i + 4] * i0, O[4 * i + 5] * i0), pack_bf16(O[4 * i + 6] * i1, O[4 * i + 7] * i1));
            }
            fence_proxy_async();
            named_arrive(BAR_ST0 + cw, 160);
        };
        auto scores_max = [&](uint32_t (&T)[32], float& x0, float& x1) {
#pragma unroll
            for (int i = 0; i < 32; i++) {
                const uint32_t sb = pack_bf16(S[2 * i], S[2 * i + 1]);
                T[i] = fma_bf16x2(sb, SCALE_HI2, mul_bf16x2(sb, SCALE_LO2));
            }
            uint32_t y0 = max_bf16x2(T[0], T[2]), y1 = max_bf16x2(T[1], T[3]);
#pragma unroll
            for (int i = 2; i < 16; i++) {
                y0 = max_bf16x2(y0, T[2 * i]);
                y1 = max_bf16x2(y1, T[2 * i + 1]);
            }
            x0 = fmaxf(bf16lo(y0), bf16hi(y0));
            x1 = fmaxf(bf16lo(y1), bf16hi(y1));
            x0 = fmaxf(x0, __shfl_xor_sync(0xffffffffu, x0, 1));
            x1 = fmaxf(x1, __shfl_xor_sync(0xffffffffu, x1, 1));
            x0 = fmaxf(x0, __shfl_xor_sync(0xffffffffu, x0, 2));
            x1 = fmaxf(x1, __shfl_xor_sync(0xffffffffu, x1, 2));
        };
        auto first_block = [&]() {
            stage_p();
            named_sync(BAR_EPI0 + cw, 128);
            vstage = stage;
            vphase = phase;
            mbar_wait(fk0 + stage * 8, phase);
            PP(named_sync(BAR_SCHED0 + cw, 256));
            issue_qk(dk0 + stage * (TILE_BYTES >> 4));
            PP(named_arrive(BAR_SCHED0 + (cw ^ 1), 256));
            if (++stage == AT_STAGES) { stage = 0; phase ^= 1; }
            okk = mbar_try_wait(fk0 + stage * 8, phase);
            okv = mbar_try_wait(fv0 + vstage * 8, vphase);
            wgmma_wait<0>();
            if (lane == 0) mbar_arrive(ek0 + vstage * 8);
        };

        int nfin = 0;
        gemm_chunk(false, true);
#pragma unroll 1
        for (; it < n_items; it++) {
            const int item = sched.item[blockIdx.x][it];
            const int type = item >> 12;
            const bool has_next = it + 1 < n_items;
            gemm_rest(type < T_F2 ? DM / 128 : (type == T_F2 ? FF / 128 : (type == T_OPE ? OPE_H : OPF_H)));
            if (type >= T_OPE) {
                float T[64];
#pragma unroll
                for (int i = 0; i < 64; i++) T[i] = S[i];
                gemm_chunk(false, has_next);
                const int a = (item >> 4) & 0xff, b = item & 15;
                float4* part = g_part + (size_t)(b * 4 + (a & 3)) * (16 * 256) + (tid - 128);
                if (type == T_OPE) {
                    part += (size_t)(a >> 2) * (64 * 16 * 256);
#pragma unroll
                    for (int j = 0; j < 16; j++) __stcg(part + j * 256, make_float4(T[4 * j], T[4 * j + 1], T[4 * j + 2], T[4 * j + 3]));
                    named_arrive(BAR_ST0 + cw, 160);
                } else {
                    mbar_wait(smem_u32(&sm.fin_bar[nfin++]), 0);
                    if (!((*reinterpret_cast<volatile uint32_t*>(&sm.redo) >> it) & 1)) {
#pragma unroll
                        for (int g = 0; g < OPE_N; g++) {
#pragma unroll
                            for (int j = 0; j < 16; j++) {
                                const float4 v = __ldcg(part + (size_t)g * (64 * 16 * 256) + j * 256);
                                T[4 * j] += v.x;
                                T[4 * j + 1] += v.y;
                                T[4 * j + 2] += v.z;
                                T[4 * j + 3] += v.w;
                            }
                        }
                        final_epi(T, b, a);
                    }
                }
            } else if (type != T_ATT) {
                pack_p();
                gemm_chunk(false, has_next);
#pragma unroll
                for (int i = 0; i < 32; i++) P[i] = pack_bf16(silu_f(bf16lo(P[i])), silu_f(bf16hi(P[i])));
                stage_p();
                named_arrive(BAR_ST0 + cw, 160);
            } else {
                pack_p();
                first_block();
                float O[64], L[4] = {0.f, 0.f, 0.f, 0.f};
#pragma unroll
                for (int i = 0; i < 64; i++) O[i] = 0.f;
                float n0, n1;
                {
                    float x0, x1;
                    scores_max(P2, x0, x1);
                    n0 = fmaf(-x0, c, FAST_BIAS);
                    n1 = fmaf(-x1, c, FAST_BIAS);
#pragma unroll
                    for (int i = 0; i < 16; i++) {
                        const float e0 = ex2(fmaf(bf16lo(P2[2 * i]), c, n0));
                        const float e1 = ex2(fmaf(bf16hi(P2[2 * i]), c, n0));
                        const float e2 = ex2(fmaf(bf16lo(P2[2 * i + 1]), c, n1));
                        const float e3 = ex2(fmaf(bf16hi(P2[2 * i + 1]), c, n1));
                        P[2 * i] = pack_bf16(e0, e1);
                        P[2 * i + 1] = pack_bf16(e2, e3);
                    }
                }
                auto expo = [&](uint32_t (&Pn)[32], int i_lo, int i_hi) {
#pragma unroll
                    for (int i = i_lo; i < i_hi; i++) {
                        const uint32_t sa = pack_bf16(S[4 * i], S[4 * i + 1]), sb = pack_bf16(S[4 * i + 2], S[4 * i + 3]);
                        const uint32_t ta = fma_bf16x2(sa, SCALE_HI2, mul_bf16x2(sa, SCALE_LO2));
                        const uint32_t tb = fma_bf16x2(sb, SCALE_HI2, mul_bf16x2(sb, SCALE_LO2));
                        const float e0 = ex2(fmaf(bf16lo(ta), c, n0));
                        const float e1 = ex2(fmaf(bf16hi(ta), c, n0));
                        const float e2 = ex2(fmaf(bf16lo(tb), c, n1));
                        float e3 = ex2(fmaf(bf16hi(tb), c, n1));
                        if (i == i_hi - 1 && i_hi < 16) while (e3 < 0.f) e3 = g_dummy;
                        Pn[2 * i] = pack_bf16(e0, e1);
                        Pn[2 * i + 1] = pack_bf16(e2, e3);
                    }
                };
                auto step = [&](uint32_t (&Pc)[32], uint32_t (&Pn)[32]) {
                    const int ust = __shfl_sync(0xffffffffu, stage, 0), uvs = __shfl_sync(0xffffffffu, vstage, 0);
                    if (!okk) mbar_wait(fk0 + stage * 8, phase);
                    if (!okv) mbar_wait(fv0 + vstage * 8, vphase);
                    PP(named_sync(BAR_SCHED0 + cw, 256));
                    issue_qk(dk0 + ust * (TILE_BYTES >> 4));
                    issue_pv(O, L, Pc, uvs);
                    PP(named_arrive(BAR_SCHED0 + (cw ^ 1), 256));
                    const int pv = vstage;
                    vstage = stage;
                    vphase = phase;
                    if (++stage == AT_STAGES) { stage = 0; phase ^= 1; }
                    okk = mbar_try_wait(fk0 + stage * 8, phase);
                    okv = mbar_try_wait(fv0 + vstage * 8, vphase);
                    wgmma_wait<1>();
                    if (lane == 0) mbar_arrive(ek0 + vstage * 8);
                    EXPO(expo(Pn, 0, 8));
                    wgmma_wait<0>();
                    if (lane == 0) mbar_arrive(ev0 + pv * 8);
                    EXPO(expo(Pn, 8, 16));
                };
#pragma unroll 1
                for (int j = 0; j < 7; j++) {
                    step(P, P2);
                    step(P2, P);
                }
                step(P, P2);
                if (!okv) mbar_wait(fv0 + vstage * 8, vphase);
                issue_pv(O, L, P2, vstage);
                gemm_chunk(false, has_next);
                wgmma_wait<1>();
                if (lane == 0) mbar_arrive(ev0 + vstage * 8);
                float z = fmaf(L[0], 0.f, L[2] * 0.f);
#pragma unroll
                for (int i = 0; i < 64; i++) z = fmaf(O[i], 0.f, z);
                if (__any_sync(0xffffffffu, z != 0.f) && lane == 0) atomicOr(&sm.redo, 1u << (16 * cw + it));
                epilogue(O, L);
            }
        }
        wgmma_wait<0>();
        __syncwarp();
        if (lane == 0) mbar_arrive(smem_u32(&sm.redo_bar));
        mbar_wait(smem_u32(&sm.redo_bar), 0);
        rmask = *reinterpret_cast<volatile uint32_t*>(&sm.redo);
        rmask = (rmask | (rmask >> 16)) & 0xffffu;
#pragma unroll 1
        for (; rmask && (sched.item[blockIdx.x][__ffs(rmask) - 1] >> 12) == T_ATT; rmask &= rmask - 1) {
            gemm_chunk(false, true);
            gemm_rest(DM / 128);
            pack_p();
            first_block();
            float O[64], L[4] = {0.f, 0.f, 0.f, 0.f};
#pragma unroll
            for (int i = 0; i < 64; i++) O[i] = 0.f;
            float m0 = -INFINITY, m1 = -INFINITY;
#pragma unroll 1
            for (int j = 0; j < 16; j++) {
                float x0, x1;
                scores_max(P2, x0, x1);
                x0 = fmaxf(x0, m0);
                x1 = fmaxf(x1, m1);
                const float a0 = ex2((m0 - x0) * c), a1 = ex2((m1 - x1) * c);
                m0 = x0;
                m1 = x1;
                const float n0 = -m0 * c, n1 = -m1 * c;
#pragma unroll
                for (int i = 0; i < 16; i++) {
                    const float e0 = ex2(fmaf(bf16lo(P2[2 * i]), c, n0));
                    const float e1 = ex2(fmaf(bf16hi(P2[2 * i]), c, n0));
                    const float e2 = ex2(fmaf(bf16lo(P2[2 * i + 1]), c, n1));
                    const float e3 = ex2(fmaf(bf16hi(P2[2 * i + 1]), c, n1));
                    P[2 * i] = pack_bf16(e0, e1);
                    P[2 * i + 1] = pack_bf16(e2, e3);
                    O[4 * i] *= a0;
                    O[4 * i + 1] *= a0;
                    O[4 * i + 2] *= a1;
                    O[4 * i + 3] *= a1;
                }
                L[0] *= a0;
                L[1] *= a0;
                L[2] *= a1;
                L[3] *= a1;
                mbar_wait(fv0 + vstage * 8, vphase);
                issue_pv(O, L, P, vstage);
                wgmma_wait<0>();
                if (lane == 0) mbar_arrive(ev0 + vstage * 8);
                if (j < 15) {
                    mbar_wait(fk0 + stage * 8, phase);
                    issue_qk(dk0 + stage * (TILE_BYTES >> 4));
                    wgmma_wait<0>();
                    if (lane == 0) mbar_arrive(ek0 + stage * 8);
                    vstage = stage;
                    vphase = phase;
                    if (++stage == AT_STAGES) { stage = 0; phase ^= 1; }
                }
            }
            epilogue(O, L);
        }
#pragma unroll 1
        for (; rmask; rmask &= rmask - 1) {
            const int item = sched.item[blockIdx.x][__ffs(rmask) - 1];
            gemm_chunk(false, true);
            gemm_rest(NH);
            final_epi(S, item & 15, (item >> 4) & 0xff);
        }
    }
}

typedef CUresult (*EncodeFn)(CUtensorMap*, CUtensorMapDataType, cuuint32_t, void*, const cuuint64_t*, const cuuint64_t*,
                             const cuuint32_t*, const cuuint32_t*, CUtensorMapInterleave, CUtensorMapSwizzle,
                             CUtensorMapL2promotion, CUtensorMapFloatOOBfill);

static CUtensorMap make_map(EncodeFn fn, const void* ptr, uint64_t rows, uint64_t cols, uint32_t box_rows, uint32_t box_blk) {
    CUtensorMap m;
    cuuint64_t dims[3] = {64, rows, cols / 64};
    cuuint64_t strides[2] = {cols * 2, 128};
    cuuint32_t box[3] = {64, box_rows, box_blk};
    cuuint32_t es[3] = {1, 1, 1};
    fn(&m, CU_TENSOR_MAP_DATA_TYPE_BFLOAT16, 3, const_cast<void*>(ptr), dims, strides, box, es, CU_TENSOR_MAP_INTERLEAVE_NONE,
       CU_TENSOR_MAP_SWIZZLE_128B, CU_TENSOR_MAP_L2_PROMOTION_L2_256B, CU_TENSOR_MAP_FLOAT_OOB_FILL_NONE);
    return m;
}

extern "C" void kernel_launch(void* const* d_in, const int* in_sizes, int n_in, void* d_out, int out_size) {
    const bf16* x = (const bf16*)d_in[0];
    const bf16* kc = (const bf16*)d_in[1];
    const bf16* vc = (const bf16*)d_in[2];
    const bf16* wq = (const bf16*)d_in[3];
    const bf16* wo = (const bf16*)d_in[4];
    const bf16* w1 = (const bf16*)d_in[6];
    const bf16* w2 = (const bf16*)d_in[7];
    bf16* out = (bf16*)d_out;

    static EncodeFn fn = nullptr;
    static void *p_xn = nullptr, *p_h = nullptr, *p_o = nullptr, *p_g = nullptr;
    static Sched sched;
    if (!fn) {
        void* f = nullptr;
        cudaDriverEntryPointQueryResult st;
        cudaGetDriverEntryPoint("cuTensorMapEncodeTiled", &f, cudaEnableDefault, &st);
        fn = (EncodeFn)f;
        cudaGetSymbolAddress(&p_xn, g_xn);
        cudaGetSymbolAddress(&p_h, g_h);
        cudaGetSymbolAddress(&p_o, g_o);
        cudaGetSymbolAddress(&p_g, g_g);
        cudaFuncSetAttribute(attn_kernel, cudaFuncAttributeMaxDynamicSharedMemorySize, (int)sizeof(AttnSmem) + 1024);
        static const struct { int n, n1; const char* tail; } cls[] = {
            {28, 0, "GE"}, {28, 1, "EO"}, {20, 1, "GO"}, {40, 3, "E"}, {8, 3, "GEEO"}, {8, 4, "GEEO"}};
        int t1 = 0, t2 = 0, t3 = 0, t4 = 0, i = 0;
        for (const auto& cl : cls) {
            for (int c = 0; c < cl.n; c++, i++) {
                int n = 0;
                for (int j = 0; j < cl.n1; j++, t1++) sched.item[i][n++] = (uint16_t)((T_F1 << 12) | ((t1 % 14) << 4) | (t1 / 14));
                for (int t = i; t < NH * 16; t += NUM_CTAS) sched.item[i][n++] = (uint16_t)((T_ATT << 12) | ((t >> 4) << 4) | (t & 15));
                for (const char* p = cl.tail; *p; p++) {
                    if (*p == 'G') { sched.item[i][n++] = (uint16_t)((T_F2 << 12) | ((t2 & 3) << 4) | (t2 >> 2)); t2++; }
                    if (*p == 'E') { sched.item[i][n++] = (uint16_t)((T_OPE << 12) | (((t3 & 3) | ((t3 >> 6) << 2)) << 4) | ((t3 >> 2) & 15)); t3++; }
                    if (*p == 'O') { sched.item[i][n++] = (uint16_t)((T_OPF << 12) | ((t4 & 3) << 4) | (t4 >> 2)); t4++; }
                }
                sched.count[i] = (uint8_t)n;
            }
        }
    }
    CUtensorMap tm_xn_at = make_map(fn, p_xn, SEQ, DM, 128, 2);
    CUtensorMap tm_wq = make_map(fn, wq, DM, NH * DH, 128, 2);
    CUtensorMap tm_k = make_map(fn, kc, NH * SEQ, DH, 128, 2);
    CUtensorMap tm_v = make_map(fn, vc, NH * SEQ, DH, 128, 2);
    CUtensorMap tm_o_st = make_map(fn, p_o, SEQ, NH * DH, 64, 2);
    CUtensorMap tm_w1 = make_map(fn, w1, DM, FF, 128, 2);
    CUtensorMap tm_h_st = make_map(fn, p_h, SEQ, FF, 64, 2);
    CUtensorMap tm_h_ld = make_map(fn, p_h, SEQ, FF, 128, 2);
    CUtensorMap tm_w2 = make_map(fn, w2, FF, DM, 128, 2);
    CUtensorMap tm_g_st = make_map(fn, p_g, SEQ, DM, 64, 2);
    CUtensorMap tm_o_g = make_map(fn, p_o, SEQ, NH * DH, 128, 2);
    CUtensorMap tm_wo = make_map(fn, wo, NH * DH, DM, 128, 2);

    ln_kernel<<<SEQ / 8, 256>>>(x);
    cudaLaunchAttribute pdl[1];
    pdl[0].id = cudaLaunchAttributeProgrammaticStreamSerialization;
    pdl[0].val.programmaticStreamSerializationAllowed = 1;
    cudaLaunchConfig_t cfg = {};
    cfg.gridDim = dim3(NUM_CTAS);
    cfg.blockDim = dim3(384);
    cfg.dynamicSmemBytes = sizeof(AttnSmem) + 1024;
    cfg.stream = cudaStreamPerThread;
    cfg.attrs = pdl;
    cfg.numAttrs = 1;
    cudaLaunchKernelEx(&cfg, attn_kernel, tm_xn_at, tm_wq, tm_k, tm_v, tm_o_st, tm_w1, tm_h_st, tm_h_ld, tm_w2, tm_g_st, tm_o_g,
                       tm_wo, x, out, sched);
}
```

```cpp
#include <cuda_runtime.h>
#include <cuda_bf16.h>
#include <cuda.h>
#include <stdint.h>

typedef __nv_bfloat16 bf16;
#define PP(x) x

constexpr int SEQ = 2048, DM = 512, NH = 32, DH = 128, FF = 1792;

__device__ __align__(1024) bf16 g_xn[SEQ * DM];
__device__ __align__(1024) bf16 g_h[SEQ * FF];
__device__ __align__(1024) bf16 g_o[SEQ * NH * DH];
__device__ __align__(1024) bf16 g_g[SEQ * DM];
constexpr int C_H = 0, C_G = 16, C_P = C_G + 64, C_BAD = C_P + 64, C_RED = C_BAD + 16;
__device__ unsigned int g_cnt[256];
__device__ unsigned long long g_mask[16];
constexpr int OPE_N = 2, OPE_H = 12, OPF_H = NH - OPE_N * OPE_H;
__device__ float4 g_part[OPE_N * 64 * 16 * 256];
__device__ volatile float g_dummy;

__device__ __forceinline__ uint32_t smem_u32(const void* p) { return (uint32_t)__cvta_generic_to_shared(p); }

__device__ __forceinline__ void mbar_init(uint32_t bar, uint32_t count) {
    asm volatile("mbarrier.init.shared::cta.b64 [%0], %1;" ::"r"(bar), "r"(count) : "memory");
}
__device__ __forceinline__ void mbar_expect_tx(uint32_t bar, uint32_t bytes) {
    asm volatile("mbarrier.arrive.expect_tx.shared::cta.b64 _, [%0], %1;" ::"r"(bar), "r"(bytes) : "memory");
}
__device__ __forceinline__ void mbar_arrive(uint32_t bar) {
    asm volatile("mbarrier.arrive.shared::cta.b64 _, [%0];" ::"r"(bar) : "memory");
}
__device__ __forceinline__ bool mbar_try_wait(uint32_t bar, uint32_t parity) {
    uint32_t ok;
    asm volatile(
        "{\n.reg .pred p;\n"
        "mbarrier.test_wait.parity.shared::cta.b64 p, [%1], %2;\n"
        "selp.u32 %0, 1, 0, p;\n}\n"
        : "=r"(ok)
        : "r"(bar), "r"(parity)
        : "memory");
    return ok != 0;
}
__device__ __forceinline__ void mbar_wait(uint32_t bar, uint32_t parity) {
    asm volatile(
        "{\n.reg .pred P1;\n.reg .u32 n;\nmov.u32 n, 0;\n"
        "LAB_WAIT:\n"
        "mbarrier.try_wait.parity.shared::cta.b64 P1, [%0], %1;\n"
        "@P1 bra DONE;\n"
        "add.u32 n, n, 1;\n"
        "setp.lt.u32 P1, n, 4194304;\n"
        "@P1 bra LAB_WAIT;\n"
        "trap;\n"
        "DONE:\n}\n" ::"r"(bar), "r"(parity)
        : "memory");
}
__device__ __forceinline__ void tma_load_3d(uint32_t dst, const CUtensorMap* map, uint32_t bar, int c0, int c1, int c2) {
    asm volatile(
        "cp.async.bulk.tensor.3d.shared::cluster.global.mbarrier::complete_tx::bytes [%0], [%1, {%3, %4, %5}], [%2];"
        ::"r"(dst), "l"((uint64_t)map), "r"(bar), "r"(c0), "r"(c1), "r"(c2)
        : "memory");
}
__device__ __forceinline__ void tma_store_3d(const CUtensorMap* map, uint32_t src, int c0, int c1, int c2) {
    asm volatile("cp.async.bulk.tensor.3d.global.shared::cta.bulk_group [%0, {%2, %3, %4}], [%1];"
                 ::"l"((uint64_t)map), "r"(src), "r"(c0), "r"(c1), "r"(c2)
                 : "memory");
}
__device__ __forceinline__ void tma_commit() { asm volatile("cp.async.bulk.commit_group;" ::: "memory"); }
__device__ __forceinline__ void tma_wait_read0() { asm volatile("cp.async.bulk.wait_group.read 0;" ::: "memory"); }
__device__ __forceinline__ void tma_wait_all0() { asm volatile("cp.async.bulk.wait_group 0;" ::: "memory"); }
__device__ __forceinline__ void fence_proxy_async() { asm volatile("fence.proxy.async.shared::cta;" ::: "memory"); }
__device__ __forceinline__ void prefetch_tmap(const CUtensorMap* map) {
    asm volatile("prefetch.tensormap [%0];" ::"l"((uint64_t)map) : "memory");
}
__device__ __forceinline__ void pdl_wait() { asm volatile("griddepcontrol.wait;" ::: "memory"); }
__device__ __forceinline__ void pdl_launch() { asm volatile("griddepcontrol.launch_dependents;" ::: "memory"); }
__device__ __forceinline__ void named_sync(int id, int n) { asm volatile("bar.sync %0, %1;" ::"r"(id), "r"(n) : "memory"); }
__device__ __forceinline__ void named_arrive(int id, int n) { asm volatile("bar.arrive %0, %1;" ::"r"(id), "r"(n) : "memory"); }

__device__ __forceinline__ void wgmma_fence() { asm volatile("wgmma.fence.sync.aligned;" ::: "memory"); }
__device__ __forceinline__ void wgmma_commit() { asm volatile("wgmma.commit_group.sync.aligned;" ::: "memory"); }
template <int N>
__device__ __forceinline__ void wgmma_wait() { asm volatile("wgmma.wait_group.sync.aligned %0;" ::"n"(N) : "memory"); }

__device__ __forceinline__ void fence_acc(float (&d)[64]) {
#pragma unroll
    for (int i = 0; i < 64; i++) asm volatile("" : "+f"(d[i])::"memory");
}

template <int R>
__device__ __forceinline__ void reg_alloc() { asm volatile("setmaxnreg.inc.sync.aligned.u32 %0;" ::"n"(R)); }
template <int R>
__device__ __forceinline__ void reg_dealloc() { asm volatile("setmaxnreg.dec.sync.aligned.u32 %0;" ::"n"(R)); }

__device__ __forceinline__ uint64_t make_desc(uint32_t saddr, uint32_t lbo_bytes, uint32_t sbo_bytes) {
    uint64_t d = 0;
    d |= (uint64_t)((saddr & 0x3FFFF) >> 4);
    d |= (uint64_t)((lbo_bytes >> 4) & 0x3FFF) << 16;
    d |= (uint64_t)((sbo_bytes >> 4) & 0x3FFF) << 32;
    d |= (uint64_t)1 << 62;
    return d;
}

__device__ __forceinline__ float ex2(float x) {
    float y;
    asm volatile("ex2.approx.ftz.f32 %0, %1;" : "=f"(y) : "f"(x));
    return y;
}
__device__ __forceinline__ uint32_t pack_bf16(float lo, float hi) {
    uint32_t r;
    asm("cvt.rn.bf16x2.f32 %0, %1, %2;" : "=r"(r) : "f"(hi), "f"(lo));
    return r;
}
__device__ __forceinline__ uint32_t mul_bf16x2(uint32_t a, uint32_t b) {
    uint32_t r;
    asm("mul.rn.bf16x2 %0, %1, %2;" : "=r"(r) : "r"(a), "r"(b));
    return r;
}
__device__ __forceinline__ uint32_t add_bf16x2(uint32_t a, uint32_t b) {
    uint32_t r;
    asm("add.rn.bf16x2 %0, %1, %2;" : "=r"(r) : "r"(a), "r"(b));
    return r;
}
__device__ __forceinline__ unsigned int ld_acq(const unsigned int* p) {
    unsigned int v;
    asm volatile("ld.acquire.gpu.global.u32 %0, [%1];" : "=r"(v) : "l"(p) : "memory");
    return v;
}
__device__ __forceinline__ unsigned long long ld_acq64(const unsigned long long* p) {
    unsigned long long v;
    asm volatile("ld.acquire.gpu.global.u64 %0, [%1];" : "=l"(v) : "l"(p) : "memory");
    return v;
}
__device__ __forceinline__ uint32_t fma_bf16x2(uint32_t a, uint32_t b, uint32_t c) {
    uint32_t r;
    asm("fma.rn.bf16x2 %0, %1, %2, %3;" : "=r"(r) : "r"(a), "r"(b), "r"(c));
    return r;
}
__device__ __forceinline__ uint32_t max_bf16x2(uint32_t a, uint32_t b) {
    uint32_t r;
    asm("max.bf16x2 %0, %1, %2;" : "=r"(r) : "r"(a), "r"(b));
    return r;
}
__device__ __forceinline__ float bf16lo(uint32_t v) { return __uint_as_float(v << 16); }
__device__ __forceinline__ float bf16hi(uint32_t v) { return __uint_as_float(v & 0xffff0000u); }
__device__ __forceinline__ float bf16_round(float x) { return __bfloat162float(__float2bfloat16_rn(x)); }
__device__ __forceinline__ float silu_f(float x) {
    const float h = 0.5f * x;
    float t;
    asm("tanh.approx.f32 %0, %1;" : "=f"(t) : "f"(h));
    return fmaf(h, t, h);
}

__device__ __forceinline__ void stmatrix_x4(uint32_t addr, uint32_t r0, uint32_t r1, uint32_t r2, uint32_t r3) {
    asm volatile("stmatrix.sync.aligned.m8n8.x4.shared.b16 [%0], {%1, %2, %3, %4};"
                 ::"r"(addr), "r"(r0), "r"(r1), "r"(r2), "r"(r3)
                 : "memory");
}

#define ACC64(d) \
    "+f"(d[0]), "+f"(d[1]), "+f"(d[2]), "+f"(d[3]), "+f"(d[4]), "+f"(d[5]), "+f"(d[6]), "+f"(d[7]), \
    "+f"(d[8]), "+f"(d[9]), "+f"(d[10]), "+f"(d[11]), "+f"(d[12]), "+f"(d[13]), "+f"(d[14]), "+f"(d[15]), \
    "+f"(d[16]), "+f"(d[17]), "+f"(d[18]), "+f"(d[19]), "+f"(d[20]), "+f"(d[21]), "+f"(d[22]), "+f"(d[23]), \
    "+f"(d[24]), "+f"(d[25]), "+f"(d[26]), "+f"(d[27]), "+f"(d[28]), "+f"(d[29]), "+f"(d[30]), "+f"(d[31]), \
    "+f"(d[32]), "+f"(d[33]), "+f"(d[34]), "+f"(d[35]), "+f"(d[36]), "+f"(d[37]), "+f"(d[38]), "+f"(d[39]), \
    "+f"(d[40]), "+f"(d[41]), "+f"(d[42]), "+f"(d[43]), "+f"(d[44]), "+f"(d[45]), "+f"(d[46]), "+f"(d[47]), \
    "+f"(d[48]), "+f"(d[49]), "+f"(d[50]), "+f"(d[51]), "+f"(d[52]), "+f"(d[53]), "+f"(d[54]), "+f"(d[55]), \
    "+f"(d[56]), "+f"(d[57]), "+f"(d[58]), "+f"(d[59]), "+f"(d[60]), "+f"(d[61]), "+f"(d[62]), "+f"(d[63])

#define ACC64_STR \
    "{%0, %1, %2, %3, %4, %5, %6, %7, %8, %9, %10, %11, %12, %13, %14, %15, " \
    "%16, %17, %18, %19, %20, %21, %22, %23, %24, %25, %26, %27, %28, %29, %30, %31, " \
    "%32, %33, %34, %35, %36, %37, %38, %39, %40, %41, %42, %43, %44, %45, %46, %47, " \
    "%48, %49, %50, %51, %52, %53, %54, %55, %56, %57, %58, %59, %60, %61, %62, %63}"

template <int TB>
__device__ __forceinline__ void wgmma_ss_n128(float (&d)[64], uint64_t da, uint64_t db, int scale_d) {
    asm volatile(
        "{\n.reg .pred p;\nsetp.ne.b32 p, %66, 0;\n"
        "wgmma.mma_async.sync.aligned.m64n128k16.f32.bf16.bf16 " ACC64_STR ", %64, %65, p, 1, 1, 0, %67;\n}\n"
        : ACC64(d)
        : "l"(da), "l"(db), "r"(scale_d), "n"(TB));
}
template <int TB>
__device__ __forceinline__ void wgmma_rs_n128(float (&d)[64], uint32_t a0, uint32_t a1, uint32_t a2, uint32_t a3,
                                              uint64_t db, int scale_d) {
    asm volatile(
        "{\n.reg .pred p;\nsetp.ne.b32 p, %69, 0;\n"
        "wgmma.mma_async.sync.aligned.m64n128k16.f32.bf16.bf16 " ACC64_STR ", {%64, %65, %66, %67}, %68, p, 1, 1, %70;\n}\n"
        : ACC64(d)
        : "r"(a0), "r"(a1), "r"(a2), "r"(a3), "l"(db), "r"(scale_d), "n"(TB));
}

constexpr uint32_t DESC_HI = 0x40000040u;
__device__ __forceinline__ uint32_t desc_lo(uint32_t saddr, uint32_t lbo_bytes) {
    return ((saddr & 0x3FFFF) >> 4) | ((lbo_bytes >> 4) << 16);
}
template <int TB>
__device__ __forceinline__ void wgmma_ss_lo(float (&d)[64], uint32_t da, uint32_t db, int scale_d) {
    asm volatile(
        "{\n.reg .pred p;\n.reg .b64 xa, xb;\nsetp.ne.b32 p, %66, 0;\n"
        "mov.b64 xa, {%64, %68};\nmov.b64 xb, {%65, %68};\n"
        "wgmma.mma_async.sync.aligned.m64n128k16.f32.bf16.bf16 " ACC64_STR ", xa, xb, p, 1, 1, 0, %67;\n}\n"
        : ACC64(d)
        : "r"(da), "r"(db), "r"(scale_d), "n"(TB), "r"(DESC_HI));
}
__device__ __forceinline__ void wgmma_rs_lo_tb(float (&d)[64], uint32_t a0, uint32_t a1, uint32_t a2, uint32_t a3, uint32_t db) {
    asm volatile(
        "{\n.reg .b64 xb;\nmov.b64 xb, {%68, %69};\n"
        "wgmma.mma_async.sync.aligned.m64n128k16.f32.bf16.bf16 " ACC64_STR ", {%64, %65, %66, %67}, xb, 1, 1, 1, 1;\n}\n"
        : ACC64(d)
        : "r"(a0), "r"(a1), "r"(a2), "r"(a3), "r"(db), "r"(DESC_HI));
}

#define ACC8(d, o) "+f"(d[o]), "+f"(d[o + 1]), "+f"(d[o + 2]), "+f"(d[o + 3]), "+f"(d[o + 4]), "+f"(d[o + 5]), "+f"(d[o + 6]), "+f"(d[o + 7])
__device__ __forceinline__ void wgmma_rs_n64(float (&d)[64], uint32_t a0, uint32_t a1, uint32_t a2, uint32_t a3, uint32_t db) {
    asm volatile(
        "{\n.reg .b64 xb;\nmov.b64 xb, {%36, %37};\n"
        "wgmma.mma_async.sync.aligned.m64n64k16.f32.bf16.bf16 "
        "{%0, %1, %2, %3, %4, %5, %6, %7, %8, %9, %10, %11, %12, %13, %14, %15, "
        "%16, %17, %18, %19, %20, %21, %22, %23, %24, %25, %26, %27, %28, %29, %30, %31}, "
        "{%32, %33, %34, %35}, xb, 1, 1, 1, 1;\n}\n"
        : ACC8(d, 0), ACC8(d, 8), ACC8(d, 16), ACC8(d, 24)
        : "r"(a0), "r"(a1), "r"(a2), "r"(a3), "r"(db), "r"(DESC_HI));
}
__device__ __forceinline__ void wgmma_rs_n72(float (&d)[64], float (&l)[4], uint32_t a0, uint32_t a1, uint32_t a2, uint32_t a3, uint32_t db) {
    asm volatile(
        "{\n.reg .b64 xb;\nmov.b64 xb, {%40, %41};\n"
        "wgmma.mma_async.sync.aligned.m64n72k16.f32.bf16.bf16 "
        "{%0, %1, %2, %3, %4, %5, %6, %7, %8, %9, %10, %11, %12, %13, %14, %15, "
        "%16, %17, %18, %19, %20, %21, %22, %23, %24, %25, %26, %27, %28, %29, %30, %31, %32, %33, %34, %35}, "
        "{%36, %37, %38, %39}, xb, 1, 1, 1, 1;\n}\n"
        : ACC8(d, 32), ACC8(d, 40), ACC8(d, 48), ACC8(d, 56), "+f"(l[0]), "+f"(l[1]), "+f"(l[2]), "+f"(l[3])
        : "r"(a0), "r"(a1), "r"(a2), "r"(a3), "r"(db), "r"(DESC_HI));
}

__global__ void __launch_bounds__(256) ln_kernel(const bf16* __restrict__ x) {
    pdl_launch();
    int warp = threadIdx.x >> 5, lane = threadIdx.x & 31;
    int row = blockIdx.x * 8 + warp;
    if (blockIdx.x == 0) g_cnt[threadIdx.x] = 0;
    if (blockIdx.x == 1 && threadIdx.x < 16) g_mask[threadIdx.x] = 0;
    const uint4* src = reinterpret_cast<const uint4*>(x + (size_t)row * DM);
    uint4 v[2];
    v[0] = src[lane];
    v[1] = src[lane + 32];
    float f[16];
#pragma unroll
    for (int i = 0; i < 2; i++) {
        const __nv_bfloat162* p = reinterpret_cast<const __nv_bfloat162*>(&v[i]);
#pragma unroll
        for (int j = 0; j < 4; j++) {
            float2 t = __bfloat1622float2(p[j]);
            f[i * 8 + j * 2] = t.x;
            f[i * 8 + j * 2 + 1] = t.y;
        }
    }
    float s = 0.f;
#pragma unroll
    for (int i = 0; i < 16; i++) s += f[i];
#pragma unroll
    for (int o = 16; o > 0; o >>= 1) s += __shfl_xor_sync(0xffffffffu, s, o);
    float mean = s * (1.0f / DM);
    float q = 0.f;
#pragma unroll
    for (int i = 0; i < 16; i++) {
        float d = f[i] - mean;
        q += d * d;
    }
#pragma unroll
    for (int o = 16; o > 0; o >>= 1) q += __shfl_xor_sync(0xffffffffu, q, o);
    float var_b = bf16_round(q * (1.0f / DM));
    float mean_b = bf16_round(mean);
    float den = bf16_round(sqrtf(bf16_round(var_b + 1e-5f)));
    uint4 o[2];
#pragma unroll
    for (int i = 0; i < 2; i++) {
        uint32_t* p = reinterpret_cast<uint32_t*>(&o[i]);
#pragma unroll
        for (int j = 0; j < 4; j++) {
            float a = bf16_round(f[i * 8 + j * 2] - mean_b) / den;
            float b = bf16_round(f[i * 8 + j * 2 + 1] - mean_b) / den;
            p[j] = pack_bf16(a, b);
        }
    }
    uint4* dst = reinterpret_cast<uint4*>(g_xn + (size_t)row * DM);
    dst[lane] = o[0];
    dst[lane + 32] = o[1];
}

constexpr int AT_STAGES = 3;
constexpr int TILE_BYTES = 128 * 128 * 2;
struct __align__(1024) AttnSmem {
    uint8_t k[AT_STAGES][TILE_BYTES];
    uint8_t v[AT_STAGES][TILE_BYTES];
    uint8_t o[TILE_BYTES];
    uint32_t ones0[4];
    uint64_t full_k[AT_STAGES], full_v[AT_STAGES], empty_k[AT_STAGES], empty_v[AT_STAGES];
    uint64_t st_free[2];
    uint64_t redo_bar;
    uint32_t redo;
    uint32_t pad0;
    uint32_t ones1[4];
    uint64_t fin_bar[4];
    uint32_t pad1[24];
    uint32_t ones2[(2048 - 288) / 4];
};

#define EXPO(x) x
#define N8(x) x
#define PPK 8
#define FAST_BIAS (-40.0f)
constexpr int NUM_CTAS = 132;
constexpr int MAX_ITEMS = 12;
enum { T_ATT = 0, T_F1 = 1, T_F2 = 2, T_OPE = 3, T_OPF = 4 };
struct Sched {
    uint16_t item[NUM_CTAS][MAX_ITEMS];
    uint8_t count[NUM_CTAS], end_att[NUM_CTAS], end_wide[NUM_CTAS];
};

__global__ void __launch_bounds__(384, 1)
attn_kernel(const __grid_constant__ CUtensorMap tm_xn, const __grid_constant__ CUtensorMap tm_wq,
            const __grid_constant__ CUtensorMap tm_k, const __grid_constant__ CUtensorMap tm_v,
            const __grid_constant__ CUtensorMap tm_o, const __grid_constant__ CUtensorMap tm_w1,
            const __grid_constant__ CUtensorMap tm_hst, const __grid_constant__ CUtensorMap tm_hld,
            const __grid_constant__ CUtensorMap tm_w2, const __grid_constant__ CUtensorMap tm_gst,
            const __grid_constant__ CUtensorMap tm_old, const __grid_constant__ CUtensorMap tm_wo,
            const bf16* __restrict__ x, bf16* __restrict__ out, const __grid_constant__ Sched sched) {
    extern __shared__ uint8_t smem_raw[];
    AttnSmem& sm = *reinterpret_cast<AttnSmem*>((reinterpret_cast<uintptr_t>(smem_raw) + 1023) & ~uintptr_t(1023));
    const int tid = threadIdx.x;
    const int wg = __shfl_sync(0xffffffffu, tid >> 7, 0);
    const int n_items = sched.count[blockIdx.x];
    if (tid == 32) {
        prefetch_tmap(&tm_xn); prefetch_tmap(&tm_wq); prefetch_tmap(&tm_k); prefetch_tmap(&tm_v); prefetch_tmap(&tm_o);
        prefetch_tmap(&tm_w1); prefetch_tmap(&tm_hst); prefetch_tmap(&tm_hld); prefetch_tmap(&tm_w2); prefetch_tmap(&tm_gst);
        prefetch_tmap(&tm_old); prefetch_tmap(&tm_wo);
    }

    if (tid == 0) {
#pragma unroll
        for (int s = 0; s < AT_STAGES; s++) {
            mbar_init(smem_u32(&sm.full_k[s]), 1);
            mbar_init(smem_u32(&sm.full_v[s]), 1);
            mbar_init(smem_u32(&sm.empty_k[s]), 8);
            mbar_init(smem_u32(&sm.empty_v[s]), 8);
        }
        mbar_init(smem_u32(&sm.st_free[0]), 1);
        mbar_init(smem_u32(&sm.st_free[1]), 1);
        mbar_init(smem_u32(&sm.redo_bar), 8);
#pragma unroll
        for (int s = 0; s < 4; s++) mbar_init(smem_u32(&sm.fin_bar[s]), 1);
        sm.redo = 0;
        asm volatile("fence.mbarrier_init.release.cluster;" ::: "memory");
    }
    if (tid < 64) {
        const int r = tid >> 2;
        sm.ones0[(r >> 3) * 256 + (r & 7) * 36 + (tid & 3)] = 0x3F803F80u;
        fence_proxy_async();
    }
    __syncthreads();
    pdl_wait();
    int it = 0;
    uint32_t rmask = 0;
    bool redo = false;
    auto next_item = [&]() -> bool {
        if (!redo) {
            if (++it < n_items) return true;
            mbar_wait(smem_u32(&sm.redo_bar), 0);
            rmask = *reinterpret_cast<volatile uint32_t*>(&sm.redo);
            rmask = (rmask | (rmask >> 16)) & 0xffffu;
            redo = true;
        }
        if (!rmask) return false;
        it = __ffs(rmask) - 1;
        rmask &= rmask - 1;
        return true;
    };
    constexpr int BAR_SCHED0 = 1, BAR_EPI0 = 3, BAR_ST0 = 5;

    if (wg == 0) {
        reg_dealloc<40>();
        if (tid >= 32 && tid < 96) {
            const int cw = (tid >> 5) - 1;
            const uint32_t obase = smem_u32(sm.o) + cw * 16384;
            do {
                const int item = sched.item[blockIdx.x][it];
                const int type = item >> 12, a = (item >> 4) & 0xff, b = item & 15;
                if (type == T_OPF) continue;
                if (type == T_F2) {
                    named_sync(BAR_ST0 + cw, 160);
                    if ((tid & 31) == 0) {
                        tma_store_3d(&tm_gst, obase, 0, b * 128 + cw * 64, a * 4);
                        tma_commit();
                        tma_wait_read0();
                        mbar_arrive(smem_u32(&sm.st_free[cw]));
                    }
                    __syncwarp();
                }
                named_sync(BAR_ST0 + cw, 160);
                if ((tid & 31) == 0) {
                    if (type == T_OPE) {
                        __threadfence();
                        atomicAdd(&g_cnt[C_P + b * 2 + (a & 1)], 1u);
                    } else {
                        if (redo) tma_wait_all0();
                        tma_store_3d(type == T_ATT ? &tm_o : (type == T_F1 ? &tm_hst : &tm_gst), obase, 0, b * 128 + cw * 64,
                                     type == T_F2 ? a * 4 + 2 : a * 2);
                        tma_commit();
                        tma_wait_read0();
                        mbar_arrive(smem_u32(&sm.st_free[cw]));
                        const bool bad = (*reinterpret_cast<volatile uint32_t*>(&sm.redo) >> (16 * cw + it)) & 1;
                        if (bad && !redo) atomicAdd(&g_cnt[C_BAD + b], 1u);
                        tma_wait_all0();
                        asm volatile("fence.proxy.async;" ::: "memory");
                        __threadfence();
                        if (type != T_ATT) atomicAdd(&g_cnt[type == T_F1 ? C_H + b : C_G + b * 2 + a], 1u);
                        else if (!redo) atomicOr(&g_mask[b], 1ull << (2 * a + cw));
                        else if (bad) atomicAdd(&g_cnt[C_RED + b], 1u);
                    }
                }
                __syncwarp();
            } while (next_item());
            if ((tid & 31) == 0) tma_wait_all0();
        }
        if (tid == 96) {
            int ord = 0;
            for (int i = 0; i < n_items; i++) {
                const int item = sched.item[blockIdx.x][i];
                const int a = (item >> 4) & 0xff, b = item & 15;
                if ((item >> 12) != T_OPF) continue;
                unsigned int spins = 0;
                while (ld_acq64(&g_mask[b]) != ~0ull && ++spins < (1u << 24)) {}
                while (ld_acq(&g_cnt[C_P + b * 2 + (a >> 1)]) < 2 * OPE_N && ++spins < (1u << 24)) {}
                while (ld_acq(&g_cnt[C_G + b * 2 + (a >> 1)]) < 2 && ++spins < (1u << 24)) {}
                if (ld_acq(&g_cnt[C_BAD + b])) atomicOr(&sm.redo, 1u << i);
                mbar_arrive(smem_u32(&sm.fin_bar[ord++]));
            }
        }
        if (tid == 0) {
            int stage = 0;
            uint32_t phase = 0;
            do {
                const int item = sched.item[blockIdx.x][it];
                const int type = item >> 12, a = (item >> 4) & 0xff, b = item & 15;
                const CUtensorMap* ta = type >= T_OPE ? &tm_old : (type == T_F2 ? &tm_hld : &tm_xn);
                const CUtensorMap* tb = type >= T_OPE ? &tm_wo : (type == T_ATT ? &tm_wq : (type == T_F1 ? &tm_w1 : &tm_w2));
                int nch = DM / 128, kc0 = 0, nb = a;
                unsigned long long need = 0, mask = 0;
                unsigned int spins = 0;
                if (type == T_F2) {
                    nch = FF / 128;
                    nb = a * 2;
                    while (ld_acq(&g_cnt[C_H + b]) < 2 * (FF / 128) && ++spins < (1u << 24)) {}
                    asm volatile("fence.proxy.async;" ::: "memory");
                } else if (type == T_OPE) {
                    nch = OPE_H;
                    kc0 = (a >> 2) * OPE_H;
                    nb = (a & 1) * 2;
                    need = 3ull << (2 * kc0);
                } else if (type == T_OPF) {
                    if (!redo) {
                        nch = OPF_H;
                        kc0 = NH - OPF_H;
                        need = 3ull << (2 * kc0);
                    } else {
                        nch = NH;
                        const unsigned int nbad = ld_acq(&g_cnt[C_BAD + b]);
                        while (ld_acq(&g_cnt[C_RED + b]) < nbad && ++spins < (1u << 24)) {}
                        asm volatile("fence.proxy.async;" ::: "memory");
                    }
                }
                for (int kc = kc0; kc < kc0 + nch; kc++) {
                    if ((mask & need) != need) {
                        do mask = ld_acq64(&g_mask[b]); while ((mask & need) != need && ++spins < (1u << 24));
                        asm volatile("fence.proxy.async;" ::: "memory");
                    }
                    need <<= 2;
                    mbar_wait(smem_u32(&sm.empty_k[stage]), phase ^ 1);
                    mbar_expect_tx(smem_u32(&sm.full_k[stage]), TILE_BYTES);
                    tma_load_3d(smem_u32(sm.k[stage]), ta, smem_u32(&sm.full_k[stage]), 0, b * 128, kc * 2);
                    mbar_wait(smem_u32(&sm.empty_v[stage]), phase ^ 1);
                    mbar_expect_tx(smem_u32(&sm.full_v[stage]), TILE_BYTES);
                    tma_load_3d(smem_u32(sm.v[stage]), tb, smem_u32(&sm.full_v[stage]), 0, kc * 128, nb * 2);
                    if (++stage == AT_STAGES) { stage = 0; phase ^= 1; }
                    if (type == T_F2 || type == T_OPE) {
                        mbar_wait(smem_u32(&sm.empty_v[stage]), phase ^ 1);
                        mbar_expect_tx(smem_u32(&sm.full_v[stage]), TILE_BYTES);
                        tma_load_3d(smem_u32(sm.v[stage]), tb, smem_u32(&sm.full_v[stage]), 0, kc * 128, nb * 2 + 2);
                        mbar_wait(smem_u32(&sm.empty_k[stage]), phase ^ 1);
                        mbar_arrive(smem_u32(&sm.full_k[stage]));
                        if (++stage == AT_STAGES) { stage = 0; phase ^= 1; }
                    }
                }
                if (type == T_ATT) {
                    for (int j = 0; j < 16; j++) {
                        mbar_wait(smem_u32(&sm.empty_k[stage]), phase ^ 1);
                        mbar_expect_tx(smem_u32(&sm.full_k[stage]), TILE_BYTES);
                        tma_load_3d(smem_u32(sm.k[stage]), &tm_k, smem_u32(&sm.full_k[stage]), 0, a * SEQ + j * 128, 0);
                        mbar_wait(smem_u32(&sm.empty_v[stage]), phase ^ 1);
                        mbar_expect_tx(smem_u32(&sm.full_v[stage]), TILE_BYTES);
                        tma_load_3d(smem_u32(sm.v[stage]), &tm_v, smem_u32(&sm.full_v[stage]), 0, a * SEQ + j * 128, 0);
                        if (++stage == AT_STAGES) { stage = 0; phase ^= 1; }
                    }
                }
            } while (next_item());
        }
    } else {
        reg_alloc<232>();
        const int cw = wg - 1;
        const int lane = tid & 31;
        const int warp_in_wg = (tid >> 5) & 3;
        const float c = 1.4426950408889634f;
        const uint32_t SCALE_HI2 = 0x3DB53DB5u, SCALE_LO2 = 0x371E371Eu;
        const uint32_t obase = smem_u32(sm.o) + cw * 16384;
        const int st_row = warp_in_wg * 16 + ((lane >> 3) & 1) * 8 + (lane & 7);

        const uint32_t dq = __shfl_sync(0xffffffffu, desc_lo(obase, 16), 0);
        const uint32_t dk0 = __shfl_sync(0xffffffffu, desc_lo(smem_u32(sm.k[0]), 16), 0);
        const uint32_t dv0 = dk0 - (1u << 16) + (1024u << 16) + AT_STAGES * (TILE_BYTES >> 4);

        PP(if (cw == 1) named_arrive(BAR_SCHED0 + 0, 256));

        int stage = 0;
        uint32_t phase = 0;
        float S[64];
        uint32_t P[32], P2[32];
        uint32_t cnt = 0;
        const uint32_t dw0 = __shfl_sync(0xffffffffu, desc_lo(smem_u32(sm.v[0]) + 16384, smem_u32(sm.ones0) - smem_u32(sm.v[0]) - 16384), 0);
        constexpr uint32_t DW_K = 128u - (128u << 16), DW_ST = 2048u - (2048u << 16);

        const uint32_t fk0 = smem_u32(&sm.full_k[0]), fv0 = smem_u32(&sm.full_v[0]);
        const uint32_t ek0 = smem_u32(&sm.empty_k[0]), ev0 = smem_u32(&sm.empty_v[0]);
        int vstage = 0;
        uint32_t vphase = 0;
        bool okk = false, okv = false;

        auto gemm_chunk = [&](float (&S)[64], bool acc, bool real) {
            if (real) {
                mbar_wait(fk0 + stage * 8, phase);
                mbar_wait(fv0 + stage * 8, phase);
            }
            const uint64_t da = make_desc(smem_u32(sm.k[stage]) + cw * 64 * 128, 16, 1024);
            const uint64_t db = make_desc(smem_u32(sm.v[stage]), 16384, 1024);
            wgmma_fence();
#pragma unroll
            for (int kk = 0; kk < 8; kk++) {
                wgmma_ss_n128<1>(S, da + (uint64_t)(((kk >> 2) * 16384 + (kk & 3) * 32) >> 4),
                                 db + (uint64_t)((kk * 2048) >> 4), acc || kk != 0);
            }
            wgmma_commit();
        };
        auto gemm_rest = [&](float (&S)[64], int nch) {
            int prev = stage;
            if (++stage == AT_STAGES) { stage = 0; phase ^= 1; }
#pragma unroll 1
            for (int kc = 1; kc < nch; kc++) {
                gemm_chunk(S, true, true);
                wgmma_wait<1>();
                if (lane == 0) {
                    mbar_arrive(ek0 + prev * 8);
                    mbar_arrive(ev0 + prev * 8);
                }
                prev = stage;
                if (++stage == AT_STAGES) { stage = 0; phase ^= 1; }
            }
            wgmma_wait<0>();
            if (lane == 0) {
                mbar_arrive(ek0 + prev * 8);
                mbar_arrive(ev0 + prev * 8);
            }
        };
        auto gemm_wide = [&](float (&S)[64], float (&W)[64], int nch) {
            auto odd = [&](int sa, bool acc) {
                mbar_wait(fk0 + stage * 8, phase);
                mbar_wait(fv0 + stage * 8, phase);
                const uint64_t da = make_desc(smem_u32(sm.k[sa]) + cw * 64 * 128, 16, 1024);
                const uint64_t db = make_desc(smem_u32(sm.v[stage]), 16384, 1024);
                wgmma_fence();
#pragma unroll
                for (int kk = 0; kk < 8; kk++) {
                    wgmma_ss_n128<1>(W, da + (uint64_t)(((kk >> 2) * 16384 + (kk & 3) * 32) >> 4),
                                     db + (uint64_t)((kk * 2048) >> 4), acc || kk != 0);
                }
                wgmma_commit();
                wgmma_wait<1>();
                if (lane == 0) mbar_arrive(ev0 + sa * 8);
            };
            int sa = stage;
            if (++stage == AT_STAGES) { stage = 0; phase ^= 1; }
#pragma unroll 1
            for (int kc = 1; kc < nch; kc++) {
                odd(sa, kc != 1);
                const int sb = stage;
                if (++stage == AT_STAGES) { stage = 0; phase ^= 1; }
                gemm_chunk(S, true, true);
                wgmma_wait<1>();
                if (lane == 0) {
                    mbar_arrive(ek0 + sa * 8);
                    mbar_arrive(ek0 + sb * 8);
                    mbar_arrive(ev0 + sb * 8);
                }
                sa = stage;
                if (++stage == AT_STAGES) { stage = 0; phase ^= 1; }
            }
            odd(sa, true);
            wgmma_wait<0>();
            if (lane == 0) {
                mbar_arrive(ek0 + sa * 8);
                mbar_arrive(ek0 + stage * 8);
                mbar_arrive(ev0 + stage * 8);
            }
            if (++stage == AT_STAGES) { stage = 0; phase ^= 1; }
        };
        auto pack_p = [&](float (&S)[64]) {
#pragma unroll
            for (int i = 0; i < 32; i++) P[i] = pack_bf16(S[2 * i], S[2 * i + 1]);
        };
        auto final_epi = [&](float (&T)[64], int mb, int nb) {
            mbar_wait(smem_u32(&sm.st_free[cw]), (cnt & 1) ^ 1);
#pragma unroll
            for (int i = 0; i < 16; i += 2) {
                const int cc = i + (lane >> 4);
                const uint32_t addr = obase + (cc >> 3) * 8192 + st_row * 128 + (((cc & 7) ^ (st_row & 7)) << 4);
                stmatrix_x4(addr, pack_bf16(T[4 * i], T[4 * i + 1]), pack_bf16(T[4 * i + 2], T[4 * i + 3]),
                            pack_bf16(T[4 * i + 4], T[4 * i + 5]), pack_bf16(T[4 * i + 6], T[4 * i + 7]));
            }
            const int t = tid & 127, ch = t & 15, row0 = t >> 4;
            const size_t off = (size_t)(mb * 128 + cw * 64 + row0) * DM + nb * 128 + ch * 8;
            uint4 xv[8], gv[8];
#pragma unroll
            for (int i = 0; i < 8; i++) {
                xv[i] = *reinterpret_cast<const uint4*>(x + off + (size_t)i * 8 * DM);
                gv[i] = __ldcg(reinterpret_cast<const uint4*>(g_g + off + (size_t)i * 8 * DM));
            }
            named_sync(BAR_EPI0 + cw, 128);
            const uint32_t sa = obase + (ch >> 3) * 8192 + row0 * 128 + (((ch & 7) ^ row0) << 4);
#pragma unroll
            for (int i = 0; i < 8; i++) {
                uint4 sv;
                asm volatile("ld.shared.v4.u32 {%0, %1, %2, %3}, [%4];" : "=r"(sv.x), "=r"(sv.y), "=r"(sv.z), "=r"(sv.w) : "r"(sa + i * 1024));
                sv.x = add_bf16x2(xv[i].x, mul_bf16x2(sv.x, gv[i].x));
                sv.y = add_bf16x2(xv[i].y, mul_bf16x2(sv.y, gv[i].y));
                sv.z = add_bf16x2(xv[i].z, mul_bf16x2(sv.z, gv[i].z));
                sv.w = add_bf16x2(xv[i].w, mul_bf16x2(sv.w, gv[i].w));
                *reinterpret_cast<uint4*>(out + off + (size_t)i * 8 * DM) = sv;
            }
            named_sync(BAR_EPI0 + cw, 128);
        };
        auto stage_p = [&](uint32_t (&P)[32]) {
            mbar_wait(smem_u32(&sm.st_free[cw]), (cnt & 1) ^ 1);
            cnt++;
#pragma unroll
            for (int i = 0; i < 16; i += 2) {
                const int cc = i + (lane >> 4);
                const uint32_t addr = obase + (cc >> 3) * 8192 + st_row * 128 + (((cc & 7) ^ (st_row & 7)) << 4);
                stmatrix_x4(addr, P[2 * i], P[2 * i + 1], P[2 * i + 2], P[2 * i + 3]);
            }
            fence_proxy_async();
        };
        auto issue_qk = [&](uint32_t dk) {
            wgmma_fence();
#pragma unroll
            for (int kk = 0; kk < 8; kk++)
                wgmma_ss_lo<0>(S, dq + (((kk >> 2) * 8192 + (kk & 3) * 32) >> 4),
                               dk + (((kk >> 2) * 16384 + (kk & 3) * 32) >> 4), kk != 0);
            wgmma_commit();
        };
        auto issue_pv = [&](float (&O)[64], float (&L)[4], uint32_t (&Pc)[32], int vs) {
            const uint32_t dv = dv0 + vs * (TILE_BYTES >> 4), dw = dw0 + vs * DW_ST;
            wgmma_fence();
#pragma unroll
            for (int kk = 0; kk < 8; kk++) {
                wgmma_rs_n64(O, Pc[4 * kk], Pc[4 * kk + 1], Pc[4 * kk + 2], Pc[4 * kk + 3], dv + ((kk * 2048) >> 4));
                wgmma_rs_n72(O, L, Pc[4 * kk], Pc[4 * kk + 1], Pc[4 * kk + 2], Pc[4 * kk + 3], dw + kk * DW_K);
            }
            wgmma_commit();
        };
        auto epilogue = [&](float (&O)[64], float (&L)[4]) {
            const float i0 = 1.0f / L[0], i1 = 1.0f / L[2];
            named_sync(BAR_EPI0 + cw, 128);
#pragma unroll
            for (int i = 0; i < 16; i += 2) {
                const int cc = i + (lane >> 4);
                const uint32_t addr = obase + (cc >> 3) * 8192 + st_row * 128 + (((cc & 7) ^ (st_row & 7)) << 4);
                stmatrix_x4(addr, pack_bf16(O[4 * i] * i0, O[4 * i + 1] * i0), pack_bf16(O[4 * i + 2] * i1, O[4 * i + 3] * i1),
                            pack_bf16(O[4 * i + 4] * i0, O[4 * i + 5] * i0), pack_bf16(O[4 * i + 6] * i1, O[4 * i + 7] * i1));
            }
            fence_proxy_async();
            named_arrive(BAR_ST0 + cw, 160);
        };
        auto scores_max = [&](uint32_t (&T)[32], float& x0, float& x1) {
#pragma unroll
            for (int i = 0; i < 32; i++) {
                const uint32_t sb = pack_bf16(S[2 * i], S[2 * i + 1]);
                T[i] = fma_bf16x2(sb, SCALE_HI2, mul_bf16x2(sb, SCALE_LO2));
            }
            uint32_t y0 = max_bf16x2(T[0], T[2]), y1 = max_bf16x2(T[1], T[3]);
#pragma unroll
            for (int i = 2; i < 16; i++) {
                y0 = max_bf16x2(y0, T[2 * i]);
                y1 = max_bf16x2(y1, T[2 * i + 1]);
            }
            x0 = fmaxf(bf16lo(y0), bf16hi(y0));
            x1 = fmaxf(bf16lo(y1), bf16hi(y1));
            x0 = fmaxf(x0, __shfl_xor_sync(0xffffffffu, x0, 1));
            x1 = fmaxf(x1, __shfl_xor_sync(0xffffffffu, x1, 1));
            x0 = fmaxf(x0, __shfl_xor_sync(0xffffffffu, x0, 2));
            x1 = fmaxf(x1, __shfl_xor_sync(0xffffffffu, x1, 2));
        };
        auto first_block = [&]() {
            stage_p(P);
            named_sync(BAR_EPI0 + cw, 128);
            vstage = stage;
            vphase = phase;
            mbar_wait(fk0 + stage * 8, phase);
            PP(named_sync(BAR_SCHED0 + cw, 256));
            issue_qk(dk0 + stage * (TILE_BYTES >> 4));
            PP(named_arrive(BAR_SCHED0 + (cw ^ 1), 256));
            if (++stage == AT_STAGES) { stage = 0; phase ^= 1; }
            okk = mbar_try_wait(fk0 + stage * 8, phase);
            okv = mbar_try_wait(fv0 + vstage * 8, vphase);
            wgmma_wait<0>();
            if (lane == 0) mbar_arrive(ek0 + vstage * 8);
        };

        int nfin = 0;
        gemm_chunk(S, false, true);
#pragma unroll 1
        for (; it < sched.end_att[blockIdx.x]; it++) {
            const int item = sched.item[blockIdx.x][it];
            const int type = item >> 12;
            const bool has_next = it + 1 < n_items;
            gemm_rest(S, DM / 128);
            if (type == T_F1) {
                pack_p(S);
                gemm_chunk(S, false, has_next);
#pragma unroll
                for (int i = 0; i < 32; i++) P[i] = pack_bf16(silu_f(bf16lo(P[i])), silu_f(bf16hi(P[i])));
                stage_p(P);
                named_arrive(BAR_ST0 + cw, 160);
            } else {
                pack_p(S);
                first_block();
                float O[64], L[4] = {0.f, 0.f, 0.f, 0.f};
#pragma unroll
                for (int i = 0; i < 64; i++) O[i] = 0.f;
                float n0, n1;
                {
                    float x0, x1;
                    scores_max(P2, x0, x1);
                    n0 = fmaf(-x0, c, FAST_BIAS);
                    n1 = fmaf(-x1, c, FAST_BIAS);
#pragma unroll
                    for (int i = 0; i < 16; i++) {
                        const float e0 = ex2(fmaf(bf16lo(P2[2 * i]), c, n0));
                        const float e1 = ex2(fmaf(bf16hi(P2[2 * i]), c, n0));
                        const float e2 = ex2(fmaf(bf16lo(P2[2 * i + 1]), c, n1));
                        const float e3 = ex2(fmaf(bf16hi(P2[2 * i + 1]), c, n1));
                        P[2 * i] = pack_bf16(e0, e1);
                        P[2 * i + 1] = pack_bf16(e2, e3);
                    }
                }
                auto expo = [&](uint32_t (&Pn)[32], int i_lo, int i_hi) {
#pragma unroll
                    for (int i = i_lo; i < i_hi; i++) {
                        const uint32_t sa = pack_bf16(S[4 * i], S[4 * i + 1]), sb = pack_bf16(S[4 * i + 2], S[4 * i + 3]);
                        const uint32_t ta = fma_bf16x2(sa, SCALE_HI2, mul_bf16x2(sa, SCALE_LO2));
                        const uint32_t tb = fma_bf16x2(sb, SCALE_HI2, mul_bf16x2(sb, SCALE_LO2));
                        const float e0 = ex2(fmaf(bf16lo(ta), c, n0));
                        const float e1 = ex2(fmaf(bf16hi(ta), c, n0));
                        const float e2 = ex2(fmaf(bf16lo(tb), c, n1));
                        float e3 = ex2(fmaf(bf16hi(tb), c, n1));
                        if (i == i_hi - 1 && i_hi < 16) while (e3 < 0.f) e3 = g_dummy;
                        Pn[2 * i] = pack_bf16(e0, e1);
                        Pn[2 * i + 1] = pack_bf16(e2, e3);
                    }
                };
                auto step = [&](uint32_t (&Pc)[32], uint32_t (&Pn)[32]) {
                    const int ust = __shfl_sync(0xffffffffu, stage, 0), uvs = __shfl_sync(0xffffffffu, vstage, 0);
                    if (!okk) mbar_wait(fk0 + stage * 8, phase);
                    if (!okv) mbar_wait(fv0 + vstage * 8, vphase);
                    PP(named_sync(BAR_SCHED0 + cw, 256));
                    issue_qk(dk0 + ust * (TILE_BYTES >> 4));
                    issue_pv(O, L, Pc, uvs);
                    PP(named_arrive(BAR_SCHED0 + (cw ^ 1), 256));
                    const int pv = vstage;
                    vstage = stage;
                    vphase = phase;
                    if (++stage == AT_STAGES) { stage = 0; phase ^= 1; }
                    okk = mbar_try_wait(fk0 + stage * 8, phase);
                    okv = mbar_try_wait(fv0 + vstage * 8, vphase);
                    wgmma_wait<1>();
                    if (lane == 0) mbar_arrive(ek0 + vstage * 8);
                    EXPO(expo(Pn, 0, 8));
                    wgmma_wait<0>();
                    if (lane == 0) mbar_arrive(ev0 + pv * 8);
                    EXPO(expo(Pn, 8, 16));
                };
#pragma unroll 1
                for (int j = 0; j < 7; j++) {
                    step(P, P2);
                    step(P2, P);
                }
                step(P, P2);
                if (!okv) mbar_wait(fv0 + vstage * 8, vphase);
                issue_pv(O, L, P2, vstage);
                gemm_chunk(S, false, has_next);
                wgmma_wait<1>();
                if (lane == 0) mbar_arrive(ev0 + vstage * 8);
                float z = fmaf(L[0], 0.f, L[2] * 0.f);
#pragma unroll
                for (int i = 0; i < 64; i++) z = fmaf(O[i], 0.f, z);
                if (__any_sync(0xffffffffu, z != 0.f) && lane == 0) atomicOr(&sm.redo, 1u << (16 * cw + it));
                epilogue(O, L);
            }
        }
        wgmma_wait<0>();
        float S2[64], S3[64];
        fence_acc(S);
#pragma unroll
        for (int i = 0; i < 64; i++) S2[i] = S[i] + 0.f;
        fence_acc(S2);
#pragma unroll 1
        for (; it < sched.end_wide[blockIdx.x]; it++) {
            const int item = sched.item[blockIdx.x][it];
            const int type = item >> 12, a = (item >> 4) & 0xff, b = item & 15;
            const bool has_next = it + 1 < n_items;
            float W[64];
            gemm_wide(S2, W, type == T_F2 ? FF / 128 : OPE_H);
            if (type == T_F2) {
                pack_p(S2);
#pragma unroll
                for (int i = 0; i < 32; i++) P2[i] = pack_bf16(W[2 * i], W[2 * i + 1]);
                gemm_chunk(S2, false, has_next);
#pragma unroll
                for (int i = 0; i < 32; i++) P[i] = pack_bf16(silu_f(bf16lo(P[i])), silu_f(bf16hi(P[i])));
                stage_p(P);
                named_arrive(BAR_ST0 + cw, 160);
#pragma unroll
                for (int i = 0; i < 32; i++) P2[i] = pack_bf16(silu_f(bf16lo(P2[i])), silu_f(bf16hi(P2[i])));
                stage_p(P2);
                named_arrive(BAR_ST0 + cw, 160);
            } else {
                float T[64];
#pragma unroll
                for (int i = 0; i < 64; i++) T[i] = S2[i] + 0.f;
                fence_acc(T);
                gemm_chunk(S2, false, has_next);
                float4* part = g_part + (size_t)(((a >> 2) * 16 + b) * 4 + (a & 1) * 2) * (16 * 256) + (tid - 128);
#pragma unroll
                for (int j = 0; j < 16; j++) __stcg(part + j * 256, make_float4(T[4 * j], T[4 * j + 1], T[4 * j + 2], T[4 * j + 3]));
#pragma unroll
                for (int j = 0; j < 16; j++) __stcg(part + (16 + j) * 256, make_float4(W[4 * j], W[4 * j + 1], W[4 * j + 2], W[4 * j + 3]));
                named_arrive(BAR_ST0 + cw, 160);
            }
        }
        wgmma_wait<0>();
        fence_acc(S2);
#pragma unroll
        for (int i = 0; i < 64; i++) S3[i] = S2[i] + 0.f;
        fence_acc(S3);
#pragma unroll 1
        for (; it < n_items; it++) {
            const int item = sched.item[blockIdx.x][it];
            const int a = (item >> 4) & 0xff, b = item & 15;
            gemm_rest(S3, OPF_H);
            float T[64];
#pragma unroll
            for (int i = 0; i < 64; i++) T[i] = S3[i] + 0.f;
            fence_acc(T);
            gemm_chunk(S3, false, it + 1 < n_items);
            const float4* part = g_part + (size_t)(b * 4 + a) * (16 * 256) + (tid - 128);
            mbar_wait(smem_u32(&sm.fin_bar[nfin++]), 0);
            if (!((*reinterpret_cast<volatile uint32_t*>(&sm.redo) >> it) & 1)) {
#pragma unroll
                for (int g = 0; g < OPE_N; g++) {
#pragma unroll
                    for (int j = 0; j < 16; j++) {
                        const float4 v = __ldcg(part + (size_t)g * (64 * 16 * 256) + j * 256);
                        T[4 * j] += v.x;
                        T[4 * j + 1] += v.y;
                        T[4 * j + 2] += v.z;
                        T[4 * j + 3] += v.w;
                    }
                }
                final_epi(T, b, a);
            }
        }
        wgmma_wait<0>();
        __syncwarp();
        if (lane == 0) mbar_arrive(smem_u32(&sm.redo_bar));
        mbar_wait(smem_u32(&sm.redo_bar), 0);
        rmask = *reinterpret_cast<volatile uint32_t*>(&sm.redo);
        rmask = (rmask | (rmask >> 16)) & 0xffffu;
#pragma unroll 1
        for (; rmask && (sched.item[blockIdx.x][__ffs(rmask) - 1] >> 12) == T_ATT; rmask &= rmask - 1) {
            gemm_chunk(S, false, true);
            gemm_rest(S, DM / 128);
            pack_p(S);
            first_block();
            float O[64], L[4] = {0.f, 0.f, 0.f, 0.f};
#pragma unroll
            for (int i = 0; i < 64; i++) O[i] = 0.f;
            float m0 = -INFINITY, m1 = -INFINITY;
#pragma unroll 1
            for (int j = 0; j < 16; j++) {
                float x0, x1;
                scores_max(P2, x0, x1);
                x0 = fmaxf(x0, m0);
                x1 = fmaxf(x1, m1);
                const float a0 = ex2((m0 - x0) * c), a1 = ex2((m1 - x1) * c);
                m0 = x0;
                m1 = x1;
                const float n0 = -m0 * c, n1 = -m1 * c;
#pragma unroll
                for (int i = 0; i < 16; i++) {
                    const float e0 = ex2(fmaf(bf16lo(P2[2 * i]), c, n0));
                    const float e1 = ex2(fmaf(bf16hi(P2[2 * i]), c, n0));
                    const float e2 = ex2(fmaf(bf16lo(P2[2 * i + 1]), c, n1));
                    const float e3 = ex2(fmaf(bf16hi(P2[2 * i + 1]), c, n1));
                    P[2 * i] = pack_bf16(e0, e1);
                    P[2 * i + 1] = pack_bf16(e2, e3);
                    O[4 * i] *= a0;
                    O[4 * i + 1] *= a0;
                    O[4 * i + 2] *= a1;
                    O[4 * i + 3] *= a1;
                }
                L[0] *= a0;
                L[1] *= a0;
                L[2] *= a1;
                L[3] *= a1;
                mbar_wait(fv0 + vstage * 8, vphase);
                issue_pv(O, L, P, vstage);
                wgmma_wait<0>();
                if (lane == 0) mbar_arrive(ev0 + vstage * 8);
                if (j < 15) {
                    mbar_wait(fk0 + stage * 8, phase);
                    issue_qk(dk0 + stage * (TILE_BYTES >> 4));
                    wgmma_wait<0>();
                    if (lane == 0) mbar_arrive(ek0 + stage * 8);
                    vstage = stage;
                    vphase = phase;
                    if (++stage == AT_STAGES) { stage = 0; phase ^= 1; }
                }
            }
            epilogue(O, L);
        }
#pragma unroll 1
        for (; rmask; rmask &= rmask - 1) {
            const int item = sched.item[blockIdx.x][__ffs(rmask) - 1];
            gemm_chunk(S, false, true);
            gemm_rest(S, NH);
            final_epi(S, item & 15, (item >> 4) & 0xff);
        }
    }
}

typedef CUresult (*EncodeFn)(CUtensorMap*, CUtensorMapDataType, cuuint32_t, void*, const cuuint64_t*, const cuuint64_t*,
                             const cuuint32_t*, const cuuint32_t*, CUtensorMapInterleave, CUtensorMapSwizzle,
                             CUtensorMapL2promotion, CUtensorMapFloatOOBfill);

static CUtensorMap make_map(EncodeFn fn, const void* ptr, uint64_t rows, uint64_t cols, uint32_t box_rows, uint32_t box_blk) {
    CUtensorMap m;
    cuuint64_t dims[3] = {64, rows, cols / 64};
    cuuint64_t strides[2] = {cols * 2, 128};
    cuuint32_t box[3] = {64, box_rows, box_blk};
    cuuint32_t es[3] = {1, 1, 1};
    fn(&m, CU_TENSOR_MAP_DATA_TYPE_BFLOAT16, 3, const_cast<void*>(ptr), dims, strides, box, es, CU_TENSOR_MAP_INTERLEAVE_NONE,
       CU_TENSOR_MAP_SWIZZLE_128B, CU_TENSOR_MAP_L2_PROMOTION_L2_256B, CU_TENSOR_MAP_FLOAT_OOB_FILL_NONE);
    return m;
}

extern "C" void kernel_launch(void* const* d_in, const int* in_sizes, int n_in, void* d_out, int out_size) {
    const bf16* x = (const bf16*)d_in[0];
    const bf16* kc = (const bf16*)d_in[1];
    const bf16* vc = (const bf16*)d_in[2];
    const bf16* wq = (const bf16*)d_in[3];
    const bf16* wo = (const bf16*)d_in[4];
    const bf16* w1 = (const bf16*)d_in[6];
    const bf16* w2 = (const bf16*)d_in[7];
    bf16* out = (bf16*)d_out;

    static EncodeFn fn = nullptr;
    static void *p_xn = nullptr, *p_h = nullptr, *p_o = nullptr, *p_g = nullptr;
    static Sched sched;
    if (!fn) {
        void* f = nullptr;
        cudaDriverEntryPointQueryResult st;
        cudaGetDriverEntryPoint("cuTensorMapEncodeTiled", &f, cudaEnableDefault, &st);
        fn = (EncodeFn)f;
        cudaGetSymbolAddress(&p_xn, g_xn);
        cudaGetSymbolAddress(&p_h, g_h);
        cudaGetSymbolAddress(&p_o, g_o);
        cudaGetSymbolAddress(&p_g, g_g);
        cudaFuncSetAttribute(attn_kernel, cudaFuncAttributeMaxDynamicSharedMemorySize, (int)sizeof(AttnSmem) + 1024);
        static const struct { int n, n1; const char* tail; } cls[] = {
            {20, 0, "G"}, {12, 1, "G"}, {32, 1, "E"}, {4, 1, "OO"}, {40, 3, "O"}, {8, 5, ""}, {16, 1, "EEO"}};
        int t1 = 0, t2 = 0, t3 = 0, t4 = 0, i = 0;
        for (const auto& cl : cls) {
            for (int c = 0; c < cl.n; c++, i++) {
                int n = 0;
                for (int j = 0; j < cl.n1; j++, t1++) sched.item[i][n++] = (uint16_t)((T_F1 << 12) | ((t1 % 14) << 4) | (t1 / 14));
                for (int t = i; t < NH * 16; t += NUM_CTAS) sched.item[i][n++] = (uint16_t)((T_ATT << 12) | ((t >> 4) << 4) | (t & 15));
                sched.end_att[i] = sched.end_wide[i] = (uint8_t)n;
                for (const char* p = cl.tail; *p; p++) {
                    if (*p == 'G') { sched.item[i][n++] = (uint16_t)((T_F2 << 12) | ((t2 & 1) << 4) | (t2 >> 1)); t2++; }
                    if (*p == 'E') { sched.item[i][n++] = (uint16_t)((T_OPE << 12) | (((t3 & 1) | ((t3 >> 5) << 2)) << 4) | ((t3 >> 1) & 15)); t3++; }
                    if (*p != 'O') sched.end_wide[i] = (uint8_t)n;
                    if (*p == 'O') { sched.item[i][n++] = (uint16_t)((T_OPF << 12) | ((t4 & 3) << 4) | (t4 >> 2)); t4++; }
                }
                sched.count[i] = (uint8_t)n;
            }
        }
    }
    CUtensorMap tm_xn_at = make_map(fn, p_xn, SEQ, DM, 128, 2);
    CUtensorMap tm_wq = make_map(fn, wq, DM, NH * DH, 128, 2);
    CUtensorMap tm_k = make_map(fn, kc, NH * SEQ, DH, 128, 2);
    CUtensorMap tm_v = make_map(fn, vc, NH * SEQ, DH, 128, 2);
    CUtensorMap tm_o_st = make_map(fn, p_o, SEQ, NH * DH, 64, 2);
    CUtensorMap tm_w1 = make_map(fn, w1, DM, FF, 128, 2);
    CUtensorMap tm_h_st = make_map(fn, p_h, SEQ, FF, 64, 2);
    CUtensorMap tm_h_ld = make_map(fn, p_h, SEQ, FF, 128, 2);
    CUtensorMap tm_w2 = make_map(fn, w2, FF, DM, 128, 2);
    CUtensorMap tm_g_st = make_map(fn, p_g, SEQ, DM, 64, 2);
    CUtensorMap tm_o_g = make_map(fn, p_o, SEQ, NH * DH, 128, 2);
    CUtensorMap tm_wo = make_map(fn, wo, NH * DH, DM, 128, 2);

    ln_kernel<<<SEQ / 8, 256>>>(x);
    cudaLaunchAttribute pdl[1];
    pdl[0].id = cudaLaunchAttributeProgrammaticStreamSerialization;
    pdl[0].val.programmaticStreamSerializationAllowed = 1;
    cudaLaunchConfig_t cfg = {};
    cfg.gridDim = dim3(NUM_CTAS);
    cfg.blockDim = dim3(384);
    cfg.dynamicSmemBytes = sizeof(AttnSmem) + 1024;
    cfg.stream = cudaStreamPerThread;
    cfg.attrs = pdl;
    cfg.numAttrs = 1;
    cudaLaunchKernelEx(&cfg, attn_kernel, tm_xn_at, tm_wq, tm_k, tm_v, tm_o_st, tm_w1, tm_h_st, tm_h_ld, tm_w2, tm_g_st, tm_o_g,
                       tm_wo, x, out, sched);
}
```

```cpp
#include <cuda_runtime.h>
#include <cuda_bf16.h>
#include <cuda.h>
#include <stdint.h>

typedef __nv_bfloat16 bf16;
#define PP(x) x

constexpr int SEQ = 2048, DM = 512, NH = 32, DH = 128, FF = 1792;

__device__ __align__(1024) bf16 g_xn[SEQ * DM];
__device__ __align__(1024) bf16 g_h[SEQ * FF];
__device__ __align__(1024) bf16 g_o[SEQ * NH * DH];
__device__ __align__(1024) bf16 g_g[SEQ * DM];
constexpr int C_H = 0, C_G = 16, C_P = C_G + 64, C_BAD = C_P + 64, C_RED = C_BAD + 16;
__device__ unsigned int g_cnt[256];
__device__ unsigned long long g_mask[16];
constexpr int OPE_N = 2, OPE_H = 12, OPF_H = NH - OPE_N * OPE_H;
__device__ float4 g_part[OPE_N * 64 * 16 * 256];
__device__ volatile float g_dummy;

__device__ __forceinline__ uint32_t smem_u32(const void* p) { return (uint32_t)__cvta_generic_to_shared(p); }

__device__ __forceinline__ void mbar_init(uint32_t bar, uint32_t count) {
    asm volatile("mbarrier.init.shared::cta.b64 [%0], %1;" ::"r"(bar), "r"(count) : "memory");
}
__device__ __forceinline__ void mbar_expect_tx(uint32_t bar, uint32_t bytes) {
    asm volatile("mbarrier.arrive.expect_tx.shared::cta.b64 _, [%0], %1;" ::"r"(bar), "r"(bytes) : "memory");
}
__device__ __forceinline__ void mbar_arrive(uint32_t bar) {
    asm volatile("mbarrier.arrive.shared::cta.b64 _, [%0];" ::"r"(bar) : "memory");
}
__device__ __forceinline__ bool mbar_try_wait(uint32_t bar, uint32_t parity) {
    uint32_t ok;
    asm volatile(
        "{\n.reg .pred p;\n"
        "mbarrier.test_wait.parity.shared::cta.b64 p, [%1], %2;\n"
        "selp.u32 %0, 1, 0, p;\n}\n"
        : "=r"(ok)
        : "r"(bar), "r"(parity)
        : "memory");
    return ok != 0;
}
__device__ __forceinline__ void mbar_wait(uint32_t bar, uint32_t parity) {
    asm volatile(
        "{\n.reg .pred P1;\n.reg .u32 n;\nmov.u32 n, 0;\n"
        "LAB_WAIT:\n"
        "mbarrier.try_wait.parity.shared::cta.b64 P1, [%0], %1;\n"
        "@P1 bra DONE;\n"
        "add.u32 n, n, 1;\n"
        "setp.lt.u32 P1, n, 4194304;\n"
        "@P1 bra LAB_WAIT;\n"
        "trap;\n"
        "DONE:\n}\n" ::"r"(bar), "r"(parity)
        : "memory");
}
__device__ __forceinline__ void tma_load_3d(uint32_t dst, const CUtensorMap* map, uint32_t bar, int c0, int c1, int c2) {
    asm volatile(
        "cp.async.bulk.tensor.3d.shared::cluster.global.mbarrier::complete_tx::bytes [%0], [%1, {%3, %4, %5}], [%2];"
        ::"r"(dst), "l"((uint64_t)map), "r"(bar), "r"(c0), "r"(c1), "r"(c2)
        : "memory");
}
__device__ __forceinline__ void tma_store_3d(const CUtensorMap* map, uint32_t src, int c0, int c1, int c2) {
    asm volatile("cp.async.bulk.tensor.3d.global.shared::cta.bulk_group [%0, {%2, %3, %4}], [%1];"
                 ::"l"((uint64_t)map), "r"(src), "r"(c0), "r"(c1), "r"(c2)
                 : "memory");
}
__device__ __forceinline__ void tma_commit() { asm volatile("cp.async.bulk.commit_group;" ::: "memory"); }
__device__ __forceinline__ void tma_wait_read0() { asm volatile("cp.async.bulk.wait_group.read 0;" ::: "memory"); }
__device__ __forceinline__ void tma_wait_all0() { asm volatile("cp.async.bulk.wait_group 0;" ::: "memory"); }
__device__ __forceinline__ void fence_proxy_async() { asm volatile("fence.proxy.async.shared::cta;" ::: "memory"); }
__device__ __forceinline__ void prefetch_tmap(const CUtensorMap* map) {
    asm volatile("prefetch.tensormap [%0];" ::"l"((uint64_t)map) : "memory");
}
__device__ __forceinline__ void pdl_wait() { asm volatile("griddepcontrol.wait;" ::: "memory"); }
__device__ __forceinline__ void pdl_launch() { asm volatile("griddepcontrol.launch_dependents;" ::: "memory"); }
__device__ __forceinline__ void named_sync(int id, int n) { asm volatile("bar.sync %0, %1;" ::"r"(id), "r"(n) : "memory"); }
__device__ __forceinline__ void named_arrive(int id, int n) { asm volatile("bar.arrive %0, %1;" ::"r"(id), "r"(n) : "memory"); }

__device__ __forceinline__ void wgmma_fence() { asm volatile("wgmma.fence.sync.aligned;" ::: "memory"); }
__device__ __forceinline__ void wgmma_commit() { asm volatile("wgmma.commit_group.sync.aligned;" ::: "memory"); }
template <int N>
__device__ __forceinline__ void wgmma_wait() { asm volatile("wgmma.wait_group.sync.aligned %0;" ::"n"(N) : "memory"); }

__device__ __forceinline__ void fence_acc(float (&d)[64]) {
#pragma unroll
    for (int i = 0; i < 64; i++) asm volatile("" : "+f"(d[i])::"memory");
}

template <int R>
__device__ __forceinline__ void reg_alloc() { asm volatile("setmaxnreg.inc.sync.aligned.u32 %0;" ::"n"(R)); }
template <int R>
__device__ __forceinline__ void reg_dealloc() { asm volatile("setmaxnreg.dec.sync.aligned.u32 %0;" ::"n"(R)); }

__device__ __forceinline__ uint64_t make_desc(uint32_t saddr, uint32_t lbo_bytes, uint32_t sbo_bytes) {
    uint64_t d = 0;
    d |= (uint64_t)((saddr & 0x3FFFF) >> 4);
    d |= (uint64_t)((lbo_bytes >> 4) & 0x3FFF) << 16;
    d |= (uint64_t)((sbo_bytes >> 4) & 0x3FFF) << 32;
    d |= (uint64_t)1 << 62;
    return d;
}

__device__ __forceinline__ float ex2(float x) {
    float y;
    asm volatile("ex2.approx.ftz.f32 %0, %1;" : "=f"(y) : "f"(x));
    return y;
}
__device__ __forceinline__ uint32_t pack_bf16(float lo, float hi) {
    uint32_t r;
    asm("cvt.rn.bf16x2.f32 %0, %1, %2;" : "=r"(r) : "f"(hi), "f"(lo));
    return r;
}
__device__ __forceinline__ uint32_t mul_bf16x2(uint32_t a, uint32_t b) {
    uint32_t r;
    asm("mul.rn.bf16x2 %0, %1, %2;" : "=r"(r) : "r"(a), "r"(b));
    return r;
}
__device__ __forceinline__ uint32_t add_bf16x2(uint32_t a, uint32_t b) {
    uint32_t r;
    asm("add.rn.bf16x2 %0, %1, %2;" : "=r"(r) : "r"(a), "r"(b));
    return r;
}
__device__ __forceinline__ unsigned int ld_acq(const unsigned int* p) {
    unsigned int v;
    asm volatile("ld.acquire.gpu.global.u32 %0, [%1];" : "=r"(v) : "l"(p) : "memory");
    return v;
}
__device__ __forceinline__ unsigned long long ld_acq64(const unsigned long long* p) {
    unsigned long long v;
    asm volatile("ld.acquire.gpu.global.u64 %0, [%1];" : "=l"(v) : "l"(p) : "memory");
    return v;
}
__device__ __forceinline__ uint32_t fma_bf16x2(uint32_t a, uint32_t b, uint32_t c) {
    uint32_t r;
    asm("fma.rn.bf16x2 %0, %1, %2, %3;" : "=r"(r) : "r"(a), "r"(b), "r"(c));
    return r;
}
__device__ __forceinline__ uint32_t max_bf16x2(uint32_t a, uint32_t b) {
    uint32_t r;
    asm("max.bf16x2 %0, %1, %2;" : "=r"(r) : "r"(a), "r"(b));
    return r;
}
__device__ __forceinline__ float bf16lo(uint32_t v) { return __uint_as_float(v << 16); }
__device__ __forceinline__ float bf16hi(uint32_t v) { return __uint_as_float(v & 0xffff0000u); }
__device__ __forceinline__ float bf16_round(float x) { return __bfloat162float(__float2bfloat16_rn(x)); }
__device__ __forceinline__ float silu_f(float x) {
    const float h = 0.5f * x;
    float t;
    asm("tanh.approx.f32 %0, %1;" : "=f"(t) : "f"(h));
    return fmaf(h, t, h);
}

__device__ __forceinline__ void stmatrix_x4(uint32_t addr, uint32_t r0, uint32_t r1, uint32_t r2, uint32_t r3) {
    asm volatile("stmatrix.sync.aligned.m8n8.x4.shared.b16 [%0], {%1, %2, %3, %4};"
                 ::"r"(addr), "r"(r0), "r"(r1), "r"(r2), "r"(r3)
                 : "memory");
}

#define ACC64(d) \
    "+f"(d[0]), "+f"(d[1]), "+f"(d[2]), "+f"(d[3]), "+f"(d[4]), "+f"(d[5]), "+f"(d[6]), "+f"(d[7]), \
    "+f"(d[8]), "+f"(d[9]), "+f"(d[10]), "+f"(d[11]), "+f"(d[12]), "+f"(d[13]), "+f"(d[14]), "+f"(d[15]), \
    "+f"(d[16]), "+f"(d[17]), "+f"(d[18]), "+f"(d[19]), "+f"(d[20]), "+f"(d[21]), "+f"(d[22]), "+f"(d[23]), \
    "+f"(d[24]), "+f"(d[25]), "+f"(d[26]), "+f"(d[27]), "+f"(d[28]), "+f"(d[29]), "+f"(d[30]), "+f"(d[31]), \
    "+f"(d[32]), "+f"(d[33]), "+f"(d[34]), "+f"(d[35]), "+f"(d[36]), "+f"(d[37]), "+f"(d[38]), "+f"(d[39]), \
    "+f"(d[40]), "+f"(d[41]), "+f"(d[42]), "+f"(d[43]), "+f"(d[44]), "+f"(d[45]), "+f"(d[46]), "+f"(d[47]), \
    "+f"(d[48]), "+f"(d[49]), "+f"(d[50]), "+f"(d[51]), "+f"(d[52]), "+f"(d[53]), "+f"(d[54]), "+f"(d[55]), \
    "+f"(d[56]), "+f"(d[57]), "+f"(d[58]), "+f"(d[59]), "+f"(d[60]), "+f"(d[61]), "+f"(d[62]), "+f"(d[63])

#define ACC64_STR \
    "{%0, %1, %2, %3, %4, %5, %6, %7, %8, %9, %10, %11, %12, %13, %14, %15, " \
    "%16, %17, %18, %19, %20, %21, %22, %23, %24, %25, %26, %27, %28, %29, %30, %31, " \
    "%32, %33, %34, %35, %36, %37, %38, %39, %40, %41, %42, %43, %44, %45, %46, %47, " \
    "%48, %49, %50, %51, %52, %53, %54, %55, %56, %57, %58, %59, %60, %61, %62, %63}"

template <int TB>
__device__ __forceinline__ void wgmma_ss_n128(float (&d)[64], uint64_t da, uint64_t db, int scale_d) {
    asm volatile(
        "{\n.reg .pred p;\nsetp.ne.b32 p, %66, 0;\n"
        "wgmma.mma_async.sync.aligned.m64n128k16.f32.bf16.bf16 " ACC64_STR ", %64, %65, p, 1, 1, 0, %67;\n}\n"
        : ACC64(d)
        : "l"(da), "l"(db), "r"(scale_d), "n"(TB));
}
template <int TB>
__device__ __forceinline__ void wgmma_rs_n128(float (&d)[64], uint32_t a0, uint32_t a1, uint32_t a2, uint32_t a3,
                                              uint64_t db, int scale_d) {
    asm volatile(
        "{\n.reg .pred p;\nsetp.ne.b32 p, %69, 0;\n"
        "wgmma.mma_async.sync.aligned.m64n128k16.f32.bf16.bf16 " ACC64_STR ", {%64, %65, %66, %67}, %68, p, 1, 1, %70;\n}\n"
        : ACC64(d)
        : "r"(a0), "r"(a1), "r"(a2), "r"(a3), "l"(db), "r"(scale_d), "n"(TB));
}

constexpr uint32_t DESC_HI = 0x40000040u;
__device__ __forceinline__ uint32_t desc_lo(uint32_t saddr, uint32_t lbo_bytes) {
    return ((saddr & 0x3FFFF) >> 4) | ((lbo_bytes >> 4) << 16);
}
template <int TB>
__device__ __forceinline__ void wgmma_ss_lo(float (&d)[64], uint32_t da, uint32_t db, int scale_d) {
    asm volatile(
        "{\n.reg .pred p;\n.reg .b64 xa, xb;\nsetp.ne.b32 p, %66, 0;\n"
        "mov.b64 xa, {%64, %68};\nmov.b64 xb, {%65, %68};\n"
        "wgmma.mma_async.sync.aligned.m64n128k16.f32.bf16.bf16 " ACC64_STR ", xa, xb, p, 1, 1, 0, %67;\n}\n"
        : ACC64(d)
        : "r"(da), "r"(db), "r"(scale_d), "n"(TB), "r"(DESC_HI));
}
__device__ __forceinline__ void wgmma_rs_lo_tb(float (&d)[64], uint32_t a0, uint32_t a1, uint32_t a2, uint32_t a3, uint32_t db) {
    asm volatile(
        "{\n.reg .b64 xb;\nmov.b64 xb, {%68, %69};\n"
        "wgmma.mma_async.sync.aligned.m64n128k16.f32.bf16.bf16 " ACC64_STR ", {%64, %65, %66, %67}, xb, 1, 1, 1, 1;\n}\n"
        : ACC64(d)
        : "r"(a0), "r"(a1), "r"(a2), "r"(a3), "r"(db), "r"(DESC_HI));
}

#define ACC8(d, o) "+f"(d[o]), "+f"(d[o + 1]), "+f"(d[o + 2]), "+f"(d[o + 3]), "+f"(d[o + 4]), "+f"(d[o + 5]), "+f"(d[o + 6]), "+f"(d[o + 7])
__device__ __forceinline__ void wgmma_rs_n64(float (&d)[64], uint32_t a0, uint32_t a1, uint32_t a2, uint32_t a3, uint32_t db) {
    asm volatile(
        "{\n.reg .b64 xb;\nmov.b64 xb, {%36, %37};\n"
        "wgmma.mma_async.sync.aligned.m64n64k16.f32.bf16.bf16 "
        "{%0, %1, %2, %3, %4, %5, %6, %7, %8, %9, %10, %11, %12, %13, %14, %15, "
        "%16, %17, %18, %19, %20, %21, %22, %23, %24, %25, %26, %27, %28, %29, %30, %31}, "
        "{%32, %33, %34, %35}, xb, 1, 1, 1, 1;\n}\n"
        : ACC8(d, 0), ACC8(d, 8), ACC8(d, 16), ACC8(d, 24)
        : "r"(a0), "r"(a1), "r"(a2), "r"(a3), "r"(db), "r"(DESC_HI));
}
__device__ __forceinline__ void wgmma_rs_n72(float (&d)[64], float (&l)[4], uint32_t a0, uint32_t a1, uint32_t a2, uint32_t a3, uint32_t db) {
    asm volatile(
        "{\n.reg .b64 xb;\nmov.b64 xb, {%40, %41};\n"
        "wgmma.mma_async.sync.aligned.m64n72k16.f32.bf16.bf16 "
        "{%0, %1, %2, %3, %4, %5, %6, %7, %8, %9, %10, %11, %12, %13, %14, %15, "
        "%16, %17, %18, %19, %20, %21, %22, %23, %24, %25, %26, %27, %28, %29, %30, %31, %32, %33, %34, %35}, "
        "{%36, %37, %38, %39}, xb, 1, 1, 1, 1;\n}\n"
        : ACC8(d, 32), ACC8(d, 40), ACC8(d, 48), ACC8(d, 56), "+f"(l[0]), "+f"(l[1]), "+f"(l[2]), "+f"(l[3])
        : "r"(a0), "r"(a1), "r"(a2), "r"(a3), "r"(db), "r"(DESC_HI));
}

__device__ __forceinline__ void wgmma_ss_n256_tb(float (&d)[128], uint64_t da, uint64_t db, int scale_d) {
    asm volatile(
        "{\n.reg .pred p;\nsetp.ne.b32 p, %130, 0;\n"
        "wgmma.mma_async.sync.aligned.m64n256k16.f32.bf16.bf16 "
        "{%0, %1, %2, %3, %4, %5, %6, %7, %8, %9, %10, %11, %12, %13, %14, %15, "
        "%16, %17, %18, %19, %20, %21, %22, %23, %24, %25, %26, %27, %28, %29, %30, %31, "
        "%32, %33, %34, %35, %36, %37, %38, %39, %40, %41, %42, %43, %44, %45, %46, %47, "
        "%48, %49, %50, %51, %52, %53, %54, %55, %56, %57, %58, %59, %60, %61, %62, %63, "
        "%64, %65, %66, %67, %68, %69, %70, %71, %72, %73, %74, %75, %76, %77, %78, %79, "
        "%80, %81, %82, %83, %84, %85, %86, %87, %88, %89, %90, %91, %92, %93, %94, %95, "
        "%96, %97, %98, %99, %100, %101, %102, %103, %104, %105, %106, %107, %108, %109, %110, %111, "
        "%112, %113, %114, %115, %116, %117, %118, %119, %120, %121, %122, %123, %124, %125, %126, %127}, "
        "%128, %129, p, 1, 1, 0, 1;\n}\n"
        : ACC8(d, 0), ACC8(d, 8), ACC8(d, 16), ACC8(d, 24), ACC8(d, 32), ACC8(d, 40), ACC8(d, 48), ACC8(d, 56),
          ACC8(d, 64), ACC8(d, 72), ACC8(d, 80), ACC8(d, 88), ACC8(d, 96), ACC8(d, 104), ACC8(d, 112), ACC8(d, 120)
        : "l"(da), "l"(db), "r"(scale_d));
}

__global__ void __launch_bounds__(256) ln_kernel(const bf16* __restrict__ x) {
    pdl_launch();
    int warp = threadIdx.x >> 5, lane = threadIdx.x & 31;
    int row = blockIdx.x * 8 + warp;
    if (blockIdx.x == 0) g_cnt[threadIdx.x] = 0;
    if (blockIdx.x == 1 && threadIdx.x < 16) g_mask[threadIdx.x] = 0;
    const uint4* src = reinterpret_cast<const uint4*>(x + (size_t)row * DM);
    uint4 v[2];
    v[0] = src[lane];
    v[1] = src[lane + 32];
    float f[16];
#pragma unroll
    for (int i = 0; i < 2; i++) {
        const __nv_bfloat162* p = reinterpret_cast<const __nv_bfloat162*>(&v[i]);
#pragma unroll
        for (int j = 0; j < 4; j++) {
            float2 t = __bfloat1622float2(p[j]);
            f[i * 8 + j * 2] = t.x;
            f[i * 8 + j * 2 + 1] = t.y;
        }
    }
    float s = 0.f;
#pragma unroll
    for (int i = 0; i < 16; i++) s += f[i];
#pragma unroll
    for (int o = 16; o > 0; o >>= 1) s += __shfl_xor_sync(0xffffffffu, s, o);
    float mean = s * (1.0f / DM);
    float q = 0.f;
#pragma unroll
    for (int i = 0; i < 16; i++) {
        float d = f[i] - mean;
        q += d * d;
    }
#pragma unroll
    for (int o = 16; o > 0; o >>= 1) q += __shfl_xor_sync(0xffffffffu, q, o);
    float var_b = bf16_round(q * (1.0f / DM));
    float mean_b = bf16_round(mean);
    float den = bf16_round(sqrtf(bf16_round(var_b + 1e-5f)));
    uint4 o[2];
#pragma unroll
    for (int i = 0; i < 2; i++) {
        uint32_t* p = reinterpret_cast<uint32_t*>(&o[i]);
#pragma unroll
        for (int j = 0; j < 4; j++) {
            float a = bf16_round(f[i * 8 + j * 2] - mean_b) / den;
            float b = bf16_round(f[i * 8 + j * 2 + 1] - mean_b) / den;
            p[j] = pack_bf16(a, b);
        }
    }
    uint4* dst = reinterpret_cast<uint4*>(g_xn + (size_t)row * DM);
    dst[lane] = o[0];
    dst[lane + 32] = o[1];
}

constexpr int AT_STAGES = 3;
constexpr int TILE_BYTES = 128 * 128 * 2;
struct __align__(1024) AttnSmem {
    uint8_t k[AT_STAGES][TILE_BYTES];
    uint8_t v[AT_STAGES][TILE_BYTES];
    uint8_t o[TILE_BYTES];
    uint32_t ones0[4];
    uint64_t full_k[AT_STAGES], full_v[AT_STAGES], empty_k[AT_STAGES], empty_v[AT_STAGES];
    uint64_t st_free[2];
    uint64_t redo_bar;
    uint32_t redo;
    uint32_t pad0;
    uint32_t ones1[4];
    uint64_t fin_bar[4];
    uint32_t pad1[24];
    uint32_t ones2[(2048 - 288) / 4];
};

#define EXPO(x) x
#define N8(x) x
#define PPK 8
#define FAST_BIAS (-40.0f)
constexpr int NUM_CTAS = 132;
constexpr int MAX_ITEMS = 12;
enum { T_ATT = 0, T_F1 = 1, T_F2 = 2, T_OPE = 3, T_OPF = 4 };
struct Sched {
    uint16_t item[NUM_CTAS][MAX_ITEMS];
    uint8_t count[NUM_CTAS], end_att[NUM_CTAS], end_wide[NUM_CTAS];
};

__global__ void __launch_bounds__(384, 1)
attn_kernel(const __grid_constant__ CUtensorMap tm_xn, const __grid_constant__ CUtensorMap tm_wq,
            const __grid_constant__ CUtensorMap tm_k, const __grid_constant__ CUtensorMap tm_v,
            const __grid_constant__ CUtensorMap tm_o, const __grid_constant__ CUtensorMap tm_w1,
            const __grid_constant__ CUtensorMap tm_hst, const __grid_constant__ CUtensorMap tm_hld,
            const __grid_constant__ CUtensorMap tm_w2, const __grid_constant__ CUtensorMap tm_gst,
            const __grid_constant__ CUtensorMap tm_old, const __grid_constant__ CUtensorMap tm_wo,
            const __grid_constant__ CUtensorMap tm_oldw, const __grid_constant__ CUtensorMap tm_wow,
            const bf16* __restrict__ x, bf16* __restrict__ out, const __grid_constant__ Sched sched) {
    extern __shared__ uint8_t smem_raw[];
    AttnSmem& sm = *reinterpret_cast<AttnSmem*>((reinterpret_cast<uintptr_t>(smem_raw) + 1023) & ~uintptr_t(1023));
    const int tid = threadIdx.x;
    const int wg = __shfl_sync(0xffffffffu, tid >> 7, 0);
    const int n_items = sched.count[blockIdx.x];
    if (tid == 32) {
        prefetch_tmap(&tm_xn); prefetch_tmap(&tm_wq); prefetch_tmap(&tm_k); prefetch_tmap(&tm_v); prefetch_tmap(&tm_o);
        prefetch_tmap(&tm_w1); prefetch_tmap(&tm_hst); prefetch_tmap(&tm_hld); prefetch_tmap(&tm_w2); prefetch_tmap(&tm_gst);
        prefetch_tmap(&tm_old); prefetch_tmap(&tm_wo); prefetch_tmap(&tm_oldw); prefetch_tmap(&tm_wow);
    }

    if (tid == 0) {
#pragma unroll
        for (int s = 0; s < AT_STAGES; s++) {
            mbar_init(smem_u32(&sm.full_k[s]), 1);
            mbar_init(smem_u32(&sm.full_v[s]), 1);
            mbar_init(smem_u32(&sm.empty_k[s]), 8);
            mbar_init(smem_u32(&sm.empty_v[s]), 8);
        }
        mbar_init(smem_u32(&sm.st_free[0]), 1);
        mbar_init(smem_u32(&sm.st_free[1]), 1);
        mbar_init(smem_u32(&sm.redo_bar), 8);
#pragma unroll
        for (int s = 0; s < 4; s++) mbar_init(smem_u32(&sm.fin_bar[s]), 1);
        sm.redo = 0;
        asm volatile("fence.mbarrier_init.release.cluster;" ::: "memory");
    }
    if (tid < 64) {
        const int r = tid >> 2;
        sm.ones0[(r >> 3) * 256 + (r & 7) * 36 + (tid & 3)] = 0x3F803F80u;
        fence_proxy_async();
    }
    __syncthreads();
    pdl_wait();
    int it = 0;
    uint32_t rmask = 0;
    bool redo = false;
    auto next_item = [&]() -> bool {
        if (!redo) {
            if (++it < n_items) return true;
            mbar_wait(smem_u32(&sm.redo_bar), 0);
            rmask = *reinterpret_cast<volatile uint32_t*>(&sm.redo);
            rmask = (rmask | (rmask >> 16)) & 0xffffu;
            redo = true;
        }
        if (!rmask) return false;
        it = __ffs(rmask) - 1;
        rmask &= rmask - 1;
        return true;
    };
    constexpr int BAR_SCHED0 = 1, BAR_EPI0 = 3, BAR_ST0 = 5;

    if (wg == 0) {
        reg_dealloc<40>();
        if (tid >= 32 && tid < 96) {
            const int cw = (tid >> 5) - 1;
            const uint32_t obase = smem_u32(sm.o) + cw * 16384;
            do {
                const int item = sched.item[blockIdx.x][it];
                const int type = item >> 12, a = (item >> 4) & 0xff, b = item & 15;
                if (type == T_OPF) continue;
                if (type == T_F2) {
                    named_sync(BAR_ST0 + cw, 160);
                    if ((tid & 31) == 0) {
                        tma_store_3d(&tm_gst, obase, 0, b * 128 + cw * 64, a * 4);
                        tma_commit();
                        tma_wait_read0();
                        mbar_arrive(smem_u32(&sm.st_free[cw]));
                    }
                    __syncwarp();
                }
                named_sync(BAR_ST0 + cw, 160);
                if ((tid & 31) == 0) {
                    if (type == T_OPE) {
                        __threadfence();
                        atomicAdd(&g_cnt[C_P + b * 2 + (a & 1)], 1u);
                    } else {
                        if (redo) tma_wait_all0();
                        tma_store_3d(type == T_ATT ? &tm_o : (type == T_F1 ? &tm_hst : &tm_gst), obase, 0, b * 128 + cw * 64,
                                     type == T_F2 ? a * 4 + 2 : a * 2);
                        tma_commit();
                        tma_wait_read0();
                        mbar_arrive(smem_u32(&sm.st_free[cw]));
                        const bool bad = (*reinterpret_cast<volatile uint32_t*>(&sm.redo) >> (16 * cw + it)) & 1;
                        if (bad && !redo) atomicAdd(&g_cnt[C_BAD + b], 1u);
                        tma_wait_all0();
                        asm volatile("fence.proxy.async;" ::: "memory");
                        __threadfence();
                        if (type != T_ATT) atomicAdd(&g_cnt[type == T_F1 ? C_H + b : C_G + b * 2 + a], 1u);
                        else if (!redo) atomicOr(&g_mask[b], 1ull << (2 * a + cw));
                        else if (bad) atomicAdd(&g_cnt[C_RED + b], 1u);
                    }
                }
                __syncwarp();
            } while (next_item());
            if ((tid & 31) == 0) tma_wait_all0();
        }
        if (tid == 96) {
            int ord = 0;
            for (int i = 0; i < n_items; i++) {
                const int item = sched.item[blockIdx.x][i];
                const int a = (item >> 4) & 0xff, b = item & 15;
                if ((item >> 12) != T_OPF) continue;
                unsigned int spins = 0;
                while (ld_acq64(&g_mask[b]) != ~0ull && ++spins < (1u << 24)) {}
                while (ld_acq(&g_cnt[C_P + b * 2 + (a >> 1)]) < 2 * OPE_N && ++spins < (1u << 24)) {}
                while (ld_acq(&g_cnt[C_G + b * 2 + (a >> 1)]) < 2 && ++spins < (1u << 24)) {}
                if (ld_acq(&g_cnt[C_BAD + b])) atomicOr(&sm.redo, 1u << i);
                mbar_arrive(smem_u32(&sm.fin_bar[ord++]));
            }
        }
        if (tid == 0) {
            int stage = 0;
            uint32_t phase = 0;
            do {
                const int item = sched.item[blockIdx.x][it];
                const int type = item >> 12, a = (item >> 4) & 0xff, b = item & 15;
                const CUtensorMap* ta = type < T_F2 ? &tm_xn : (type == T_F2 ? &tm_hld : (type == T_OPE ? &tm_oldw : &tm_old));
                const CUtensorMap* tb = type < T_F2 ? (type == T_ATT ? &tm_wq : &tm_w1) : (type == T_F2 ? &tm_w2 : (type == T_OPE ? &tm_wow : &tm_wo));
                const bool wide = type == T_F2 || type == T_OPE;
                int nch = DM / 128, kc0 = 0, nb = a;
                unsigned long long need = 0, mask = 0;
                unsigned int spins = 0;
                if (type == T_F2) {
                    nch = FF / 128;
                    nb = a * 2;
                    while (ld_acq(&g_cnt[C_H + b]) < 2 * (FF / 128) && ++spins < (1u << 24)) {}
                    asm volatile("fence.proxy.async;" ::: "memory");
                } else if (type == T_OPE) {
                    nch = OPE_H;
                    kc0 = (a >> 2) * OPE_H;
                    nb = (a & 1) * 2;
                    need = 3ull << (2 * kc0);
                } else if (type == T_OPF) {
                    if (!redo) {
                        nch = OPF_H;
                        kc0 = NH - OPF_H;
                        need = 3ull << (2 * kc0);
                    } else {
                        nch = NH;
                        const unsigned int nbad = ld_acq(&g_cnt[C_BAD + b]);
                        while (ld_acq(&g_cnt[C_RED + b]) < nbad && ++spins < (1u << 24)) {}
                        asm volatile("fence.proxy.async;" ::: "memory");
                    }
                }
                for (int kc = kc0; kc < kc0 + nch; kc++) {
                    if ((mask & need) != need) {
                        do mask = ld_acq64(&g_mask[b]); while ((mask & need) != need && ++spins < (1u << 24));
                        asm volatile("fence.proxy.async;" ::: "memory");
                    }
                    need <<= 2;
                    for (int hk = 0; hk <= (int)wide; hk++) {
                        mbar_wait(smem_u32(&sm.empty_k[stage]), phase ^ 1);
                        mbar_expect_tx(smem_u32(&sm.full_k[stage]), wide ? TILE_BYTES / 2 : TILE_BYTES);
                        tma_load_3d(smem_u32(sm.k[stage]), ta, smem_u32(&sm.full_k[stage]), 0, b * 128, kc * 2 + hk);
                        mbar_wait(smem_u32(&sm.empty_v[stage]), phase ^ 1);
                        mbar_expect_tx(smem_u32(&sm.full_v[stage]), TILE_BYTES);
                        tma_load_3d(smem_u32(sm.v[stage]), tb, smem_u32(&sm.full_v[stage]), 0, kc * 128 + hk * 64, nb * 2);
                        if (++stage == AT_STAGES) { stage = 0; phase ^= 1; }
                    }
                }
                if (type == T_ATT) {
                    for (int j = 0; j < 16; j++) {
                        mbar_wait(smem_u32(&sm.empty_k[stage]), phase ^ 1);
                        mbar_expect_tx(smem_u32(&sm.full_k[stage]), TILE_BYTES);
                        tma_load_3d(smem_u32(sm.k[stage]), &tm_k, smem_u32(&sm.full_k[stage]), 0, a * SEQ + j * 128, 0);
                        mbar_wait(smem_u32(&sm.empty_v[stage]), phase ^ 1);
                        mbar_expect_tx(smem_u32(&sm.full_v[stage]), TILE_BYTES);
                        tma_load_3d(smem_u32(sm.v[stage]), &tm_v, smem_u32(&sm.full_v[stage]), 0, a * SEQ + j * 128, 0);
                        if (++stage == AT_STAGES) { stage = 0; phase ^= 1; }
                    }
                }
            } while (next_item());
        }
    } else {
        reg_alloc<232>();
        const int cw = wg - 1;
        const int lane = tid & 31;
        const int warp_in_wg = (tid >> 5) & 3;
        const float c = 1.4426950408889634f;
        const uint32_t SCALE_HI2 = 0x3DB53DB5u, SCALE_LO2 = 0x371E371Eu;
        const uint32_t obase = smem_u32(sm.o) + cw * 16384;
        const int st_row = warp_in_wg * 16 + ((lane >> 3) & 1) * 8 + (lane & 7);

        const uint32_t dq = __shfl_sync(0xffffffffu, desc_lo(obase, 16), 0);
        const uint32_t dk0 = __shfl_sync(0xffffffffu, desc_lo(smem_u32(sm.k[0]), 16), 0);
        const uint32_t dv0 = dk0 - (1u << 16) + (1024u << 16) + AT_STAGES * (TILE_BYTES >> 4);

        PP(if (cw == 1) named_arrive(BAR_SCHED0 + 0, 256));

        int stage = 0;
        uint32_t phase = 0;
        float S[64];
        uint32_t P[32], P2[32];
        uint32_t cnt = 0;
        const uint32_t dw0 = __shfl_sync(0xffffffffu, desc_lo(smem_u32(sm.v[0]) + 16384, smem_u32(sm.ones0) - smem_u32(sm.v[0]) - 16384), 0);
        constexpr uint32_t DW_K = 128u - (128u << 16), DW_ST = 2048u - (2048u << 16);

        const uint32_t fk0 = smem_u32(&sm.full_k[0]), fv0 = smem_u32(&sm.full_v[0]);
        const uint32_t ek0 = smem_u32(&sm.empty_k[0]), ev0 = smem_u32(&sm.empty_v[0]);
        int vstage = 0;
        uint32_t vphase = 0;
        bool okk = false, okv = false;

        auto gemm_chunk = [&](float (&S)[64], bool acc, bool real) {
            if (real) {
                mbar_wait(fk0 + stage * 8, phase);
                mbar_wait(fv0 + stage * 8, phase);
            }
            const uint64_t da = make_desc(smem_u32(sm.k[stage]) + cw * 64 * 128, 16, 1024);
            const uint64_t db = make_desc(smem_u32(sm.v[stage]), 16384, 1024);
            wgmma_fence();
#pragma unroll
            for (int kk = 0; kk < 8; kk++) {
                wgmma_ss_n128<1>(S, da + (uint64_t)(((kk >> 2) * 16384 + (kk & 3) * 32) >> 4),
                                 db + (uint64_t)((kk * 2048) >> 4), acc || kk != 0);
            }
            wgmma_commit();
        };
        auto gemm_rest = [&](float (&S)[64], int nch) {
            int prev = stage;
            if (++stage == AT_STAGES) { stage = 0; phase ^= 1; }
#pragma unroll 1
            for (int kc = 1; kc < nch; kc++) {
                gemm_chunk(S, true, true);
                wgmma_wait<1>();
                if (lane == 0) {
                    mbar_arrive(ek0 + prev * 8);
                    mbar_arrive(ev0 + prev * 8);
                }
                prev = stage;
                if (++stage == AT_STAGES) { stage = 0; phase ^= 1; }
            }
            wgmma_wait<0>();
            if (lane == 0) {
                mbar_arrive(ek0 + prev * 8);
                mbar_arrive(ev0 + prev * 8);
            }
        };
        auto pack_p = [&](float (&S)[64]) {
#pragma unroll
            for (int i = 0; i < 32; i++) P[i] = pack_bf16(S[2 * i], S[2 * i + 1]);
        };
        auto final_epi = [&](float (&T)[64], int mb, int nb) {
            mbar_wait(smem_u32(&sm.st_free[cw]), (cnt & 1) ^ 1);
#pragma unroll
            for (int i = 0; i < 16; i += 2) {
                const int cc = i + (lane >> 4);
                const uint32_t addr = obase + (cc >> 3) * 8192 + st_row * 128 + (((cc & 7) ^ (st_row & 7)) << 4);
                stmatrix_x4(addr, pack_bf16(T[4 * i], T[4 * i + 1]), pack_bf16(T[4 * i + 2], T[4 * i + 3]),
                            pack_bf16(T[4 * i + 4], T[4 * i + 5]), pack_bf16(T[4 * i + 6], T[4 * i + 7]));
            }
            const int t = tid & 127, ch = t & 15, row0 = t >> 4;
            const size_t off = (size_t)(mb * 128 + cw * 64 + row0) * DM + nb * 128 + ch * 8;
            uint4 xv[8], gv[8];
#pragma unroll
            for (int i = 0; i < 8; i++) {
                xv[i] = *reinterpret_cast<const uint4*>(x + off + (size_t)i * 8 * DM);
                gv[i] = __ldcg(reinterpret_cast<const uint4*>(g_g + off + (size_t)i * 8 * DM));
            }
            named_sync(BAR_EPI0 + cw, 128);
            const uint32_t sa = obase + (ch >> 3) * 8192 + row0 * 128 + (((ch & 7) ^ row0) << 4);
#pragma unroll
            for (int i = 0; i < 8; i++) {
                uint4 sv;
                asm volatile("ld.shared.v4.u32 {%0, %1, %2, %3}, [%4];" : "=r"(sv.x), "=r"(sv.y), "=r"(sv.z), "=r"(sv.w) : "r"(sa + i * 1024));
                sv.x = add_bf16x2(xv[i].x, mul_bf16x2(sv.x, gv[i].x));
                sv.y = add_bf16x2(xv[i].y, mul_bf16x2(sv.y, gv[i].y));
                sv.z = add_bf16x2(xv[i].z, mul_bf16x2(sv.z, gv[i].z));
                sv.w = add_bf16x2(xv[i].w, mul_bf16x2(sv.w, gv[i].w));
                *reinterpret_cast<uint4*>(out + off + (size_t)i * 8 * DM) = sv;
            }
            named_sync(BAR_EPI0 + cw, 128);
        };
        auto stage_p = [&](uint32_t (&P)[32]) {
            mbar_wait(smem_u32(&sm.st_free[cw]), (cnt & 1) ^ 1);
            cnt++;
#pragma unroll
            for (int i = 0; i < 16; i += 2) {
                const int cc = i + (lane >> 4);
                const uint32_t addr = obase + (cc >> 3) * 8192 + st_row * 128 + (((cc & 7) ^ (st_row & 7)) << 4);
                stmatrix_x4(addr, P[2 * i], P[2 * i + 1], P[2 * i + 2], P[2 * i + 3]);
            }
            fence_proxy_async();
        };
        auto issue_qk = [&](uint32_t dk) {
            wgmma_fence();
#pragma unroll
            for (int kk = 0; kk < 8; kk++)
                wgmma_ss_lo<0>(S, dq + (((kk >> 2) * 8192 + (kk & 3) * 32) >> 4),
                               dk + (((kk >> 2) * 16384 + (kk & 3) * 32) >> 4), kk != 0);
            wgmma_commit();
        };
        auto issue_pv = [&](float (&O)[64], float (&L)[4], uint32_t (&Pc)[32], int vs) {
            const uint32_t dv = dv0 + vs * (TILE_BYTES >> 4), dw = dw0 + vs * DW_ST;
            wgmma_fence();
#pragma unroll
            for (int kk = 0; kk < 8; kk++) {
                wgmma_rs_n64(O, Pc[4 * kk], Pc[4 * kk + 1], Pc[4 * kk + 2], Pc[4 * kk + 3], dv + ((kk * 2048) >> 4));
                wgmma_rs_n72(O, L, Pc[4 * kk], Pc[4 * kk + 1], Pc[4 * kk + 2], Pc[4 * kk + 3], dw + kk * DW_K);
            }
            wgmma_commit();
        };
        auto epilogue = [&](float (&O)[64], float (&L)[4]) {
            const float i0 = 1.0f / L[0], i1 = 1.0f / L[2];
            named_sync(BAR_EPI0 + cw, 128);
#pragma unroll
            for (int i = 0; i < 16; i += 2) {
                const int cc = i + (lane >> 4);
                const uint32_t addr = obase + (cc >> 3) * 8192 + st_row * 128 + (((cc & 7) ^ (st_row & 7)) << 4);
                stmatrix_x4(addr, pack_bf16(O[4 * i] * i0, O[4 * i + 1] * i0), pack_bf16(O[4 * i + 2] * i1, O[4 * i + 3] * i1),
                            pack_bf16(O[4 * i + 4] * i0, O[4 * i + 5] * i0), pack_bf16(O[4 * i + 6] * i1, O[4 * i + 7] * i1));
            }
            fence_proxy_async();
            named_arrive(BAR_ST0 + cw, 160);
        };
        auto scores_max = [&](uint32_t (&T)[32], float& x0, float& x1) {
#pragma unroll
            for (int i = 0; i < 32; i++) {
                const uint32_t sb = pack_bf16(S[2 * i], S[2 * i + 1]);
                T[i] = fma_bf16x2(sb, SCALE_HI2, mul_bf16x2(sb, SCALE_LO2));
            }
            uint32_t y0 = max_bf16x2(T[0], T[2]), y1 = max_bf16x2(T[1], T[3]);
#pragma unroll
            for (int i = 2; i < 16; i++) {
                y0 = max_bf16x2(y0, T[2 * i]);
                y1 = max_bf16x2(y1, T[2 * i + 1]);
            }
            x0 = fmaxf(bf16lo(y0), bf16hi(y0));
            x1 = fmaxf(bf16lo(y1), bf16hi(y1));
            x0 = fmaxf(x0, __shfl_xor_sync(0xffffffffu, x0, 1));
            x1 = fmaxf(x1, __shfl_xor_sync(0xffffffffu, x1, 1));
            x0 = fmaxf(x0, __shfl_xor_sync(0xffffffffu, x0, 2));
            x1 = fmaxf(x1, __shfl_xor_sync(0xffffffffu, x1, 2));
        };
        auto first_block = [&]() {
            stage_p(P);
            named_sync(BAR_EPI0 + cw, 128);
            vstage = stage;
            vphase = phase;
            mbar_wait(fk0 + stage * 8, phase);
            PP(named_sync(BAR_SCHED0 + cw, 256));
            issue_qk(dk0 + stage * (TILE_BYTES >> 4));
            PP(named_arrive(BAR_SCHED0 + (cw ^ 1), 256));
            if (++stage == AT_STAGES) { stage = 0; phase ^= 1; }
            okk = mbar_try_wait(fk0 + stage * 8, phase);
            okv = mbar_try_wait(fv0 + vstage * 8, vphase);
            wgmma_wait<0>();
            if (lane == 0) mbar_arrive(ek0 + vstage * 8);
        };

        int nfin = 0;
        gemm_chunk(S, false, true);
#pragma unroll 1
        for (; it < sched.end_att[blockIdx.x]; it++) {
            const int item = sched.item[blockIdx.x][it];
            const int type = item >> 12;
            const bool has_next = it + 1 < sched.end_att[blockIdx.x];
            gemm_rest(S, DM / 128);
            if (type == T_F1) {
                pack_p(S);
                gemm_chunk(S, false, has_next);
#pragma unroll
                for (int i = 0; i < 32; i++) P[i] = pack_bf16(silu_f(bf16lo(P[i])), silu_f(bf16hi(P[i])));
                stage_p(P);
                named_arrive(BAR_ST0 + cw, 160);
            } else {
                pack_p(S);
                first_block();
                float O[64], L[4] = {0.f, 0.f, 0.f, 0.f};
#pragma unroll
                for (int i = 0; i < 64; i++) O[i] = 0.f;
                float n0, n1;
                {
                    float x0, x1;
                    scores_max(P2, x0, x1);
                    n0 = fmaf(-x0, c, FAST_BIAS);
                    n1 = fmaf(-x1, c, FAST_BIAS);
#pragma unroll
                    for (int i = 0; i < 16; i++) {
                        const float e0 = ex2(fmaf(bf16lo(P2[2 * i]), c, n0));
                        const float e1 = ex2(fmaf(bf16hi(P2[2 * i]), c, n0));
                        const float e2 = ex2(fmaf(bf16lo(P2[2 * i + 1]), c, n1));
                        const float e3 = ex2(fmaf(bf16hi(P2[2 * i + 1]), c, n1));
                        P[2 * i] = pack_bf16(e0, e1);
                        P[2 * i + 1] = pack_bf16(e2, e3);
                    }
                }
                auto expo = [&](uint32_t (&Pn)[32], int i_lo, int i_hi) {
#pragma unroll
                    for (int i = i_lo; i < i_hi; i++) {
                        const uint32_t sa = pack_bf16(S[4 * i], S[4 * i + 1]), sb = pack_bf16(S[4 * i + 2], S[4 * i + 3]);
                        const uint32_t ta = fma_bf16x2(sa, SCALE_HI2, mul_bf16x2(sa, SCALE_LO2));
                        const uint32_t tb = fma_bf16x2(sb, SCALE_HI2, mul_bf16x2(sb, SCALE_LO2));
                        const float e0 = ex2(fmaf(bf16lo(ta), c, n0));
                        const float e1 = ex2(fmaf(bf16hi(ta), c, n0));
                        const float e2 = ex2(fmaf(bf16lo(tb), c, n1));
                        float e3 = ex2(fmaf(bf16hi(tb), c, n1));
                        if (i == i_hi - 1 && i_hi < 16) while (e3 < 0.f) e3 = g_dummy;
                        Pn[2 * i] = pack_bf16(e0, e1);
                        Pn[2 * i + 1] = pack_bf16(e2, e3);
                    }
                };
                auto step = [&](uint32_t (&Pc)[32], uint32_t (&Pn)[32]) {
                    const int ust = __shfl_sync(0xffffffffu, stage, 0), uvs = __shfl_sync(0xffffffffu, vstage, 0);
                    if (!okk) mbar_wait(fk0 + stage * 8, phase);
                    if (!okv) mbar_wait(fv0 + vstage * 8, vphase);
                    PP(named_sync(BAR_SCHED0 + cw, 256));
                    issue_qk(dk0 + ust * (TILE_BYTES >> 4));
                    issue_pv(O, L, Pc, uvs);
                    PP(named_arrive(BAR_SCHED0 + (cw ^ 1), 256));
                    const int pv = vstage;
                    vstage = stage;
                    vphase = phase;
                    if (++stage == AT_STAGES) { stage = 0; phase ^= 1; }
                    okk = mbar_try_wait(fk0 + stage * 8, phase);
                    okv = mbar_try_wait(fv0 + vstage * 8, vphase);
                    wgmma_wait<1>();
                    if (lane == 0) mbar_arrive(ek0 + vstage * 8);
                    EXPO(expo(Pn, 0, 8));
                    wgmma_wait<0>();
                    if (lane == 0) mbar_arrive(ev0 + pv * 8);
                    EXPO(expo(Pn, 8, 16));
                };
#pragma unroll 1
                for (int j = 0; j < 7; j++) {
                    step(P, P2);
                    step(P2, P);
                }
                step(P, P2);
                if (!okv) mbar_wait(fv0 + vstage * 8, vphase);
                issue_pv(O, L, P2, vstage);
                gemm_chunk(S, false, has_next);
                wgmma_wait<1>();
                if (lane == 0) mbar_arrive(ev0 + vstage * 8);
                float z = fmaf(L[0], 0.f, L[2] * 0.f);
#pragma unroll
                for (int i = 0; i < 64; i++) z = fmaf(O[i], 0.f, z);
                if (__any_sync(0xffffffffu, z != 0.f) && lane == 0) atomicOr(&sm.redo, 1u << (16 * cw + it));
                epilogue(O, L);
            }
        }
        wgmma_wait<0>();
#pragma unroll 1
        for (; it < sched.end_wide[blockIdx.x]; it++) {
            const int item = sched.item[blockIdx.x][it];
            const int type = item >> 12, a = (item >> 4) & 0xff, b = item & 15;
            const int nk = type == T_F2 ? FF / 64 : 2 * OPE_H;
            float acc[128];
            int prev = -1;
#pragma unroll 1
            for (int kt = 0; kt < nk; kt++) {
                mbar_wait(fk0 + stage * 8, phase);
                mbar_wait(fv0 + stage * 8, phase);
                const uint64_t da = make_desc(smem_u32(sm.k[stage]) + cw * 64 * 128, 16, 1024);
                const uint64_t db = make_desc(smem_u32(sm.v[stage]), 8192, 1024);
                wgmma_fence();
#pragma unroll
                for (int kk = 0; kk < 4; kk++)
                    wgmma_ss_n256_tb(acc, da + (uint64_t)((kk * 32) >> 4), db + (uint64_t)((kk * 2048) >> 4), (kt | kk) != 0);
                wgmma_commit();
                wgmma_wait<1>();
                if (prev >= 0 && lane == 0) {
                    mbar_arrive(ek0 + prev * 8);
                    mbar_arrive(ev0 + prev * 8);
                }
                prev = stage;
                if (++stage == AT_STAGES) { stage = 0; phase ^= 1; }
            }
            wgmma_wait<0>();
            if (lane == 0) {
                mbar_arrive(ek0 + prev * 8);
                mbar_arrive(ev0 + prev * 8);
            }
            if (type == T_F2) {
#pragma unroll
                for (int h = 0; h < 2; h++) {
#pragma unroll
                    for (int i = 0; i < 32; i++)
                        P[i] = pack_bf16(silu_f(bf16_round(acc[64 * h + 2 * i])), silu_f(bf16_round(acc[64 * h + 2 * i + 1])));
                    stage_p(P);
                    named_arrive(BAR_ST0 + cw, 160);
                }
            } else {
                float4* part = g_part + (size_t)(((a >> 2) * 16 + b) * 4 + (a & 1) * 2) * (16 * 256) + (tid - 128);
#pragma unroll
                for (int j = 0; j < 32; j++) __stcg(part + j * 256, make_float4(acc[4 * j], acc[4 * j + 1], acc[4 * j + 2], acc[4 * j + 3]));
                named_arrive(BAR_ST0 + cw, 160);
            }
        }
        float S3[64];
        gemm_chunk(S3, false, it < n_items);
#pragma unroll 1
        for (; it < n_items; it++) {
            const int item = sched.item[blockIdx.x][it];
            const int a = (item >> 4) & 0xff, b = item & 15;
            gemm_rest(S3, OPF_H);
            float T[64];
#pragma unroll
            for (int i = 0; i < 64; i++) T[i] = S3[i] + 0.f;
            fence_acc(T);
            gemm_chunk(S3, false, it + 1 < n_items);
            const float4* part = g_part + (size_t)(b * 4 + a) * (16 * 256) + (tid - 128);
            mbar_wait(smem_u32(&sm.fin_bar[nfin++]), 0);
            if (!((*reinterpret_cast<volatile uint32_t*>(&sm.redo) >> it) & 1)) {
#pragma unroll
                for (int g = 0; g < OPE_N; g++) {
#pragma unroll
                    for (int j = 0; j < 16; j++) {
                        const float4 v = __ldcg(part + (size_t)g * (64 * 16 * 256) + j * 256);
                        T[4 * j] += v.x;
                        T[4 * j + 1] += v.y;
                        T[4 * j + 2] += v.z;
                        T[4 * j + 3] += v.w;
                    }
                }
                final_epi(T, b, a);
            }
        }
        wgmma_wait<0>();
        __syncwarp();
        if (lane == 0) mbar_arrive(smem_u32(&sm.redo_bar));
        mbar_wait(smem_u32(&sm.redo_bar), 0);
        rmask = *reinterpret_cast<volatile uint32_t*>(&sm.redo);
        rmask = (rmask | (rmask >> 16)) & 0xffffu;
#pragma unroll 1
        for (; rmask && (sched.item[blockIdx.x][__ffs(rmask) - 1] >> 12) == T_ATT; rmask &= rmask - 1) {
            gemm_chunk(S, false, true);
            gemm_rest(S, DM / 128);
            pack_p(S);
            first_block();
            float O[64], L[4] = {0.f, 0.f, 0.f, 0.f};
#pragma unroll
            for (int i = 0; i < 64; i++) O[i] = 0.f;
            float m0 = -INFINITY, m1 = -INFINITY;
#pragma unroll 1
            for (int j = 0; j < 16; j++) {
                float x0, x1;
                scores_max(P2, x0, x1);
                x0 = fmaxf(x0, m0);
                x1 = fmaxf(x1, m1);
                const float a0 = ex2((m0 - x0) * c), a1 = ex2((m1 - x1) * c);
                m0 = x0;
                m1 = x1;
                const float n0 = -m0 * c, n1 = -m1 * c;
#pragma unroll
                for (int i = 0; i < 16; i++) {
                    const float e0 = ex2(fmaf(bf16lo(P2[2 * i]), c, n0));
                    const float e1 = ex2(fmaf(bf16hi(P2[2 * i]), c, n0));
                    const float e2 = ex2(fmaf(bf16lo(P2[2 * i + 1]), c, n1));
                    const float e3 = ex2(fmaf(bf16hi(P2[2 * i + 1]), c, n1));
                    P[2 * i] = pack_bf16(e0, e1);
                    P[2 * i + 1] = pack_bf16(e2, e3);
                    O[4 * i] *= a0;
                    O[4 * i + 1] *= a0;
                    O[4 * i + 2] *= a1;
                    O[4 * i + 3] *= a1;
                }
                L[0] *= a0;
                L[1] *= a0;
                L[2] *= a1;
                L[3] *= a1;
                mbar_wait(fv0 + vstage * 8, vphase);
                issue_pv(O, L, P, vstage);
                wgmma_wait<0>();
                if (lane == 0) mbar_arrive(ev0 + vstage * 8);
                if (j < 15) {
                    mbar_wait(fk0 + stage * 8, phase);
                    issue_qk(dk0 + stage * (TILE_BYTES >> 4));
                    wgmma_wait<0>();
                    if (lane == 0) mbar_arrive(ek0 + stage * 8);
                    vstage = stage;
                    vphase = phase;
                    if (++stage == AT_STAGES) { stage = 0; phase ^= 1; }
                }
            }
            epilogue(O, L);
        }
#pragma unroll 1
        for (; rmask; rmask &= rmask - 1) {
            const int item = sched.item[blockIdx.x][__ffs(rmask) - 1];
            gemm_chunk(S, false, true);
            gemm_rest(S, NH);
            final_epi(S, item & 15, (item >> 4) & 0xff);
        }
    }
}

typedef CUresult (*EncodeFn)(CUtensorMap*, CUtensorMapDataType, cuuint32_t, void*, const cuuint64_t*, const cuuint64_t*,
                             const cuuint32_t*, const cuuint32_t*, CUtensorMapInterleave, CUtensorMapSwizzle,
                             CUtensorMapL2promotion, CUtensorMapFloatOOBfill);

static CUtensorMap make_map(EncodeFn fn, const void* ptr, uint64_t rows, uint64_t cols, uint32_t box_rows, uint32_t box_blk) {
    CUtensorMap m;
    cuuint64_t dims[3] = {64, rows, cols / 64};
    cuuint64_t strides[2] = {cols * 2, 128};
    cuuint32_t box[3] = {64, box_rows, box_blk};
    cuuint32_t es[3] = {1, 1, 1};
    fn(&m, CU_TENSOR_MAP_DATA_TYPE_BFLOAT16, 3, const_cast<void*>(ptr), dims, strides, box, es, CU_TENSOR_MAP_INTERLEAVE_NONE,
       CU_TENSOR_MAP_SWIZZLE_128B, CU_TENSOR_MAP_L2_PROMOTION_L2_256B, CU_TENSOR_MAP_FLOAT_OOB_FILL_NONE);
    return m;
}

extern "C" void kernel_launch(void* const* d_in, const int* in_sizes, int n_in, void* d_out, int out_size) {
    const bf16* x = (const bf16*)d_in[0];
    const bf16* kc = (const bf16*)d_in[1];
    const bf16* vc = (const bf16*)d_in[2];
    const bf16* wq = (const bf16*)d_in[3];
    const bf16* wo = (const bf16*)d_in[4];
    const bf16* w1 = (const bf16*)d_in[6];
    const bf16* w2 = (const bf16*)d_in[7];
    bf16* out = (bf16*)d_out;

    static EncodeFn fn = nullptr;
    static void *p_xn = nullptr, *p_h = nullptr, *p_o = nullptr, *p_g = nullptr;
    static Sched sched;
    if (!fn) {
        void* f = nullptr;
        cudaDriverEntryPointQueryResult st;
        cudaGetDriverEntryPoint("cuTensorMapEncodeTiled", &f, cudaEnableDefault, &st);
        fn = (EncodeFn)f;
        cudaGetSymbolAddress(&p_xn, g_xn);
        cudaGetSymbolAddress(&p_h, g_h);
        cudaGetSymbolAddress(&p_o, g_o);
        cudaGetSymbolAddress(&p_g, g_g);
        cudaFuncSetAttribute(attn_kernel, cudaFuncAttributeMaxDynamicSharedMemorySize, (int)sizeof(AttnSmem) + 1024);
        static const struct { int n, n1; const char* tail; } cls[] = {
            {20, 0, "G"}, {12, 1, "G"}, {32, 1, "E"}, {4, 1, "OO"}, {40, 3, "O"}, {8, 5, ""}, {16, 1, "EEO"}};
        int t1 = 0, t2 = 0, t3 = 0, t4 = 0, i = 0;
        for (const auto& cl : cls) {
            for (int c = 0; c < cl.n; c++, i++) {
                int n = 0;
                for (int j = 0; j < cl.n1; j++, t1++) sched.item[i][n++] = (uint16_t)((T_F1 << 12) | ((t1 % 14) << 4) | (t1 / 14));
                for (int t = i; t < NH * 16; t += NUM_CTAS) sched.item[i][n++] = (uint16_t)((T_ATT << 12) | ((t >> 4) << 4) | (t & 15));
                sched.end_att[i] = sched.end_wide[i] = (uint8_t)n;
                for (const char* p = cl.tail; *p; p++) {
                    if (*p == 'G') { sched.item[i][n++] = (uint16_t)((T_F2 << 12) | ((t2 & 1) << 4) | (t2 >> 1)); t2++; }
                    if (*p == 'E') { sched.item[i][n++] = (uint16_t)((T_OPE << 12) | (((t3 & 1) | ((t3 >> 5) << 2)) << 4) | ((t3 >> 1) & 15)); t3++; }
                    if (*p != 'O') sched.end_wide[i] = (uint8_t)n;
                    if (*p == 'O') { sched.item[i][n++] = (uint16_t)((T_OPF << 12) | ((t4 & 3) << 4) | (t4 >> 2)); t4++; }
                }
                sched.count[i] = (uint8_t)n;
            }
        }
    }
    CUtensorMap tm_xn_at = make_map(fn, p_xn, SEQ, DM, 128, 2);
    CUtensorMap tm_wq = make_map(fn, wq, DM, NH * DH, 128, 2);
    CUtensorMap tm_k = make_map(fn, kc, NH * SEQ, DH, 128, 2);
    CUtensorMap tm_v = make_map(fn, vc, NH * SEQ, DH, 128, 2);
    CUtensorMap tm_o_st = make_map(fn, p_o, SEQ, NH * DH, 64, 2);
    CUtensorMap tm_w1 = make_map(fn, w1, DM, FF, 128, 2);
    CUtensorMap tm_h_st = make_map(fn, p_h, SEQ, FF, 64, 2);
    CUtensorMap tm_h_ld = make_map(fn, p_h, SEQ, FF, 128, 1);
    CUtensorMap tm_w2 = make_map(fn, w2, FF, DM, 64, 4);
    CUtensorMap tm_g_st = make_map(fn, p_g, SEQ, DM, 64, 2);
    CUtensorMap tm_o_g = make_map(fn, p_o, SEQ, NH * DH, 128, 2);
    CUtensorMap tm_wo = make_map(fn, wo, NH * DH, DM, 128, 2);
    CUtensorMap tm_o_gw = make_map(fn, p_o, SEQ, NH * DH, 128, 1);
    CUtensorMap tm_wow = make_map(fn, wo, NH * DH, DM, 64, 4);

    ln_kernel<<<SEQ / 8, 256>>>(x);
    cudaLaunchAttribute pdl[1];
    pdl[0].id = cudaLaunchAttributeProgrammaticStreamSerialization;
    pdl[0].val.programmaticStreamSerializationAllowed = 1;
    cudaLaunchConfig_t cfg = {};
    cfg.gridDim = dim3(NUM_CTAS);
    cfg.blockDim = dim3(384);
    cfg.dynamicSmemBytes = sizeof(AttnSmem) + 1024;
    cfg.stream = cudaStreamPerThread;
    cfg.attrs = pdl;
    cfg.numAttrs = 1;
    cudaLaunchKernelEx(&cfg, attn_kernel, tm_xn_at, tm_wq, tm_k, tm_v, tm_o_st, tm_w1, tm_h_st, tm_h_ld, tm_w2, tm_g_st, tm_o_g,
                       tm_wo, tm_o_gw, tm_wow, x, out, sched);
}
```

```cpp
#include <cuda_runtime.h>
#include <cuda_bf16.h>
#include <cuda.h>
#include <stdint.h>

typedef __nv_bfloat16 bf16;
#define PP(x) x

constexpr int SEQ = 2048, DM = 512, NH = 32, DH = 128, FF = 1792;

__device__ __align__(1024) bf16 g_xn[SEQ * DM];
__device__ __align__(1024) bf16 g_h[SEQ * FF];
__device__ __align__(1024) bf16 g_o[SEQ * NH * DH];
__device__ uint4 g_g[64 * 8 * 256];
constexpr int C_H = 0, C_G = 16, C_P = C_G + 64, C_BAD = C_P + 64, C_RED = C_BAD + 16;
__device__ unsigned int g_cnt[256];
__device__ unsigned long long g_mask[16];
constexpr int OPE_N = 2, OPE_H = 14, OPF_H = NH - OPE_N * OPE_H;
__device__ float4 g_part[OPE_N * 64 * 16 * 256];
__device__ volatile float g_dummy;

__device__ __forceinline__ uint32_t smem_u32(const void* p) { return (uint32_t)__cvta_generic_to_shared(p); }

__device__ __forceinline__ void mbar_init(uint32_t bar, uint32_t count) {
    asm volatile("mbarrier.init.shared::cta.b64 [%0], %1;" ::"r"(bar), "r"(count) : "memory");
}
__device__ __forceinline__ void mbar_expect_tx(uint32_t bar, uint32_t bytes) {
    asm volatile("mbarrier.arrive.expect_tx.shared::cta.b64 _, [%0], %1;" ::"r"(bar), "r"(bytes) : "memory");
}
__device__ __forceinline__ void mbar_arrive(uint32_t bar) {
    asm volatile("mbarrier.arrive.shared::cta.b64 _, [%0];" ::"r"(bar) : "memory");
}
__device__ __forceinline__ bool mbar_try_wait(uint32_t bar, uint32_t parity) {
    uint32_t ok;
    asm volatile(
        "{\n.reg .pred p;\n"
        "mbarrier.test_wait.parity.shared::cta.b64 p, [%1], %2;\n"
        "selp.u32 %0, 1, 0, p;\n}\n"
        : "=r"(ok)
        : "r"(bar), "r"(parity)
        : "memory");
    return ok != 0;
}
__device__ __forceinline__ void mbar_wait(uint32_t bar, uint32_t parity) {
    asm volatile(
        "{\n.reg .pred P1;\n.reg .u32 n;\nmov.u32 n, 0;\n"
        "LAB_WAIT:\n"
        "mbarrier.try_wait.parity.shared::cta.b64 P1, [%0], %1;\n"
        "@P1 bra DONE;\n"
        "add.u32 n, n, 1;\n"
        "setp.lt.u32 P1, n, 4194304;\n"
        "@P1 bra LAB_WAIT;\n"
        "trap;\n"
        "DONE:\n}\n" ::"r"(bar), "r"(parity)
        : "memory");
}
__device__ __forceinline__ void tma_load_3d(uint32_t dst, const CUtensorMap* map, uint32_t bar, int c0, int c1, int c2) {
    asm volatile(
        "cp.async.bulk.tensor.3d.shared::cluster.global.mbarrier::complete_tx::bytes [%0], [%1, {%3, %4, %5}], [%2];"
        ::"r"(dst), "l"((uint64_t)map), "r"(bar), "r"(c0), "r"(c1), "r"(c2)
        : "memory");
}
__device__ __forceinline__ void tma_store_3d(const CUtensorMap* map, uint32_t src, int c0, int c1, int c2) {
    asm volatile("cp.async.bulk.tensor.3d.global.shared::cta.bulk_group [%0, {%2, %3, %4}], [%1];"
                 ::"l"((uint64_t)map), "r"(src), "r"(c0), "r"(c1), "r"(c2)
                 : "memory");
}
__device__ __forceinline__ void tma_commit() { asm volatile("cp.async.bulk.commit_group;" ::: "memory"); }
__device__ __forceinline__ void tma_wait_read0() { asm volatile("cp.async.bulk.wait_group.read 0;" ::: "memory"); }
__device__ __forceinline__ void tma_wait_all0() { asm volatile("cp.async.bulk.wait_group 0;" ::: "memory"); }
__device__ __forceinline__ void fence_proxy_async() { asm volatile("fence.proxy.async.shared::cta;" ::: "memory"); }
__device__ __forceinline__ void prefetch_tmap(const CUtensorMap* map) {
    asm volatile("prefetch.tensormap [%0];" ::"l"((uint64_t)map) : "memory");
}
__device__ __forceinline__ void pdl_wait() { asm volatile("griddepcontrol.wait;" ::: "memory"); }
__device__ __forceinline__ void pdl_launch() { asm volatile("griddepcontrol.launch_dependents;" ::: "memory"); }
__device__ __forceinline__ void named_sync(int id, int n) { asm volatile("bar.sync %0, %1;" ::"r"(id), "r"(n) : "memory"); }
__device__ __forceinline__ void named_arrive(int id, int n) { asm volatile("bar.arrive %0, %1;" ::"r"(id), "r"(n) : "memory"); }

__device__ __forceinline__ void wgmma_fence() { asm volatile("wgmma.fence.sync.aligned;" ::: "memory"); }
__device__ __forceinline__ void wgmma_commit() { asm volatile("wgmma.commit_group.sync.aligned;" ::: "memory"); }
template <int N>
__device__ __forceinline__ void wgmma_wait() { asm volatile("wgmma.wait_group.sync.aligned %0;" ::"n"(N) : "memory"); }

__device__ __forceinline__ void fence_acc(float (&d)[64]) {
#pragma unroll
    for (int i = 0; i < 64; i++) asm volatile("" : "+f"(d[i])::"memory");
}

template <int R>
__device__ __forceinline__ void reg_alloc() { asm volatile("setmaxnreg.inc.sync.aligned.u32 %0;" ::"n"(R)); }
template <int R>
__device__ __forceinline__ void reg_dealloc() { asm volatile("setmaxnreg.dec.sync.aligned.u32 %0;" ::"n"(R)); }

__device__ __forceinline__ uint64_t make_desc(uint32_t saddr, uint32_t lbo_bytes, uint32_t sbo_bytes) {
    uint64_t d = 0;
    d |= (uint64_t)((saddr & 0x3FFFF) >> 4);
    d |= (uint64_t)((lbo_bytes >> 4) & 0x3FFF) << 16;
    d |= (uint64_t)((sbo_bytes >> 4) & 0x3FFF) << 32;
    d |= (uint64_t)1 << 62;
    return d;
}

__device__ __forceinline__ float ex2(float x) {
    float y;
    asm volatile("ex2.approx.ftz.f32 %0, %1;" : "=f"(y) : "f"(x));
    return y;
}
__device__ __forceinline__ uint32_t pack_bf16(float lo, float hi) {
    uint32_t r;
    asm("cvt.rn.bf16x2.f32 %0, %1, %2;" : "=r"(r) : "f"(hi), "f"(lo));
    return r;
}
__device__ __forceinline__ uint32_t mul_bf16x2(uint32_t a, uint32_t b) {
    uint32_t r;
    asm("mul.rn.bf16x2 %0, %1, %2;" : "=r"(r) : "r"(a), "r"(b));
    return r;
}
__device__ __forceinline__ uint32_t add_bf16x2(uint32_t a, uint32_t b) {
    uint32_t r;
    asm("add.rn.bf16x2 %0, %1, %2;" : "=r"(r) : "r"(a), "r"(b));
    return r;
}
__device__ __forceinline__ unsigned int ld_acq(const unsigned int* p) {
    unsigned int v;
    asm volatile("ld.acquire.gpu.global.u32 %0, [%1];" : "=r"(v) : "l"(p) : "memory");
    return v;
}
__device__ __forceinline__ unsigned long long ld_acq64(const unsigned long long* p) {
    unsigned long long v;
    asm volatile("ld.acquire.gpu.global.u64 %0, [%1];" : "=l"(v) : "l"(p) : "memory");
    return v;
}
__device__ __forceinline__ uint32_t fma_bf16x2(uint32_t a, uint32_t b, uint32_t c) {
    uint32_t r;
    asm("fma.rn.bf16x2 %0, %1, %2, %3;" : "=r"(r) : "r"(a), "r"(b), "r"(c));
    return r;
}
__device__ __forceinline__ uint32_t max_bf16x2(uint32_t a, uint32_t b) {
    uint32_t r;
    asm("max.bf16x2 %0, %1, %2;" : "=r"(r) : "r"(a), "r"(b));
    return r;
}
__device__ __forceinline__ float bf16lo(uint32_t v) { return __uint_as_float(v << 16); }
__device__ __forceinline__ float bf16hi(uint32_t v) { return __uint_as_float(v & 0xffff0000u); }
__device__ __forceinline__ float bf16_round(float x) { return __bfloat162float(__float2bfloat16_rn(x)); }
__device__ __forceinline__ float silu_f(float x) {
    const float h = 0.5f * x;
    float t;
    asm("tanh.approx.f32 %0, %1;" : "=f"(t) : "f"(h));
    return fmaf(h, t, h);
}

__device__ __forceinline__ void stmatrix_x4(uint32_t addr, uint32_t r0, uint32_t r1, uint32_t r2, uint32_t r3) {
    asm volatile("stmatrix.sync.aligned.m8n8.x4.shared.b16 [%0], {%1, %2, %3, %4};"
                 ::"r"(addr), "r"(r0), "r"(r1), "r"(r2), "r"(r3)
                 : "memory");
}

#define ACC64(d) \
    "+f"(d[0]), "+f"(d[1]), "+f"(d[2]), "+f"(d[3]), "+f"(d[4]), "+f"(d[5]), "+f"(d[6]), "+f"(d[7]), \
    "+f"(d[8]), "+f"(d[9]), "+f"(d[10]), "+f"(d[11]), "+f"(d[12]), "+f"(d[13]), "+f"(d[14]), "+f"(d[15]), \
    "+f"(d[16]), "+f"(d[17]), "+f"(d[18]), "+f"(d[19]), "+f"(d[20]), "+f"(d[21]), "+f"(d[22]), "+f"(d[23]), \
    "+f"(d[24]), "+f"(d[25]), "+f"(d[26]), "+f"(d[27]), "+f"(d[28]), "+f"(d[29]), "+f"(d[30]), "+f"(d[31]), \
    "+f"(d[32]), "+f"(d[33]), "+f"(d[34]), "+f"(d[35]), "+f"(d[36]), "+f"(d[37]), "+f"(d[38]), "+f"(d[39]), \
    "+f"(d[40]), "+f"(d[41]), "+f"(d[42]), "+f"(d[43]), "+f"(d[44]), "+f"(d[45]), "+f"(d[46]), "+f"(d[47]), \
    "+f"(d[48]), "+f"(d[49]), "+f"(d[50]), "+f"(d[51]), "+f"(d[52]), "+f"(d[53]), "+f"(d[54]), "+f"(d[55]), \
    "+f"(d[56]), "+f"(d[57]), "+f"(d[58]), "+f"(d[59]), "+f"(d[60]), "+f"(d[61]), "+f"(d[62]), "+f"(d[63])

#define ACC64_STR \
    "{%0, %1, %2, %3, %4, %5, %6, %7, %8, %9, %10, %11, %12, %13, %14, %15, " \
    "%16, %17, %18, %19, %20, %21, %22, %23, %24, %25, %26, %27, %28, %29, %30, %31, " \
    "%32, %33, %34, %35, %36, %37, %38, %39, %40, %41, %42, %43, %44, %45, %46, %47, " \
    "%48, %49, %50, %51, %52, %53, %54, %55, %56, %57, %58, %59, %60, %61, %62, %63}"

template <int TB>
__device__ __forceinline__ void wgmma_ss_n128(float (&d)[64], uint64_t da, uint64_t db, int scale_d) {
    asm volatile(
        "{\n.reg .pred p;\nsetp.ne.b32 p, %66, 0;\n"
        "wgmma.mma_async.sync.aligned.m64n128k16.f32.bf16.bf16 " ACC64_STR ", %64, %65, p, 1, 1, 0, %67;\n}\n"
        : ACC64(d)
        : "l"(da), "l"(db), "r"(scale_d), "n"(TB));
}
template <int TB>
__device__ __forceinline__ void wgmma_rs_n128(float (&d)[64], uint32_t a0, uint32_t a1, uint32_t a2, uint32_t a3,
                                              uint64_t db, int scale_d) {
    asm volatile(
        "{\n.reg .pred p;\nsetp.ne.b32 p, %69, 0;\n"
        "wgmma.mma_async.sync.aligned.m64n128k16.f32.bf16.bf16 " ACC64_STR ", {%64, %65, %66, %67}, %68, p, 1, 1, %70;\n}\n"
        : ACC64(d)
        : "r"(a0), "r"(a1), "r"(a2), "r"(a3), "l"(db), "r"(scale_d), "n"(TB));
}

constexpr uint32_t DESC_HI = 0x40000040u;
__device__ __forceinline__ uint32_t desc_lo(uint32_t saddr, uint32_t lbo_bytes) {
    return ((saddr & 0x3FFFF) >> 4) | ((lbo_bytes >> 4) << 16);
}
template <int TB>
__device__ __forceinline__ void wgmma_ss_lo(float (&d)[64], uint32_t da, uint32_t db, int scale_d) {
    asm volatile(
        "{\n.reg .pred p;\n.reg .b64 xa, xb;\nsetp.ne.b32 p, %66, 0;\n"
        "mov.b64 xa, {%64, %68};\nmov.b64 xb, {%65, %68};\n"
        "wgmma.mma_async.sync.aligned.m64n128k16.f32.bf16.bf16 " ACC64_STR ", xa, xb, p, 1, 1, 0, %67;\n}\n"
        : ACC64(d)
        : "r"(da), "r"(db), "r"(scale_d), "n"(TB), "r"(DESC_HI));
}
__device__ __forceinline__ void wgmma_rs_lo_tb(float (&d)[64], uint32_t a0, uint32_t a1, uint32_t a2, uint32_t a3, uint32_t db) {
    asm volatile(
        "{\n.reg .b64 xb;\nmov.b64 xb, {%68, %69};\n"
        "wgmma.mma_async.sync.aligned.m64n128k16.f32.bf16.bf16 " ACC64_STR ", {%64, %65, %66, %67}, xb, 1, 1, 1, 1;\n}\n"
        : ACC64(d)
        : "r"(a0), "r"(a1), "r"(a2), "r"(a3), "r"(db), "r"(DESC_HI));
}

#define ACC8(d, o) "+f"(d[o]), "+f"(d[o + 1]), "+f"(d[o + 2]), "+f"(d[o + 3]), "+f"(d[o + 4]), "+f"(d[o + 5]), "+f"(d[o + 6]), "+f"(d[o + 7])
__device__ __forceinline__ void wgmma_rs_n64(float (&d)[64], uint32_t a0, uint32_t a1, uint32_t a2, uint32_t a3, uint32_t db) {
    asm volatile(
        "{\n.reg .b64 xb;\nmov.b64 xb, {%36, %37};\n"
        "wgmma.mma_async.sync.aligned.m64n64k16.f32.bf16.bf16 "
        "{%0, %1, %2, %3, %4, %5, %6, %7, %8, %9, %10, %11, %12, %13, %14, %15, "
        "%16, %17, %18, %19, %20, %21, %22, %23, %24, %25, %26, %27, %28, %29, %30, %31}, "
        "{%32, %33, %34, %35}, xb, 1, 1, 1, 1;\n}\n"
        : ACC8(d, 0), ACC8(d, 8), ACC8(d, 16), ACC8(d, 24)
        : "r"(a0), "r"(a1), "r"(a2), "r"(a3), "r"(db), "r"(DESC_HI));
}
__device__ __forceinline__ void wgmma_rs_n72(float (&d)[64], float (&l)[4], uint32_t a0, uint32_t a1, uint32_t a2, uint32_t a3, uint32_t db) {
    asm volatile(
        "{\n.reg .b64 xb;\nmov.b64 xb, {%40, %41};\n"
        "wgmma.mma_async.sync.aligned.m64n72k16.f32.bf16.bf16 "
        "{%0, %1, %2, %3, %4, %5, %6, %7, %8, %9, %10, %11, %12, %13, %14, %15, "
        "%16, %17, %18, %19, %20, %21, %22, %23, %24, %25, %26, %27, %28, %29, %30, %31, %32, %33, %34, %35}, "
        "{%36, %37, %38, %39}, xb, 1, 1, 1, 1;\n}\n"
        : ACC8(d, 32), ACC8(d, 40), ACC8(d, 48), ACC8(d, 56), "+f"(l[0]), "+f"(l[1]), "+f"(l[2]), "+f"(l[3])
        : "r"(a0), "r"(a1), "r"(a2), "r"(a3), "r"(db), "r"(DESC_HI));
}

__device__ __forceinline__ void wgmma_ss_n256_tb(float (&d)[128], uint64_t da, uint64_t db, int scale_d) {
    asm volatile(
        "{\n.reg .pred p;\nsetp.ne.b32 p, %130, 0;\n"
        "wgmma.mma_async.sync.aligned.m64n256k16.f32.bf16.bf16 "
        "{%0, %1, %2, %3, %4, %5, %6, %7, %8, %9, %10, %11, %12, %13, %14, %15, "
        "%16, %17, %18, %19, %20, %21, %22, %23, %24, %25, %26, %27, %28, %29, %30, %31, "
        "%32, %33, %34, %35, %36, %37, %38, %39, %40, %41, %42, %43, %44, %45, %46, %47, "
        "%48, %49, %50, %51, %52, %53, %54, %55, %56, %57, %58, %59, %60, %61, %62, %63, "
        "%64, %65, %66, %67, %68, %69, %70, %71, %72, %73, %74, %75, %76, %77, %78, %79, "
        "%80, %81, %82, %83, %84, %85, %86, %87, %88, %89, %90, %91, %92, %93, %94, %95, "
        "%96, %97, %98, %99, %100, %101, %102, %103, %104, %105, %106, %107, %108, %109, %110, %111, "
        "%112, %113, %114, %115, %116, %117, %118, %119, %120, %121, %122, %123, %124, %125, %126, %127}, "
        "%128, %129, p, 1, 1, 0, 1;\n}\n"
        : ACC8(d, 0), ACC8(d, 8), ACC8(d, 16), ACC8(d, 24), ACC8(d, 32), ACC8(d, 40), ACC8(d, 48), ACC8(d, 56),
          ACC8(d, 64), ACC8(d, 72), ACC8(d, 80), ACC8(d, 88), ACC8(d, 96), ACC8(d, 104), ACC8(d, 112), ACC8(d, 120)
        : "l"(da), "l"(db), "r"(scale_d));
}

__global__ void __launch_bounds__(256) ln_kernel(const bf16* __restrict__ x) {
    pdl_launch();
    int warp = threadIdx.x >> 5, lane = threadIdx.x & 31;
    int row = blockIdx.x * 8 + warp;
    if (blockIdx.x == 0) g_cnt[threadIdx.x] = 0;
    if (blockIdx.x == 1 && threadIdx.x < 16) g_mask[threadIdx.x] = 0;
    const uint4* src = reinterpret_cast<const uint4*>(x + (size_t)row * DM);
    uint4 v[2];
    v[0] = src[lane];
    v[1] = src[lane + 32];
    float f[16];
#pragma unroll
    for (int i = 0; i < 2; i++) {
        const __nv_bfloat162* p = reinterpret_cast<const __nv_bfloat162*>(&v[i]);
#pragma unroll
        for (int j = 0; j < 4; j++) {
            float2 t = __bfloat1622float2(p[j]);
            f[i * 8 + j * 2] = t.x;
            f[i * 8 + j * 2 + 1] = t.y;
        }
    }
    float s = 0.f;
#pragma unroll
    for (int i = 0; i < 16; i++) s += f[i];
#pragma unroll
    for (int o = 16; o > 0; o >>= 1) s += __shfl_xor_sync(0xffffffffu, s, o);
    float mean = s * (1.0f / DM);
    float q = 0.f;
#pragma unroll
    for (int i = 0; i < 16; i++) {
        float d = f[i] - mean;
        q += d * d;
    }
#pragma unroll
    for (int o = 16; o > 0; o >>= 1) q += __shfl_xor_sync(0xffffffffu, q, o);
    float var_b = bf16_round(q * (1.0f / DM));
    float mean_b = bf16_round(mean);
    float den = bf16_round(sqrtf(bf16_round(var_b + 1e-5f)));
    uint4 o[2];
#pragma unroll
    for (int i = 0; i < 2; i++) {
        uint32_t* p = reinterpret_cast<uint32_t*>(&o[i]);
#pragma unroll
        for (int j = 0; j < 4; j++) {
            float a = bf16_round(f[i * 8 + j * 2] - mean_b) / den;
            float b = bf16_round(f[i * 8 + j * 2 + 1] - mean_b) / den;
            p[j] = pack_bf16(a, b);
        }
    }
    uint4* dst = reinterpret_cast<uint4*>(g_xn + (size_t)row * DM);
    dst[lane] = o[0];
    dst[lane + 32] = o[1];
}

constexpr int AT_STAGES = 3;
constexpr int TILE_BYTES = 128 * 128 * 2;
struct __align__(1024) AttnSmem {
    uint8_t k[AT_STAGES][TILE_BYTES];
    uint8_t v[AT_STAGES][TILE_BYTES];
    uint8_t o[TILE_BYTES];
    uint32_t ones0[4];
    uint64_t full_k[AT_STAGES], full_v[AT_STAGES], empty_k[AT_STAGES], empty_v[AT_STAGES];
    uint64_t st_free[2];
    uint64_t redo_bar;
    uint32_t redo;
    uint32_t pad0;
    uint32_t ones1[4];
    uint64_t fin_bar[4];
    uint32_t pad1[24];
    uint32_t ones2[(2048 - 288) / 4];
};

#define EXPO(x) x
#define N8(x) x
#define PPK 8
#define FAST_BIAS (-40.0f)
constexpr int NUM_CTAS = 132;
constexpr int MAX_ITEMS = 12;
enum { T_ATT = 0, T_F1 = 1, T_F2 = 2, T_OPE = 3, T_OPF = 4 };
struct Sched {
    uint16_t item[NUM_CTAS][MAX_ITEMS];
    uint8_t count[NUM_CTAS], end_att[NUM_CTAS], end_wide[NUM_CTAS];
};

__global__ void __launch_bounds__(384, 1)
attn_kernel(const __grid_constant__ CUtensorMap tm_xn, const __grid_constant__ CUtensorMap tm_wq,
            const __grid_constant__ CUtensorMap tm_k, const __grid_constant__ CUtensorMap tm_v,
            const __grid_constant__ CUtensorMap tm_o, const __grid_constant__ CUtensorMap tm_w1,
            const __grid_constant__ CUtensorMap tm_hst, const __grid_constant__ CUtensorMap tm_hld,
            const __grid_constant__ CUtensorMap tm_w2,
            const __grid_constant__ CUtensorMap tm_old, const __grid_constant__ CUtensorMap tm_wo,
            const __grid_constant__ CUtensorMap tm_oldw, const __grid_constant__ CUtensorMap tm_wow,
            const bf16* __restrict__ x, bf16* __restrict__ out, const __grid_constant__ Sched sched) {
    extern __shared__ uint8_t smem_raw[];
    AttnSmem& sm = *reinterpret_cast<AttnSmem*>((reinterpret_cast<uintptr_t>(smem_raw) + 1023) & ~uintptr_t(1023));
    const int tid = threadIdx.x;
    const int wg = __shfl_sync(0xffffffffu, tid >> 7, 0);
    const int n_items = sched.count[blockIdx.x];
    if (tid == 32) {
        prefetch_tmap(&tm_xn); prefetch_tmap(&tm_wq); prefetch_tmap(&tm_k); prefetch_tmap(&tm_v); prefetch_tmap(&tm_o);
        prefetch_tmap(&tm_w1); prefetch_tmap(&tm_hst); prefetch_tmap(&tm_hld); prefetch_tmap(&tm_w2);
        prefetch_tmap(&tm_old); prefetch_tmap(&tm_wo); prefetch_tmap(&tm_oldw); prefetch_tmap(&tm_wow);
    }

    if (tid == 0) {
#pragma unroll
        for (int s = 0; s < AT_STAGES; s++) {
            mbar_init(smem_u32(&sm.full_k[s]), 1);
            mbar_init(smem_u32(&sm.full_v[s]), 1);
            mbar_init(smem_u32(&sm.empty_k[s]), 8);
            mbar_init(smem_u32(&sm.empty_v[s]), 8);
        }
        mbar_init(smem_u32(&sm.st_free[0]), 1);
        mbar_init(smem_u32(&sm.st_free[1]), 1);
        mbar_init(smem_u32(&sm.redo_bar), 8);
#pragma unroll
        for (int s = 0; s < 4; s++) mbar_init(smem_u32(&sm.fin_bar[s]), 1);
        sm.redo = 0;
        asm volatile("fence.mbarrier_init.release.cluster;" ::: "memory");
    }
    if (tid < 64) {
        const int r = tid >> 2;
        sm.ones0[(r >> 3) * 256 + (r & 7) * 36 + (tid & 3)] = 0x3F803F80u;
        fence_proxy_async();
    }
    __syncthreads();
    pdl_wait();
    int it = 0;
    uint32_t rmask = 0;
    bool redo = false;
    auto next_item = [&]() -> bool {
        if (!redo) {
            if (++it < n_items) return true;
            mbar_wait(smem_u32(&sm.redo_bar), 0);
            rmask = *reinterpret_cast<volatile uint32_t*>(&sm.redo);
            rmask = (rmask | (rmask >> 16)) & 0xffffu;
            redo = true;
        }
        if (!rmask) return false;
        it = __ffs(rmask) - 1;
        rmask &= rmask - 1;
        return true;
    };
    constexpr int BAR_SCHED0 = 1, BAR_EPI0 = 3, BAR_ST0 = 5;

    if (wg == 0) {
        reg_dealloc<40>();
        if (tid >= 32 && tid < 96) {
            const int cw = (tid >> 5) - 1;
            const uint32_t obase = smem_u32(sm.o) + cw * 16384;
            do {
                const int item = sched.item[blockIdx.x][it];
                const int type = item >> 12, a = (item >> 4) & 0xff, b = item & 15;
                if (type == T_OPF) continue;
                named_sync(BAR_ST0 + cw, 160);
                if ((tid & 31) == 0) {
                    if (type >= T_F2) {
                        __threadfence();
                        atomicAdd(&g_cnt[(type == T_F2 ? C_G : C_P) + b * 2 + (a & 1)], 1u);
                    } else {
                        if (redo) tma_wait_all0();
                        tma_store_3d(type == T_ATT ? &tm_o : &tm_hst, obase, 0, b * 128 + cw * 64, a * 2);
                        tma_commit();
                        tma_wait_read0();
                        mbar_arrive(smem_u32(&sm.st_free[cw]));
                        const bool bad = (*reinterpret_cast<volatile uint32_t*>(&sm.redo) >> (16 * cw + it)) & 1;
                        if (bad && !redo) atomicAdd(&g_cnt[C_BAD + b], 1u);
                        tma_wait_all0();
                        asm volatile("fence.proxy.async;" ::: "memory");
                        __threadfence();
                        if (type != T_ATT) atomicAdd(&g_cnt[C_H + b], 1u);
                        else if (!redo) atomicOr(&g_mask[b], 1ull << (2 * a + cw));
                        else if (bad) atomicAdd(&g_cnt[C_RED + b], 1u);
                    }
                }
                __syncwarp();
            } while (next_item());
            if ((tid & 31) == 0) tma_wait_all0();
        }
        if (tid == 96) {
            int ord = 0;
            for (int i = 0; i < n_items; i++) {
                const int item = sched.item[blockIdx.x][i];
                const int a = (item >> 4) & 0xff, b = item & 15;
                if ((item >> 12) != T_OPF) continue;
                unsigned int spins = 0;
                while (ld_acq64(&g_mask[b]) != ~0ull && ++spins < (1u << 24)) {}
                while (ld_acq(&g_cnt[C_P + b * 2 + (a >> 1)]) < 2 * OPE_N && ++spins < (1u << 24)) {}
                while (ld_acq(&g_cnt[C_G + b * 2 + (a >> 1)]) < 2 && ++spins < (1u << 24)) {}
                if (ld_acq(&g_cnt[C_BAD + b])) atomicOr(&sm.redo, 1u << i);
                mbar_arrive(smem_u32(&sm.fin_bar[ord++]));
            }
        }
        if (tid == 0) {
            int stage = 0;
            uint32_t phase = 0;
            do {
                const int item = sched.item[blockIdx.x][it];
                const int type = item >> 12, a = (item >> 4) & 0xff, b = item & 15;
                const CUtensorMap* ta = type < T_F2 ? &tm_xn : (type == T_F2 ? &tm_hld : (type == T_OPE ? &tm_oldw : &tm_old));
                const CUtensorMap* tb = type < T_F2 ? (type == T_ATT ? &tm_wq : &tm_w1) : (type == T_F2 ? &tm_w2 : (type == T_OPE ? &tm_wow : &tm_wo));
                const bool wide = type == T_F2 || type == T_OPE;
                int nch = DM / 128, kc0 = 0, nb = a;
                unsigned long long need = 0, mask = 0;
                unsigned int spins = 0;
                if (type == T_F2) {
                    nch = FF / 128;
                    nb = a * 2;
                    while (ld_acq(&g_cnt[C_H + b]) < 2 * (FF / 128) && ++spins < (1u << 24)) {}
                    asm volatile("fence.proxy.async;" ::: "memory");
                } else if (type == T_OPE) {
                    nch = OPE_H;
                    kc0 = (a >> 2) * OPE_H;
                    nb = (a & 1) * 2;
                    need = 3ull << (2 * kc0);
                } else if (type == T_OPF) {
                    if (!redo) {
                        nch = OPF_H;
                        kc0 = NH - OPF_H;
                        need = 3ull << (2 * kc0);
                    } else {
                        nch = NH;
                        const unsigned int nbad = ld_acq(&g_cnt[C_BAD + b]);
                        while (ld_acq(&g_cnt[C_RED + b]) < nbad && ++spins < (1u << 24)) {}
                        asm volatile("fence.proxy.async;" ::: "memory");
                    }
                }
                for (int kc = kc0; kc < kc0 + nch; kc++) {
                    if ((mask & need) != need) {
                        do mask = ld_acq64(&g_mask[b]); while ((mask & need) != need && ++spins < (1u << 24));
                        asm volatile("fence.proxy.async;" ::: "memory");
                    }
                    need <<= 2;
                    for (int hk = 0; hk <= (int)wide; hk++) {
                        mbar_wait(smem_u32(&sm.empty_k[stage]), phase ^ 1);
                        mbar_expect_tx(smem_u32(&sm.full_k[stage]), wide ? TILE_BYTES / 2 : TILE_BYTES);
                        tma_load_3d(smem_u32(sm.k[stage]), ta, smem_u32(&sm.full_k[stage]), 0, b * 128, kc * 2 + hk);
                        mbar_wait(smem_u32(&sm.empty_v[stage]), phase ^ 1);
                        mbar_expect_tx(smem_u32(&sm.full_v[stage]), TILE_BYTES);
                        tma_load_3d(smem_u32(sm.v[stage]), tb, smem_u32(&sm.full_v[stage]), 0, kc * 128 + hk * 64, nb * 2);
                        if (++stage == AT_STAGES) { stage = 0; phase ^= 1; }
                    }
                }
                if (type == T_ATT) {
                    for (int j = 0; j < 16; j++) {
                        mbar_wait(smem_u32(&sm.empty_k[stage]), phase ^ 1);
                        mbar_expect_tx(smem_u32(&sm.full_k[stage]), TILE_BYTES);
                        tma_load_3d(smem_u32(sm.k[stage]), &tm_k, smem_u32(&sm.full_k[stage]), 0, a * SEQ + j * 128, 0);
                        mbar_wait(smem_u32(&sm.empty_v[stage]), phase ^ 1);
                        mbar_expect_tx(smem_u32(&sm.full_v[stage]), TILE_BYTES);
                        tma_load_3d(smem_u32(sm.v[stage]), &tm_v, smem_u32(&sm.full_v[stage]), 0, a * SEQ + j * 128, 0);
                        if (++stage == AT_STAGES) { stage = 0; phase ^= 1; }
                    }
                }
            } while (next_item());
        }
    } else {
        reg_alloc<232>();
        const int cw = wg - 1;
        const int lane = tid & 31;
        const int warp_in_wg = (tid >> 5) & 3;
        const float c = 1.4426950408889634f;
        const uint32_t SCALE_HI2 = 0x3DB53DB5u, SCALE_LO2 = 0x371E371Eu;
        const uint32_t obase = smem_u32(sm.o) + cw * 16384;
        const int st_row = warp_in_wg * 16 + ((lane >> 3) & 1) * 8 + (lane & 7);

        const uint32_t dq = __shfl_sync(0xffffffffu, desc_lo(obase, 16), 0);
        const uint32_t dk0 = __shfl_sync(0xffffffffu, desc_lo(smem_u32(sm.k[0]), 16), 0);
        const uint32_t dv0 = dk0 - (1u << 16) + (1024u << 16) + AT_STAGES * (TILE_BYTES >> 4);

        PP(if (cw == 1) named_arrive(BAR_SCHED0 + 0, 256));

        int stage = 0;
        uint32_t phase = 0;
        float S[64];
        uint32_t P[32], P2[32];
        uint32_t cnt = 0;
        const uint32_t dw0 = __shfl_sync(0xffffffffu, desc_lo(smem_u32(sm.v[0]) + 16384, smem_u32(sm.ones0) - smem_u32(sm.v[0]) - 16384), 0);
        constexpr uint32_t DW_K = 128u - (128u << 16), DW_ST = 2048u - (2048u << 16);

        const uint32_t fk0 = smem_u32(&sm.full_k[0]), fv0 = smem_u32(&sm.full_v[0]);
        const uint32_t ek0 = smem_u32(&sm.empty_k[0]), ev0 = smem_u32(&sm.empty_v[0]);
        int vstage = 0;
        uint32_t vphase = 0;
        bool okk = false, okv = false;

        auto gemm_chunk = [&](float (&S)[64], bool acc, bool real) {
            if (real) {
                mbar_wait(fk0 + stage * 8, phase);
                mbar_wait(fv0 + stage * 8, phase);
            }
            const uint64_t da = make_desc(smem_u32(sm.k[stage]) + cw * 64 * 128, 16, 1024);
            const uint64_t db = make_desc(smem_u32(sm.v[stage]), 16384, 1024);
            wgmma_fence();
#pragma unroll
            for (int kk = 0; kk < 8; kk++) {
                wgmma_ss_n128<1>(S, da + (uint64_t)(((kk >> 2) * 16384 + (kk & 3) * 32) >> 4),
                                 db + (uint64_t)((kk * 2048) >> 4), acc || kk != 0);
            }
            wgmma_commit();
        };
        auto gemm_rest = [&](float (&S)[64], int nch) {
            int prev = stage;
            if (++stage == AT_STAGES) { stage = 0; phase ^= 1; }
#pragma unroll 1
            for (int kc = 1; kc < nch; kc++) {
                gemm_chunk(S, true, true);
                wgmma_wait<1>();
                if (lane == 0) {
                    mbar_arrive(ek0 + prev * 8);
                    mbar_arrive(ev0 + prev * 8);
                }
                prev = stage;
                if (++stage == AT_STAGES) { stage = 0; phase ^= 1; }
            }
            wgmma_wait<0>();
            if (lane == 0) {
                mbar_arrive(ek0 + prev * 8);
                mbar_arrive(ev0 + prev * 8);
            }
        };
        auto pack_p = [&](float (&S)[64]) {
#pragma unroll
            for (int i = 0; i < 32; i++) P[i] = pack_bf16(S[2 * i], S[2 * i + 1]);
        };
        auto final_epi = [&](float (&T)[64], int mb, int nb) {
            const int t = tid & 127, ch = t & 15, row0 = t >> 4;
            const size_t off = (size_t)(mb * 128 + cw * 64 + row0) * DM + nb * 128 + ch * 8;
            uint4 xv[8];
#pragma unroll
            for (int i = 0; i < 8; i++) xv[i] = *reinterpret_cast<const uint4*>(x + off + (size_t)i * 8 * DM);
            mbar_wait(smem_u32(&sm.st_free[cw]), (cnt & 1) ^ 1);
#pragma unroll
            for (int i = 0; i < 16; i += 2) {
                const uint4 gv = __ldcg(g_g + ((mb * 4 + nb) * 8 + (i >> 1)) * 256 + (tid - 128));
                const int cc = i + (lane >> 4);
                const uint32_t addr = obase + (cc >> 3) * 8192 + st_row * 128 + (((cc & 7) ^ (st_row & 7)) << 4);
                stmatrix_x4(addr, mul_bf16x2(pack_bf16(T[4 * i], T[4 * i + 1]), gv.x), mul_bf16x2(pack_bf16(T[4 * i + 2], T[4 * i + 3]), gv.y),
                            mul_bf16x2(pack_bf16(T[4 * i + 4], T[4 * i + 5]), gv.z), mul_bf16x2(pack_bf16(T[4 * i + 6], T[4 * i + 7]), gv.w));
            }
            named_sync(BAR_EPI0 + cw, 128);
            const uint32_t sa = obase + (ch >> 3) * 8192 + row0 * 128 + (((ch & 7) ^ row0) << 4);
#pragma unroll
            for (int i = 0; i < 8; i++) {
                uint4 sv;
                asm volatile("ld.shared.v4.u32 {%0, %1, %2, %3}, [%4];" : "=r"(sv.x), "=r"(sv.y), "=r"(sv.z), "=r"(sv.w) : "r"(sa + i * 1024));
                sv.x = add_bf16x2(xv[i].x, sv.x);
                sv.y = add_bf16x2(xv[i].y, sv.y);
                sv.z = add_bf16x2(xv[i].z, sv.z);
                sv.w = add_bf16x2(xv[i].w, sv.w);
                *reinterpret_cast<uint4*>(out + off + (size_t)i * 8 * DM) = sv;
            }
            named_sync(BAR_EPI0 + cw, 128);
        };
        auto stage_p = [&](uint32_t (&P)[32]) {
            mbar_wait(smem_u32(&sm.st_free[cw]), (cnt & 1) ^ 1);
            cnt++;
#pragma unroll
            for (int i = 0; i < 16; i += 2) {
                const int cc = i + (lane >> 4);
                const uint32_t addr = obase + (cc >> 3) * 8192 + st_row * 128 + (((cc & 7) ^ (st_row & 7)) << 4);
                stmatrix_x4(addr, P[2 * i], P[2 * i + 1], P[2 * i + 2], P[2 * i + 3]);
            }
            fence_proxy_async();
        };
        auto issue_qk = [&](uint32_t dk) {
            wgmma_fence();
#pragma unroll
            for (int kk = 0; kk < 8; kk++)
                wgmma_ss_lo<0>(S, dq + (((kk >> 2) * 8192 + (kk & 3) * 32) >> 4),
                               dk + (((kk >> 2) * 16384 + (kk & 3) * 32) >> 4), kk != 0);
            wgmma_commit();
        };
        auto issue_pv = [&](float (&O)[64], float (&L)[4], uint32_t (&Pc)[32], int vs) {
            const uint32_t dv = dv0 + vs * (TILE_BYTES >> 4), dw = dw0 + vs * DW_ST;
            wgmma_fence();
#pragma unroll
            for (int kk = 0; kk < 8; kk++) {
                wgmma_rs_n64(O, Pc[4 * kk], Pc[4 * kk + 1], Pc[4 * kk + 2], Pc[4 * kk + 3], dv + ((kk * 2048) >> 4));
                wgmma_rs_n72(O, L, Pc[4 * kk], Pc[4 * kk + 1], Pc[4 * kk + 2], Pc[4 * kk + 3], dw + kk * DW_K);
            }
            wgmma_commit();
        };
        auto epilogue = [&](float (&O)[64], float (&L)[4]) {
            const float i0 = 1.0f / L[0], i1 = 1.0f / L[2];
            named_sync(BAR_EPI0 + cw, 128);
#pragma unroll
            for (int i = 0; i < 16; i += 2) {
                const int cc = i + (lane >> 4);
                const uint32_t addr = obase + (cc >> 3) * 8192 + st_row * 128 + (((cc & 7) ^ (st_row & 7)) << 4);
                stmatrix_x4(addr, pack_bf16(O[4 * i] * i0, O[4 * i + 1] * i0), pack_bf16(O[4 * i + 2] * i1, O[4 * i + 3] * i1),
                            pack_bf16(O[4 * i + 4] * i0, O[4 * i + 5] * i0), pack_bf16(O[4 * i + 6] * i1, O[4 * i + 7] * i1));
            }
            fence_proxy_async();
            named_arrive(BAR_ST0 + cw, 160);
        };
        auto scores_max = [&](uint32_t (&T)[32], float& x0, float& x1) {
#pragma unroll
            for (int i = 0; i < 32; i++) {
                const uint32_t sb = pack_bf16(S[2 * i], S[2 * i + 1]);
                T[i] = fma_bf16x2(sb, SCALE_HI2, mul_bf16x2(sb, SCALE_LO2));
            }
            uint32_t y0 = max_bf16x2(T[0], T[2]), y1 = max_bf16x2(T[1], T[3]);
#pragma unroll
            for (int i = 2; i < 16; i++) {
                y0 = max_bf16x2(y0, T[2 * i]);
                y1 = max_bf16x2(y1, T[2 * i + 1]);
            }
            x0 = fmaxf(bf16lo(y0), bf16hi(y0));
            x1 = fmaxf(bf16lo(y1), bf16hi(y1));
            x0 = fmaxf(x0, __shfl_xor_sync(0xffffffffu, x0, 1));
            x1 = fmaxf(x1, __shfl_xor_sync(0xffffffffu, x1, 1));
            x0 = fmaxf(x0, __shfl_xor_sync(0xffffffffu, x0, 2));
            x1 = fmaxf(x1, __shfl_xor_sync(0xffffffffu, x1, 2));
        };
        auto first_block = [&]() {
            stage_p(P);
            named_sync(BAR_EPI0 + cw, 128);
            vstage = stage;
            vphase = phase;
            mbar_wait(fk0 + stage * 8, phase);
            PP(named_sync(BAR_SCHED0 + cw, 256));
            issue_qk(dk0 + stage * (TILE_BYTES >> 4));
            PP(named_arrive(BAR_SCHED0 + (cw ^ 1), 256));
            if (++stage == AT_STAGES) { stage = 0; phase ^= 1; }
            okk = mbar_try_wait(fk0 + stage * 8, phase);
            okv = mbar_try_wait(fv0 + vstage * 8, vphase);
            wgmma_wait<0>();
            if (lane == 0) mbar_arrive(ek0 + vstage * 8);
        };

        int nfin = 0;
        gemm_chunk(S, false, true);
#pragma unroll 1
        for (; it < sched.end_att[blockIdx.x]; it++) {
            const int item = sched.item[blockIdx.x][it];
            const int type = item >> 12;
            const bool has_next = it + 1 < sched.end_att[blockIdx.x];
            gemm_rest(S, DM / 128);
            if (type == T_F1) {
                pack_p(S);
                gemm_chunk(S, false, has_next);
#pragma unroll
                for (int i = 0; i < 32; i++) P[i] = pack_bf16(silu_f(bf16lo(P[i])), silu_f(bf16hi(P[i])));
                stage_p(P);
                named_arrive(BAR_ST0 + cw, 160);
            } else {
                pack_p(S);
                first_block();
                float O[64], L[4] = {0.f, 0.f, 0.f, 0.f};
#pragma unroll
                for (int i = 0; i < 64; i++) O[i] = 0.f;
                float n0, n1;
                {
                    float x0, x1;
                    scores_max(P2, x0, x1);
                    n0 = fmaf(-x0, c, FAST_BIAS);
                    n1 = fmaf(-x1, c, FAST_BIAS);
#pragma unroll
                    for (int i = 0; i < 16; i++) {
                        const float e0 = ex2(fmaf(bf16lo(P2[2 * i]), c, n0));
                        const float e1 = ex2(fmaf(bf16hi(P2[2 * i]), c, n0));
                        const float e2 = ex2(fmaf(bf16lo(P2[2 * i + 1]), c, n1));
                        const float e3 = ex2(fmaf(bf16hi(P2[2 * i + 1]), c, n1));
                        P[2 * i] = pack_bf16(e0, e1);
                        P[2 * i + 1] = pack_bf16(e2, e3);
                    }
                }
                auto expo = [&](uint32_t (&Pn)[32], int i_lo, int i_hi) {
#pragma unroll
                    for (int i = i_lo; i < i_hi; i++) {
                        const uint32_t sa = pack_bf16(S[4 * i], S[4 * i + 1]), sb = pack_bf16(S[4 * i + 2], S[4 * i + 3]);
                        const uint32_t ta = fma_bf16x2(sa, SCALE_HI2, mul_bf16x2(sa, SCALE_LO2));
                        const uint32_t tb = fma_bf16x2(sb, SCALE_HI2, mul_bf16x2(sb, SCALE_LO2));
                        const float e0 = ex2(fmaf(bf16lo(ta), c, n0));
                        const float e1 = ex2(fmaf(bf16hi(ta), c, n0));
                        const float e2 = ex2(fmaf(bf16lo(tb), c, n1));
                        float e3 = ex2(fmaf(bf16hi(tb), c, n1));
                        if (i == i_hi - 1 && i_hi < 16) while (e3 < 0.f) e3 = g_dummy;
                        Pn[2 * i] = pack_bf16(e0, e1);
                        Pn[2 * i + 1] = pack_bf16(e2, e3);
                    }
                };
                auto step = [&](uint32_t (&Pc)[32], uint32_t (&Pn)[32]) {
                    const int ust = __shfl_sync(0xffffffffu, stage, 0), uvs = __shfl_sync(0xffffffffu, vstage, 0);
                    if (!okk) mbar_wait(fk0 + stage * 8, phase);
                    if (!okv) mbar_wait(fv0 + vstage * 8, vphase);
                    PP(named_sync(BAR_SCHED0 + cw, 256));
                    issue_qk(dk0 + ust * (TILE_BYTES >> 4));
                    issue_pv(O, L, Pc, uvs);
                    PP(named_arrive(BAR_SCHED0 + (cw ^ 1), 256));
                    const int pv = vstage;
                    vstage = stage;
                    vphase = phase;
                    if (++stage == AT_STAGES) { stage = 0; phase ^= 1; }
                    okk = mbar_try_wait(fk0 + stage * 8, phase);
                    okv = mbar_try_wait(fv0 + vstage * 8, vphase);
                    wgmma_wait<1>();
                    if (lane == 0) mbar_arrive(ek0 + vstage * 8);
                    EXPO(expo(Pn, 0, 8));
                    wgmma_wait<0>();
                    if (lane == 0) mbar_arrive(ev0 + pv * 8);
                    EXPO(expo(Pn, 8, 16));
                };
#pragma unroll 1
                for (int j = 0; j < 7; j++) {
                    step(P, P2);
                    step(P2, P);
                }
                step(P, P2);
                if (!okv) mbar_wait(fv0 + vstage * 8, vphase);
                issue_pv(O, L, P2, vstage);
                gemm_chunk(S, false, has_next);
                wgmma_wait<1>();
                if (lane == 0) mbar_arrive(ev0 + vstage * 8);
                float z = fmaf(L[0], 0.f, L[2] * 0.f);
#pragma unroll
                for (int i = 0; i < 64; i++) z = fmaf(O[i], 0.f, z);
                if (__any_sync(0xffffffffu, z != 0.f) && lane == 0) atomicOr(&sm.redo, 1u << (16 * cw + it));
                epilogue(O, L);
            }
        }
        wgmma_wait<0>();
#pragma unroll 1
        for (; it < sched.end_wide[blockIdx.x]; it++) {
            const int item = sched.item[blockIdx.x][it];
            const int type = item >> 12, a = (item >> 4) & 0xff, b = item & 15;
            const int nk = type == T_F2 ? FF / 64 : 2 * OPE_H;
            float acc[128];
            int prev = -1;
#pragma unroll 1
            for (int kt = 0; kt < nk; kt++) {
                mbar_wait(fk0 + stage * 8, phase);
                mbar_wait(fv0 + stage * 8, phase);
                const uint64_t da = make_desc(smem_u32(sm.k[stage]) + cw * 64 * 128, 16, 1024);
                const uint64_t db = make_desc(smem_u32(sm.v[stage]), 8192, 1024);
                wgmma_fence();
#pragma unroll
                for (int kk = 0; kk < 4; kk++)
                    wgmma_ss_n256_tb(acc, da + (uint64_t)((kk * 32) >> 4), db + (uint64_t)((kk * 2048) >> 4), (kt | kk) != 0);
                wgmma_commit();
                wgmma_wait<1>();
                if (prev >= 0 && lane == 0) {
                    mbar_arrive(ek0 + prev * 8);
                    mbar_arrive(ev0 + prev * 8);
                }
                prev = stage;
                if (++stage == AT_STAGES) { stage = 0; phase ^= 1; }
            }
            wgmma_wait<0>();
            if (lane == 0) {
                mbar_arrive(ek0 + prev * 8);
                mbar_arrive(ev0 + prev * 8);
            }
            if (type == T_F2) {
                uint4* gp = g_g + (b * 4 + a * 2) * (8 * 256) + (tid - 128);
#pragma unroll
                for (int j = 0; j < 16; j++) {
                    uint32_t y[4];
#pragma unroll
                    for (int i = 0; i < 4; i++)
                        y[i] = pack_bf16(silu_f(bf16_round(acc[8 * j + 2 * i])), silu_f(bf16_round(acc[8 * j + 2 * i + 1])));
                    __stcg(gp + j * 256, make_uint4(y[0], y[1], y[2], y[3]));
                }
            } else {
                float4* part = g_part + (size_t)(((a >> 2) * 16 + b) * 4 + (a & 1) * 2) * (16 * 256) + (tid - 128);
#pragma unroll
                for (int j = 0; j < 32; j++) __stcg(part + j * 256, make_float4(acc[4 * j], acc[4 * j + 1], acc[4 * j + 2], acc[4 * j + 3]));
            }
            named_arrive(BAR_ST0 + cw, 160);
        }
        float S3[64];
        gemm_chunk(S3, false, it < n_items);
#pragma unroll 1
        for (; it < n_items; it++) {
            const int item = sched.item[blockIdx.x][it];
            const int a = (item >> 4) & 0xff, b = item & 15;
            gemm_rest(S3, OPF_H);
            float T[64];
#pragma unroll
            for (int i = 0; i < 64; i++) T[i] = S3[i] + 0.f;
            fence_acc(T);
            gemm_chunk(S3, false, it + 1 < n_items);
            const float4* part = g_part + (size_t)(b * 4 + a) * (16 * 256) + (tid - 128);
            mbar_wait(smem_u32(&sm.fin_bar[nfin++]), 0);
            if (!((*reinterpret_cast<volatile uint32_t*>(&sm.redo) >> it) & 1)) {
#pragma unroll
                for (int g = 0; g < OPE_N; g++) {
#pragma unroll
                    for (int j = 0; j < 16; j++) {
                        const float4 v = __ldcg(part + (size_t)g * (64 * 16 * 256) + j * 256);
                        T[4 * j] += v.x;
                        T[4 * j + 1] += v.y;
                        T[4 * j + 2] += v.z;
                        T[4 * j + 3] += v.w;
                    }
                }
                final_epi(T, b, a);
            }
        }
        wgmma_wait<0>();
        __syncwarp();
        if (lane == 0) mbar_arrive(smem_u32(&sm.redo_bar));
        mbar_wait(smem_u32(&sm.redo_bar), 0);
        rmask = *reinterpret_cast<volatile uint32_t*>(&sm.redo);
        rmask = (rmask | (rmask >> 16)) & 0xffffu;
#pragma unroll 1
        for (; rmask && (sched.item[blockIdx.x][__ffs(rmask) - 1] >> 12) == T_ATT; rmask &= rmask - 1) {
            gemm_chunk(S, false, true);
            gemm_rest(S, DM / 128);
            pack_p(S);
            first_block();
            float O[64], L[4] = {0.f, 0.f, 0.f, 0.f};
#pragma unroll
            for (int i = 0; i < 64; i++) O[i] = 0.f;
            float m0 = -INFINITY, m1 = -INFINITY;
#pragma unroll 1
            for (int j = 0; j < 16; j++) {
                float x0, x1;
                scores_max(P2, x0, x1);
                x0 = fmaxf(x0, m0);
                x1 = fmaxf(x1, m1);
                const float a0 = ex2((m0 - x0) * c), a1 = ex2((m1 - x1) * c);
                m0 = x0;
                m1 = x1;
                const float n0 = -m0 * c, n1 = -m1 * c;
#pragma unroll
                for (int i = 0; i < 16; i++) {
                    const float e0 = ex2(fmaf(bf16lo(P2[2 * i]), c, n0));
                    const float e1 = ex2(fmaf(bf16hi(P2[2 * i]), c, n0));
                    const float e2 = ex2(fmaf(bf16lo(P2[2 * i + 1]), c, n1));
                    const float e3 = ex2(fmaf(bf16hi(P2[2 * i + 1]), c, n1));
                    P[2 * i] = pack_bf16(e0, e1);
                    P[2 * i + 1] = pack_bf16(e2, e3);
                    O[4 * i] *= a0;
                    O[4 * i + 1] *= a0;
                    O[4 * i + 2] *= a1;
                    O[4 * i + 3] *= a1;
                }
                L[0] *= a0;
                L[1] *= a0;
                L[2] *= a1;
                L[3] *= a1;
                mbar_wait(fv0 + vstage * 8, vphase);
                issue_pv(O, L, P, vstage);
                wgmma_wait<0>();
                if (lane == 0) mbar_arrive(ev0 + vstage * 8);
                if (j < 15) {
                    mbar_wait(fk0 + stage * 8, phase);
                    issue_qk(dk0 + stage * (TILE_BYTES >> 4));
                    wgmma_wait<0>();
                    if (lane == 0) mbar_arrive(ek0 + stage * 8);
                    vstage = stage;
                    vphase = phase;
                    if (++stage == AT_STAGES) { stage = 0; phase ^= 1; }
                }
            }
            epilogue(O, L);
        }
#pragma unroll 1
        for (; rmask; rmask &= rmask - 1) {
            const int item = sched.item[blockIdx.x][__ffs(rmask) - 1];
            gemm_chunk(S, false, true);
            gemm_rest(S, NH);
            final_epi(S, item & 15, (item >> 4) & 0xff);
        }
    }
}

typedef CUresult (*EncodeFn)(CUtensorMap*, CUtensorMapDataType, cuuint32_t, void*, const cuuint64_t*, const cuuint64_t*,
                             const cuuint32_t*, const cuuint32_t*, CUtensorMapInterleave, CUtensorMapSwizzle,
                             CUtensorMapL2promotion, CUtensorMapFloatOOBfill);

static CUtensorMap make_map(EncodeFn fn, const void* ptr, uint64_t rows, uint64_t cols, uint32_t box_rows, uint32_t box_blk) {
    CUtensorMap m;
    cuuint64_t dims[3] = {64, rows, cols / 64};
    cuuint64_t strides[2] = {cols * 2, 128};
    cuuint32_t box[3] = {64, box_rows, box_blk};
    cuuint32_t es[3] = {1, 1, 1};
    fn(&m, CU_TENSOR_MAP_DATA_TYPE_BFLOAT16, 3, const_cast<void*>(ptr), dims, strides, box, es, CU_TENSOR_MAP_INTERLEAVE_NONE,
       CU_TENSOR_MAP_SWIZZLE_128B, CU_TENSOR_MAP_L2_PROMOTION_L2_256B, CU_TENSOR_MAP_FLOAT_OOB_FILL_NONE);
    return m;
}

extern "C" void kernel_launch(void* const* d_in, const int* in_sizes, int n_in, void* d_out, int out_size) {
    const bf16* x = (const bf16*)d_in[0];
    const bf16* kc = (const bf16*)d_in[1];
    const bf16* vc = (const bf16*)d_in[2];
    const bf16* wq = (const bf16*)d_in[3];
    const bf16* wo = (const bf16*)d_in[4];
    const bf16* w1 = (const bf16*)d_in[6];
    const bf16* w2 = (const bf16*)d_in[7];
    bf16* out = (bf16*)d_out;

    static EncodeFn fn = nullptr;
    static void *p_xn = nullptr, *p_h = nullptr, *p_o = nullptr;
    static Sched sched;
    if (!fn) {
        void* f = nullptr;
        cudaDriverEntryPointQueryResult st;
        cudaGetDriverEntryPoint("cuTensorMapEncodeTiled", &f, cudaEnableDefault, &st);
        fn = (EncodeFn)f;
        cudaGetSymbolAddress(&p_xn, g_xn);
        cudaGetSymbolAddress(&p_h, g_h);
        cudaGetSymbolAddress(&p_o, g_o);
        cudaFuncSetAttribute(attn_kernel, cudaFuncAttributeMaxDynamicSharedMemorySize, (int)sizeof(AttnSmem) + 1024);
        static const struct { int n, n1; const char* tail; } cls[] = {
            {20, 0, "E"}, {24, 0, "D"}, {24, 0, "G"}, {48, 4, "O"}, {8, 1, "GEO"}, {4, 1, "DEO"}, {4, 5, "DO"}};
        int t1 = 0, t2 = 0, t3[2] = {0, 0}, t4 = 0, i = 0;
        for (const auto& cl : cls) {
            for (int c = 0; c < cl.n; c++, i++) {
                int n = 0;
                for (int j = 0; j < cl.n1; j++, t1++) sched.item[i][n++] = (uint16_t)((T_F1 << 12) | ((t1 % 14) << 4) | (t1 / 14));
                for (int t = i; t < NH * 16; t += NUM_CTAS) sched.item[i][n++] = (uint16_t)((T_ATT << 12) | ((t >> 4) << 4) | (t & 15));
                sched.end_att[i] = sched.end_wide[i] = (uint8_t)n;
                for (const char* p = cl.tail; *p; p++) {
                    if (*p == 'G') { sched.item[i][n++] = (uint16_t)((T_F2 << 12) | ((t2 & 1) << 4) | (t2 >> 1)); t2++; }
                    if (*p == 'D' || *p == 'E') {
                        const int g = *p - 'D', t = t3[g]++;
                        sched.item[i][n++] = (uint16_t)((T_OPE << 12) | (((t & 1) | (g << 2)) << 4) | (t >> 1));
                    }
                    if (*p != 'O') sched.end_wide[i] = (uint8_t)n;
                    if (*p == 'O') { sched.item[i][n++] = (uint16_t)((T_OPF << 12) | ((t4 & 3) << 4) | (t4 >> 2)); t4++; }
                }
                sched.count[i] = (uint8_t)n;
            }
        }
    }
    CUtensorMap tm_xn_at = make_map(fn, p_xn, SEQ, DM, 128, 2);
    CUtensorMap tm_wq = make_map(fn, wq, DM, NH * DH, 128, 2);
    CUtensorMap tm_k = make_map(fn, kc, NH * SEQ, DH, 128, 2);
    CUtensorMap tm_v = make_map(fn, vc, NH * SEQ, DH, 128, 2);
    CUtensorMap tm_o_st = make_map(fn, p_o, SEQ, NH * DH, 64, 2);
    CUtensorMap tm_w1 = make_map(fn, w1, DM, FF, 128, 2);
    CUtensorMap tm_h_st = make_map(fn, p_h, SEQ, FF, 64, 2);
    CUtensorMap tm_h_ld = make_map(fn, p_h, SEQ, FF, 128, 1);
    CUtensorMap tm_w2 = make_map(fn, w2, FF, DM, 64, 4);
    CUtensorMap tm_o_g = make_map(fn, p_o, SEQ, NH * DH, 128, 2);
    CUtensorMap tm_wo = make_map(fn, wo, NH * DH, DM, 128, 2);
    CUtensorMap tm_o_gw = make_map(fn, p_o, SEQ, NH * DH, 128, 1);
    CUtensorMap tm_wow = make_map(fn, wo, NH * DH, DM, 64, 4);

    ln_kernel<<<SEQ / 8, 256>>>(x);
    cudaLaunchAttribute pdl[1];
    pdl[0].id = cudaLaunchAttributeProgrammaticStreamSerialization;
    pdl[0].val.programmaticStreamSerializationAllowed = 1;
    cudaLaunchConfig_t cfg = {};
    cfg.gridDim = dim3(NUM_CTAS);
    cfg.blockDim = dim3(384);
    cfg.dynamicSmemBytes = sizeof(AttnSmem) + 1024;
    cfg.stream = cudaStreamPerThread;
    cfg.attrs = pdl;
    cfg.numAttrs = 1;
    cudaLaunchKernelEx(&cfg, attn_kernel, tm_xn_at, tm_wq, tm_k, tm_v, tm_o_st, tm_w1, tm_h_st, tm_h_ld, tm_w2, tm_o_g,
                       tm_wo, tm_o_gw, tm_wow, x, out, sched);
}
```

```cpp
#include <cuda_runtime.h>
#include <cuda_bf16.h>
#include <cuda.h>
#include <stdint.h>

typedef __nv_bfloat16 bf16;
#define PP(x) x

constexpr int SEQ = 2048, DM = 512, NH = 32, DH = 128, FF = 1792;

__device__ __align__(1024) bf16 g_xn[SEQ * DM];
__device__ __align__(1024) bf16 g_h[SEQ * FF];
__device__ __align__(1024) bf16 g_o[SEQ * NH * DH];
__device__ uint4 g_g[64 * 8 * 256];
constexpr int C_H = 0, C_G = 16, C_P = C_G + 64, C_BAD = C_P + 64, C_RED = C_BAD + 16;
__device__ unsigned int g_cnt[256];
__device__ unsigned long long g_mask[16];
constexpr int OPE_N = 3, OPE_H = 11;
__device__ float4 g_part[OPE_N * 64 * 16 * 256];
__device__ volatile float g_dummy;

__device__ __forceinline__ uint32_t smem_u32(const void* p) { return (uint32_t)__cvta_generic_to_shared(p); }

__device__ __forceinline__ void mbar_init(uint32_t bar, uint32_t count) {
    asm volatile("mbarrier.init.shared::cta.b64 [%0], %1;" ::"r"(bar), "r"(count) : "memory");
}
__device__ __forceinline__ void mbar_expect_tx(uint32_t bar, uint32_t bytes) {
    asm volatile("mbarrier.arrive.expect_tx.shared::cta.b64 _, [%0], %1;" ::"r"(bar), "r"(bytes) : "memory");
}
__device__ __forceinline__ void mbar_arrive(uint32_t bar) {
    asm volatile("mbarrier.arrive.shared::cta.b64 _, [%0];" ::"r"(bar) : "memory");
}
__device__ __forceinline__ bool mbar_try_wait(uint32_t bar, uint32_t parity) {
    uint32_t ok;
    asm volatile(
        "{\n.reg .pred p;\n"
        "mbarrier.test_wait.parity.shared::cta.b64 p, [%1], %2;\n"
        "selp.u32 %0, 1, 0, p;\n}\n"
        : "=r"(ok)
        : "r"(bar), "r"(parity)
        : "memory");
    return ok != 0;
}
__device__ __forceinline__ void mbar_wait(uint32_t bar, uint32_t parity) {
    asm volatile(
        "{\n.reg .pred P1;\n.reg .u32 n;\nmov.u32 n, 0;\n"
        "LAB_WAIT:\n"
        "mbarrier.try_wait.parity.shared::cta.b64 P1, [%0], %1;\n"
        "@P1 bra DONE;\n"
        "add.u32 n, n, 1;\n"
        "setp.lt.u32 P1, n, 4194304;\n"
        "@P1 bra LAB_WAIT;\n"
        "trap;\n"
        "DONE:\n}\n" ::"r"(bar), "r"(parity)
        : "memory");
}
__device__ __forceinline__ void tma_load_3d(uint32_t dst, const CUtensorMap* map, uint32_t bar, int c0, int c1, int c2) {
    asm volatile(
        "cp.async.bulk.tensor.3d.shared::cluster.global.mbarrier::complete_tx::bytes [%0], [%1, {%3, %4, %5}], [%2];"
        ::"r"(dst), "l"((uint64_t)map), "r"(bar), "r"(c0), "r"(c1), "r"(c2)
        : "memory");
}
__device__ __forceinline__ void tma_store_3d(const CUtensorMap* map, uint32_t src, int c0, int c1, int c2) {
    asm volatile("cp.async.bulk.tensor.3d.global.shared::cta.bulk_group [%0, {%2, %3, %4}], [%1];"
                 ::"l"((uint64_t)map), "r"(src), "r"(c0), "r"(c1), "r"(c2)
                 : "memory");
}
__device__ __forceinline__ void tma_commit() { asm volatile("cp.async.bulk.commit_group;" ::: "memory"); }
__device__ __forceinline__ void tma_wait_read0() { asm volatile("cp.async.bulk.wait_group.read 0;" ::: "memory"); }
__device__ __forceinline__ void tma_wait_all0() { asm volatile("cp.async.bulk.wait_group 0;" ::: "memory"); }
__device__ __forceinline__ void fence_proxy_async() { asm volatile("fence.proxy.async.shared::cta;" ::: "memory"); }
__device__ __forceinline__ void prefetch_tmap(const CUtensorMap* map) {
    asm volatile("prefetch.tensormap [%0];" ::"l"((uint64_t)map) : "memory");
}
__device__ __forceinline__ void pdl_wait() { asm volatile("griddepcontrol.wait;" ::: "memory"); }
__device__ __forceinline__ void pdl_launch() { asm volatile("griddepcontrol.launch_dependents;" ::: "memory"); }
__device__ __forceinline__ void named_sync(int id, int n) { asm volatile("bar.sync %0, %1;" ::"r"(id), "r"(n) : "memory"); }
__device__ __forceinline__ void named_arrive(int id, int n) { asm volatile("bar.arrive %0, %1;" ::"r"(id), "r"(n) : "memory"); }

__device__ __forceinline__ void wgmma_fence() { asm volatile("wgmma.fence.sync.aligned;" ::: "memory"); }
__device__ __forceinline__ void wgmma_commit() { asm volatile("wgmma.commit_group.sync.aligned;" ::: "memory"); }
template <int N>
__device__ __forceinline__ void wgmma_wait() { asm volatile("wgmma.wait_group.sync.aligned %0;" ::"n"(N) : "memory"); }

__device__ __forceinline__ void fence_acc(float (&d)[64]) {
#pragma unroll
    for (int i = 0; i < 64; i++) asm volatile("" : "+f"(d[i])::"memory");
}

template <int R>
__device__ __forceinline__ void reg_alloc() { asm volatile("setmaxnreg.inc.sync.aligned.u32 %0;" ::"n"(R)); }
template <int R>
__device__ __forceinline__ void reg_dealloc() { asm volatile("setmaxnreg.dec.sync.aligned.u32 %0;" ::"n"(R)); }

__device__ __forceinline__ uint64_t make_desc(uint32_t saddr, uint32_t lbo_bytes, uint32_t sbo_bytes) {
    uint64_t d = 0;
    d |= (uint64_t)((saddr & 0x3FFFF) >> 4);
    d |= (uint64_t)((lbo_bytes >> 4) & 0x3FFF) << 16;
    d |= (uint64_t)((sbo_bytes >> 4) & 0x3FFF) << 32;
    d |= (uint64_t)1 << 62;
    return d;
}

__device__ __forceinline__ float ex2(float x) {
    float y;
    asm volatile("ex2.approx.ftz.f32 %0, %1;" : "=f"(y) : "f"(x));
    return y;
}
__device__ __forceinline__ uint32_t pack_bf16(float lo, float hi) {
    uint32_t r;
    asm("cvt.rn.bf16x2.f32 %0, %1, %2;" : "=r"(r) : "f"(hi), "f"(lo));
    return r;
}
__device__ __forceinline__ uint32_t mul_bf16x2(uint32_t a, uint32_t b) {
    uint32_t r;
    asm("mul.rn.bf16x2 %0, %1, %2;" : "=r"(r) : "r"(a), "r"(b));
    return r;
}
__device__ __forceinline__ uint32_t add_bf16x2(uint32_t a, uint32_t b) {
    uint32_t r;
    asm("add.rn.bf16x2 %0, %1, %2;" : "=r"(r) : "r"(a), "r"(b));
    return r;
}
__device__ __forceinline__ unsigned int ld_acq(const unsigned int* p) {
    unsigned int v;
    asm volatile("ld.acquire.gpu.global.u32 %0, [%1];" : "=r"(v) : "l"(p) : "memory");
    return v;
}
__device__ __forceinline__ unsigned long long ld_acq64(const unsigned long long* p) {
    unsigned long long v;
    asm volatile("ld.acquire.gpu.global.u64 %0, [%1];" : "=l"(v) : "l"(p) : "memory");
    return v;
}
__device__ __forceinline__ uint32_t fma_bf16x2(uint32_t a, uint32_t b, uint32_t c) {
    uint32_t r;
    asm("fma.rn.bf16x2 %0, %1, %2, %3;" : "=r"(r) : "r"(a), "r"(b), "r"(c));
    return r;
}
__device__ __forceinline__ uint32_t max_bf16x2(uint32_t a, uint32_t b) {
    uint32_t r;
    asm("max.bf16x2 %0, %1, %2;" : "=r"(r) : "r"(a), "r"(b));
    return r;
}
__device__ __forceinline__ float bf16lo(uint32_t v) { return __uint_as_float(v << 16); }
__device__ __forceinline__ float bf16hi(uint32_t v) { return __uint_as_float(v & 0xffff0000u); }
__device__ __forceinline__ float bf16_round(float x) { return __bfloat162float(__float2bfloat16_rn(x)); }
__device__ __forceinline__ float silu_f(float x) {
    const float h = 0.5f * x;
    float t;
    asm("tanh.approx.f32 %0, %1;" : "=f"(t) : "f"(h));
    return fmaf(h, t, h);
}

__device__ __forceinline__ void stmatrix_x4(uint32_t addr, uint32_t r0, uint32_t r1, uint32_t r2, uint32_t r3) {
    asm volatile("stmatrix.sync.aligned.m8n8.x4.shared.b16 [%0], {%1, %2, %3, %4};"
                 ::"r"(addr), "r"(r0), "r"(r1), "r"(r2), "r"(r3)
                 : "memory");
}

#define ACC64(d) \
    "+f"(d[0]), "+f"(d[1]), "+f"(d[2]), "+f"(d[3]), "+f"(d[4]), "+f"(d[5]), "+f"(d[6]), "+f"(d[7]), \
    "+f"(d[8]), "+f"(d[9]), "+f"(d[10]), "+f"(d[11]), "+f"(d[12]), "+f"(d[13]), "+f"(d[14]), "+f"(d[15]), \
    "+f"(d[16]), "+f"(d[17]), "+f"(d[18]), "+f"(d[19]), "+f"(d[20]), "+f"(d[21]), "+f"(d[22]), "+f"(d[23]), \
    "+f"(d[24]), "+f"(d[25]), "+f"(d[26]), "+f"(d[27]), "+f"(d[28]), "+f"(d[29]), "+f"(d[30]), "+f"(d[31]), \
    "+f"(d[32]), "+f"(d[33]), "+f"(d[34]), "+f"(d[35]), "+f"(d[36]), "+f"(d[37]), "+f"(d[38]), "+f"(d[39]), \
    "+f"(d[40]), "+f"(d[41]), "+f"(d[42]), "+f"(d[43]), "+f"(d[44]), "+f"(d[45]), "+f"(d[46]), "+f"(d[47]), \
    "+f"(d[48]), "+f"(d[49]), "+f"(d[50]), "+f"(d[51]), "+f"(d[52]), "+f"(d[53]), "+f"(d[54]), "+f"(d[55]), \
    "+f"(d[56]), "+f"(d[57]), "+f"(d[58]), "+f"(d[59]), "+f"(d[60]), "+f"(d[61]), "+f"(d[62]), "+f"(d[63])

#define ACC64_STR \
    "{%0, %1, %2, %3, %4, %5, %6, %7, %8, %9, %10, %11, %12, %13, %14, %15, " \
    "%16, %17, %18, %19, %20, %21, %22, %23, %24, %25, %26, %27, %28, %29, %30, %31, " \
    "%32, %33, %34, %35, %36, %37, %38, %39, %40, %41, %42, %43, %44, %45, %46, %47, " \
    "%48, %49, %50, %51, %52, %53, %54, %55, %56, %57, %58, %59, %60, %61, %62, %63}"

template <int TB>
__device__ __forceinline__ void wgmma_ss_n128(float (&d)[64], uint64_t da, uint64_t db, int scale_d) {
    asm volatile(
        "{\n.reg .pred p;\nsetp.ne.b32 p, %66, 0;\n"
        "wgmma.mma_async.sync.aligned.m64n128k16.f32.bf16.bf16 " ACC64_STR ", %64, %65, p, 1, 1, 0, %67;\n}\n"
        : ACC64(d)
        : "l"(da), "l"(db), "r"(scale_d), "n"(TB));
}
template <int TB>
__device__ __forceinline__ void wgmma_rs_n128(float (&d)[64], uint32_t a0, uint32_t a1, uint32_t a2, uint32_t a3,
                                              uint64_t db, int scale_d) {
    asm volatile(
        "{\n.reg .pred p;\nsetp.ne.b32 p, %69, 0;\n"
        "wgmma.mma_async.sync.aligned.m64n128k16.f32.bf16.bf16 " ACC64_STR ", {%64, %65, %66, %67}, %68, p, 1, 1, %70;\n}\n"
        : ACC64(d)
        : "r"(a0), "r"(a1), "r"(a2), "r"(a3), "l"(db), "r"(scale_d), "n"(TB));
}

constexpr uint32_t DESC_HI = 0x40000040u;
__device__ __forceinline__ uint32_t desc_lo(uint32_t saddr, uint32_t lbo_bytes) {
    return ((saddr & 0x3FFFF) >> 4) | ((lbo_bytes >> 4) << 16);
}
template <int TB>
__device__ __forceinline__ void wgmma_ss_lo(float (&d)[64], uint32_t da, uint32_t db, int scale_d) {
    asm volatile(
        "{\n.reg .pred p;\n.reg .b64 xa, xb;\nsetp.ne.b32 p, %66, 0;\n"
        "mov.b64 xa, {%64, %68};\nmov.b64 xb, {%65, %68};\n"
        "wgmma.mma_async.sync.aligned.m64n128k16.f32.bf16.bf16 " ACC64_STR ", xa, xb, p, 1, 1, 0, %67;\n}\n"
        : ACC64(d)
        : "r"(da), "r"(db), "r"(scale_d), "n"(TB), "r"(DESC_HI));
}
__device__ __forceinline__ void wgmma_rs_lo_tb(float (&d)[64], uint32_t a0, uint32_t a1, uint32_t a2, uint32_t a3, uint32_t db) {
    asm volatile(
        "{\n.reg .b64 xb;\nmov.b64 xb, {%68, %69};\n"
        "wgmma.mma_async.sync.aligned.m64n128k16.f32.bf16.bf16 " ACC64_STR ", {%64, %65, %66, %67}, xb, 1, 1, 1, 1;\n}\n"
        : ACC64(d)
        : "r"(a0), "r"(a1), "r"(a2), "r"(a3), "r"(db), "r"(DESC_HI));
}

#define ACC8(d, o) "+f"(d[o]), "+f"(d[o + 1]), "+f"(d[o + 2]), "+f"(d[o + 3]), "+f"(d[o + 4]), "+f"(d[o + 5]), "+f"(d[o + 6]), "+f"(d[o + 7])
__device__ __forceinline__ void wgmma_rs_n64(float (&d)[64], uint32_t a0, uint32_t a1, uint32_t a2, uint32_t a3, uint32_t db) {
    asm volatile(
        "{\n.reg .b64 xb;\nmov.b64 xb, {%36, %37};\n"
        "wgmma.mma_async.sync.aligned.m64n64k16.f32.bf16.bf16 "
        "{%0, %1, %2, %3, %4, %5, %6, %7, %8, %9, %10, %11, %12, %13, %14, %15, "
        "%16, %17, %18, %19, %20, %21, %22, %23, %24, %25, %26, %27, %28, %29, %30, %31}, "
        "{%32, %33, %34, %35}, xb, 1, 1, 1, 1;\n}\n"
        : ACC8(d, 0), ACC8(d, 8), ACC8(d, 16), ACC8(d, 24)
        : "r"(a0), "r"(a1), "r"(a2), "r"(a3), "r"(db), "r"(DESC_HI));
}
__device__ __forceinline__ void wgmma_rs_n72(float (&d)[64], float (&l)[4], uint32_t a0, uint32_t a1, uint32_t a2, uint32_t a3, uint32_t db) {
    asm volatile(
        "{\n.reg .b64 xb;\nmov.b64 xb, {%40, %41};\n"
        "wgmma.mma_async.sync.aligned.m64n72k16.f32.bf16.bf16 "
        "{%0, %1, %2, %3, %4, %5, %6, %7, %8, %9, %10, %11, %12, %13, %14, %15, "
        "%16, %17, %18, %19, %20, %21, %22, %23, %24, %25, %26, %27, %28, %29, %30, %31, %32, %33, %34, %35}, "
        "{%36, %37, %38, %39}, xb, 1, 1, 1, 1;\n}\n"
        : ACC8(d, 32), ACC8(d, 40), ACC8(d, 48), ACC8(d, 56), "+f"(l[0]), "+f"(l[1]), "+f"(l[2]), "+f"(l[3])
        : "r"(a0), "r"(a1), "r"(a2), "r"(a3), "r"(db), "r"(DESC_HI));
}

__device__ __forceinline__ void wgmma_ss_n256_tb(float (&d)[128], uint64_t da, uint64_t db, int scale_d) {
    asm volatile(
        "{\n.reg .pred p;\nsetp.ne.b32 p, %130, 0;\n"
        "wgmma.mma_async.sync.aligned.m64n256k16.f32.bf16.bf16 "
        "{%0, %1, %2, %3, %4, %5, %6, %7, %8, %9, %10, %11, %12, %13, %14, %15, "
        "%16, %17, %18, %19, %20, %21, %22, %23, %24, %25, %26, %27, %28, %29, %30, %31, "
        "%32, %33, %34, %35, %36, %37, %38, %39, %40, %41, %42, %43, %44, %45, %46, %47, "
        "%48, %49, %50, %51, %52, %53, %54, %55, %56, %57, %58, %59, %60, %61, %62, %63, "
        "%64, %65, %66, %67, %68, %69, %70, %71, %72, %73, %74, %75, %76, %77, %78, %79, "
        "%80, %81, %82, %83, %84, %85, %86, %87, %88, %89, %90, %91, %92, %93, %94, %95, "
        "%96, %97, %98, %99, %100, %101, %102, %103, %104, %105, %106, %107, %108, %109, %110, %111, "
        "%112, %113, %114, %115, %116, %117, %118, %119, %120, %121, %122, %123, %124, %125, %126, %127}, "
        "%128, %129, p, 1, 1, 0, 1;\n}\n"
        : ACC8(d, 0), ACC8(d, 8), ACC8(d, 16), ACC8(d, 24), ACC8(d, 32), ACC8(d, 40), ACC8(d, 48), ACC8(d, 56),
          ACC8(d, 64), ACC8(d, 72), ACC8(d, 80), ACC8(d, 88), ACC8(d, 96), ACC8(d, 104), ACC8(d, 112), ACC8(d, 120)
        : "l"(da), "l"(db), "r"(scale_d));
}

__global__ void __launch_bounds__(256) ln_kernel(const bf16* __restrict__ x) {
    pdl_launch();
    int warp = threadIdx.x >> 5, lane = threadIdx.x & 31;
    int row = blockIdx.x * 8 + warp;
    if (blockIdx.x == 0) g_cnt[threadIdx.x] = 0;
    if (blockIdx.x == 1 && threadIdx.x < 16) g_mask[threadIdx.x] = 0;
    const uint4* src = reinterpret_cast<const uint4*>(x + (size_t)row * DM);
    uint4 v[2];
    v[0] = src[lane];
    v[1] = src[lane + 32];
    float f[16];
#pragma unroll
    for (int i = 0; i < 2; i++) {
        const __nv_bfloat162* p = reinterpret_cast<const __nv_bfloat162*>(&v[i]);
#pragma unroll
        for (int j = 0; j < 4; j++) {
            float2 t = __bfloat1622float2(p[j]);
            f[i * 8 + j * 2] = t.x;
            f[i * 8 + j * 2 + 1] = t.y;
        }
    }
    float s = 0.f;
#pragma unroll
    for (int i = 0; i < 16; i++) s += f[i];
#pragma unroll
    for (int o = 16; o > 0; o >>= 1) s += __shfl_xor_sync(0xffffffffu, s, o);
    float mean = s * (1.0f / DM);
    float q = 0.f;
#pragma unroll
    for (int i = 0; i < 16; i++) {
        float d = f[i] - mean;
        q += d * d;
    }
#pragma unroll
    for (int o = 16; o > 0; o >>= 1) q += __shfl_xor_sync(0xffffffffu, q, o);
    float var_b = bf16_round(q * (1.0f / DM));
    float mean_b = bf16_round(mean);
    float den = bf16_round(sqrtf(bf16_round(var_b + 1e-5f)));
    uint4 o[2];
#pragma unroll
    for (int i = 0; i < 2; i++) {
        uint32_t* p = reinterpret_cast<uint32_t*>(&o[i]);
#pragma unroll
        for (int j = 0; j < 4; j++) {
            float a = bf16_round(f[i * 8 + j * 2] - mean_b) / den;
            float b = bf16_round(f[i * 8 + j * 2 + 1] - mean_b) / den;
            p[j] = pack_bf16(a, b);
        }
    }
    uint4* dst = reinterpret_cast<uint4*>(g_xn + (size_t)row * DM);
    dst[lane] = o[0];
    dst[lane + 32] = o[1];
}

constexpr int AT_STAGES = 3;
constexpr int TILE_BYTES = 128 * 128 * 2;
struct __align__(1024) AttnSmem {
    uint8_t k[AT_STAGES][TILE_BYTES];
    uint8_t v[AT_STAGES][TILE_BYTES];
    uint8_t o[TILE_BYTES];
    uint32_t ones0[4];
    uint64_t full_k[AT_STAGES], full_v[AT_STAGES], empty_k[AT_STAGES], empty_v[AT_STAGES];
    uint64_t st_free[2];
    uint64_t redo_bar;
    uint32_t redo;
    uint32_t pad0;
    uint32_t ones1[4];
    uint64_t fin_bar[4];
    uint32_t pad1[24];
    uint32_t ones2[(2048 - 288) / 4];
};

#define EXPO(x) x
#define N8(x) x
#define PPK 8
#define FAST_BIAS (-40.0f)
constexpr int NUM_CTAS = 132;
constexpr int MAX_ITEMS = 12;
enum { T_ATT = 0, T_F1 = 1, T_F2 = 2, T_OPE = 3, T_OPF = 4 };
struct Sched {
    uint16_t item[NUM_CTAS][MAX_ITEMS];
    uint8_t count[NUM_CTAS], end_att[NUM_CTAS], end_wide[NUM_CTAS];
};

__global__ void __launch_bounds__(384, 1)
attn_kernel(const __grid_constant__ CUtensorMap tm_xn, const __grid_constant__ CUtensorMap tm_wq,
            const __grid_constant__ CUtensorMap tm_k, const __grid_constant__ CUtensorMap tm_v,
            const __grid_constant__ CUtensorMap tm_o, const __grid_constant__ CUtensorMap tm_w1,
            const __grid_constant__ CUtensorMap tm_hst, const __grid_constant__ CUtensorMap tm_hld,
            const __grid_constant__ CUtensorMap tm_w2,
            const __grid_constant__ CUtensorMap tm_old, const __grid_constant__ CUtensorMap tm_wo,
            const __grid_constant__ CUtensorMap tm_oldw, const __grid_constant__ CUtensorMap tm_wow,
            const bf16* __restrict__ x, bf16* __restrict__ out, const __grid_constant__ Sched sched) {
    extern __shared__ uint8_t smem_raw[];
    AttnSmem& sm = *reinterpret_cast<AttnSmem*>((reinterpret_cast<uintptr_t>(smem_raw) + 1023) & ~uintptr_t(1023));
    const int tid = threadIdx.x;
    const int wg = __shfl_sync(0xffffffffu, tid >> 7, 0);
    const int n_items = sched.count[blockIdx.x];
    if (tid == 32) {
        prefetch_tmap(&tm_xn); prefetch_tmap(&tm_wq); prefetch_tmap(&tm_k); prefetch_tmap(&tm_v); prefetch_tmap(&tm_o);
        prefetch_tmap(&tm_w1); prefetch_tmap(&tm_hst); prefetch_tmap(&tm_hld); prefetch_tmap(&tm_w2);
        prefetch_tmap(&tm_old); prefetch_tmap(&tm_wo); prefetch_tmap(&tm_oldw); prefetch_tmap(&tm_wow);
    }

    if (tid == 0) {
#pragma unroll
        for (int s = 0; s < AT_STAGES; s++) {
            mbar_init(smem_u32(&sm.full_k[s]), 1);
            mbar_init(smem_u32(&sm.full_v[s]), 1);
            mbar_init(smem_u32(&sm.empty_k[s]), 8);
            mbar_init(smem_u32(&sm.empty_v[s]), 8);
        }
        mbar_init(smem_u32(&sm.st_free[0]), 1);
        mbar_init(smem_u32(&sm.st_free[1]), 1);
        mbar_init(smem_u32(&sm.redo_bar), 8);
#pragma unroll
        for (int s = 0; s < 4; s++) mbar_init(smem_u32(&sm.fin_bar[s]), 1);
        sm.redo = 0;
        asm volatile("fence.mbarrier_init.release.cluster;" ::: "memory");
    }
    if (tid < 64) {
        const int r = tid >> 2;
        sm.ones0[(r >> 3) * 256 + (r & 7) * 36 + (tid & 3)] = 0x3F803F80u;
        fence_proxy_async();
    }
    __syncthreads();
    pdl_wait();
    int it = 0;
    uint32_t rmask = 0;
    bool redo = false;
    auto next_item = [&]() -> bool {
        if (!redo) {
            if (++it < n_items) return true;
            mbar_wait(smem_u32(&sm.redo_bar), 0);
            rmask = *reinterpret_cast<volatile uint32_t*>(&sm.redo);
            rmask = (rmask | (rmask >> 16)) & 0xffffu;
            redo = true;
        }
        if (!rmask) return false;
        it = __ffs(rmask) - 1;
        rmask &= rmask - 1;
        return true;
    };
    constexpr int BAR_SCHED0 = 1, BAR_EPI0 = 3, BAR_ST0 = 5;

    if (wg == 0) {
        reg_dealloc<40>();
        if (tid >= 32 && tid < 96) {
            const int cw = (tid >> 5) - 1;
            const uint32_t obase = smem_u32(sm.o) + cw * 16384;
            do {
                const int item = sched.item[blockIdx.x][it];
                const int type = item >> 12, a = (item >> 4) & 0xff, b = item & 15;
                if (type == T_OPF) continue;
                named_sync(BAR_ST0 + cw, 160);
                if ((tid & 31) == 0) {
                    if (type >= T_F2) {
                        __threadfence();
                        atomicAdd(&g_cnt[(type == T_F2 ? C_G : C_P) + b * 2 + (a & 1)], 1u);
                    } else {
                        if (redo) tma_wait_all0();
                        tma_store_3d(type == T_ATT ? &tm_o : &tm_hst, obase, 0, b * 128 + cw * 64, a * 2);
                        tma_commit();
                        tma_wait_read0();
                        mbar_arrive(smem_u32(&sm.st_free[cw]));
                        const bool bad = (*reinterpret_cast<volatile uint32_t*>(&sm.redo) >> (16 * cw + it)) & 1;
                        if (bad && !redo) atomicAdd(&g_cnt[C_BAD + b], 1u);
                        tma_wait_all0();
                        asm volatile("fence.proxy.async;" ::: "memory");
                        __threadfence();
                        if (type != T_ATT) atomicAdd(&g_cnt[C_H + b], 1u);
                        else if (!redo) atomicOr(&g_mask[b], 1ull << (2 * a + cw));
                        else if (bad) atomicAdd(&g_cnt[C_RED + b], 1u);
                    }
                }
                __syncwarp();
            } while (next_item());
            if ((tid & 31) == 0) tma_wait_all0();
        }
        if (tid == 96) {
            int ord = 0;
            for (int i = 0; i < n_items; i++) {
                const int item = sched.item[blockIdx.x][i];
                const int a = (item >> 4) & 0xff, b = item & 15;
                if ((item >> 12) != T_OPF) continue;
                unsigned int spins = 0;
                while (ld_acq64(&g_mask[b]) != ~0ull && ++spins < (1u << 24)) {}
                while (ld_acq(&g_cnt[C_G + b * 2 + (a >> 2)]) < 2 && ++spins < (1u << 24)) {}
                while (ld_acq(&g_cnt[C_P + b * 2 + (a >> 2)]) < 2 * OPE_N && ++spins < (1u << 24)) {}
                if (ld_acq(&g_cnt[C_BAD + b])) atomicOr(&sm.redo, 1u << i);
                mbar_arrive(smem_u32(&sm.fin_bar[ord++]));
            }
        }
        if (tid == 0) {
            int stage = 0;
            uint32_t phase = 0;
            do {
                const int item = sched.item[blockIdx.x][it];
                const int type = item >> 12, a = (item >> 4) & 0xff, b = item & 15;
                const CUtensorMap* ta = type < T_F2 ? &tm_xn : (type == T_F2 ? &tm_hld : (type == T_OPE ? &tm_oldw : &tm_old));
                const CUtensorMap* tb = type < T_F2 ? (type == T_ATT ? &tm_wq : &tm_w1) : (type == T_F2 ? &tm_w2 : (type == T_OPE ? &tm_wow : &tm_wo));
                const bool wide = type == T_F2 || type == T_OPE;
                int nch = DM / 128, kc0 = 0, nb = a;
                unsigned long long need = 0, mask = 0;
                unsigned int spins = 0;
                if (type == T_F2) {
                    nch = FF / 128;
                    nb = a * 2;
                    while (ld_acq(&g_cnt[C_H + b]) < 2 * (FF / 128) && ++spins < (1u << 24)) {}
                    asm volatile("fence.proxy.async;" ::: "memory");
                } else if (type == T_OPE) {
                    kc0 = (a >> 2) * OPE_H;
                    nch = min(OPE_H, NH - kc0);
                    nb = (a & 1) * 2;
                    need = 3ull << (2 * kc0);
                } else if (type == T_OPF) {
                    if (!redo) {
                        nch = 0;
                    } else {
                        nch = NH;
                        nb = a >> 1;
                        const unsigned int nbad = ld_acq(&g_cnt[C_BAD + b]);
                        while (ld_acq(&g_cnt[C_RED + b]) < nbad && ++spins < (1u << 24)) {}
                        asm volatile("fence.proxy.async;" ::: "memory");
                    }
                }
                for (int kc = kc0; kc < kc0 + nch; kc++) {
                    if ((mask & need) != need) {
                        do mask = ld_acq64(&g_mask[b]); while ((mask & need) != need && ++spins < (1u << 24));
                        asm volatile("fence.proxy.async;" ::: "memory");
                    }
                    need <<= 2;
                    for (int hk = 0; hk <= (int)wide; hk++) {
                        mbar_wait(smem_u32(&sm.empty_k[stage]), phase ^ 1);
                        mbar_expect_tx(smem_u32(&sm.full_k[stage]), wide ? TILE_BYTES / 2 : TILE_BYTES);
                        tma_load_3d(smem_u32(sm.k[stage]), ta, smem_u32(&sm.full_k[stage]), 0, b * 128, kc * 2 + hk);
                        mbar_wait(smem_u32(&sm.empty_v[stage]), phase ^ 1);
                        mbar_expect_tx(smem_u32(&sm.full_v[stage]), TILE_BYTES);
                        tma_load_3d(smem_u32(sm.v[stage]), tb, smem_u32(&sm.full_v[stage]), 0, kc * 128 + hk * 64, nb * 2);
                        if (++stage == AT_STAGES) { stage = 0; phase ^= 1; }
                    }
                }
                if (type == T_ATT) {
                    for (int j = 0; j < 16; j++) {
                        mbar_wait(smem_u32(&sm.empty_k[stage]), phase ^ 1);
                        mbar_expect_tx(smem_u32(&sm.full_k[stage]), TILE_BYTES);
                        tma_load_3d(smem_u32(sm.k[stage]), &tm_k, smem_u32(&sm.full_k[stage]), 0, a * SEQ + j * 128, 0);
                        mbar_wait(smem_u32(&sm.empty_v[stage]), phase ^ 1);
                        mbar_expect_tx(smem_u32(&sm.full_v[stage]), TILE_BYTES);
                        tma_load_3d(smem_u32(sm.v[stage]), &tm_v, smem_u32(&sm.full_v[stage]), 0, a * SEQ + j * 128, 0);
                        if (++stage == AT_STAGES) { stage = 0; phase ^= 1; }
                    }
                }
            } while (next_item());
        }
    } else {
        reg_alloc<232>();
        const int cw = wg - 1;
        const int lane = tid & 31;
        const int warp_in_wg = (tid >> 5) & 3;
        const float c = 1.4426950408889634f;
        const uint32_t SCALE_HI2 = 0x3DB53DB5u, SCALE_LO2 = 0x371E371Eu;
        const uint32_t obase = smem_u32(sm.o) + cw * 16384;
        const int st_row = warp_in_wg * 16 + ((lane >> 3) & 1) * 8 + (lane & 7);

        const uint32_t dq = __shfl_sync(0xffffffffu, desc_lo(obase, 16), 0);
        const uint32_t dk0 = __shfl_sync(0xffffffffu, desc_lo(smem_u32(sm.k[0]), 16), 0);
        const uint32_t dv0 = dk0 - (1u << 16) + (1024u << 16) + AT_STAGES * (TILE_BYTES >> 4);

        PP(if (cw == 1) named_arrive(BAR_SCHED0 + 0, 256));

        int stage = 0;
        uint32_t phase = 0;
        float S[64];
        uint32_t P[32], P2[32];
        uint32_t cnt = 0;
        const uint32_t dw0 = __shfl_sync(0xffffffffu, desc_lo(smem_u32(sm.v[0]) + 16384, smem_u32(sm.ones0) - smem_u32(sm.v[0]) - 16384), 0);
        constexpr uint32_t DW_K = 128u - (128u << 16), DW_ST = 2048u - (2048u << 16);

        const uint32_t fk0 = smem_u32(&sm.full_k[0]), fv0 = smem_u32(&sm.full_v[0]);
        const uint32_t ek0 = smem_u32(&sm.empty_k[0]), ev0 = smem_u32(&sm.empty_v[0]);
        int vstage = 0;
        uint32_t vphase = 0;
        bool okk = false, okv = false;

        auto gemm_chunk = [&](float (&S)[64], bool acc, bool real) {
            if (real) {
                mbar_wait(fk0 + stage * 8, phase);
                mbar_wait(fv0 + stage * 8, phase);
            }
            const uint64_t da = make_desc(smem_u32(sm.k[stage]) + cw * 64 * 128, 16, 1024);
            const uint64_t db = make_desc(smem_u32(sm.v[stage]), 16384, 1024);
            wgmma_fence();
#pragma unroll
            for (int kk = 0; kk < 8; kk++) {
                wgmma_ss_n128<1>(S, da + (uint64_t)(((kk >> 2) * 16384 + (kk & 3) * 32) >> 4),
                                 db + (uint64_t)((kk * 2048) >> 4), acc || kk != 0);
            }
            wgmma_commit();
        };
        auto gemm_rest = [&](float (&S)[64], int nch) {
            int prev = stage;
            if (++stage == AT_STAGES) { stage = 0; phase ^= 1; }
#pragma unroll 1
            for (int kc = 1; kc < nch; kc++) {
                gemm_chunk(S, true, true);
                wgmma_wait<1>();
                if (lane == 0) {
                    mbar_arrive(ek0 + prev * 8);
                    mbar_arrive(ev0 + prev * 8);
                }
                prev = stage;
                if (++stage == AT_STAGES) { stage = 0; phase ^= 1; }
            }
            wgmma_wait<0>();
            if (lane == 0) {
                mbar_arrive(ek0 + prev * 8);
                mbar_arrive(ev0 + prev * 8);
            }
        };
        auto pack_p = [&](float (&S)[64]) {
#pragma unroll
            for (int i = 0; i < 32; i++) P[i] = pack_bf16(S[2 * i], S[2 * i + 1]);
        };
        auto final_epi = [&](float (&T)[32], uint4 (&xv)[4], int mb, int a) {
            uint4 gv[4];
#pragma unroll
            for (int i = 0; i < 4; i++) gv[i] = __ldcg(g_g + ((mb * 8 + a) * 4 + i) * 256 + (tid - 128));
            mbar_wait(smem_u32(&sm.st_free[cw]), (cnt & 1) ^ 1);
#pragma unroll
            for (int i = 0; i < 8; i += 2) {
                const uint32_t addr = obase + st_row * 128 + (((i + (lane >> 4)) ^ (st_row & 7)) << 4);
                stmatrix_x4(addr, mul_bf16x2(pack_bf16(T[4 * i], T[4 * i + 1]), gv[i >> 1].x), mul_bf16x2(pack_bf16(T[4 * i + 2], T[4 * i + 3]), gv[i >> 1].y),
                            mul_bf16x2(pack_bf16(T[4 * i + 4], T[4 * i + 5]), gv[i >> 1].z), mul_bf16x2(pack_bf16(T[4 * i + 6], T[4 * i + 7]), gv[i >> 1].w));
            }
            named_sync(BAR_EPI0 + cw, 128);
            const int ch = tid & 7, row0 = (tid & 127) >> 3;
            const uint32_t sa = obase + row0 * 128 + ((ch ^ (row0 & 7)) << 4);
            bf16* op = out + (size_t)(mb * 128 + cw * 64 + row0) * DM + a * 64 + ch * 8;
#pragma unroll
            for (int i = 0; i < 4; i++) {
                uint4 sv;
                asm volatile("ld.shared.v4.u32 {%0, %1, %2, %3}, [%4];" : "=r"(sv.x), "=r"(sv.y), "=r"(sv.z), "=r"(sv.w) : "r"(sa + i * 2048));
                sv.x = add_bf16x2(xv[i].x, sv.x);
                sv.y = add_bf16x2(xv[i].y, sv.y);
                sv.z = add_bf16x2(xv[i].z, sv.z);
                sv.w = add_bf16x2(xv[i].w, sv.w);
                *reinterpret_cast<uint4*>(op + (size_t)i * 16 * DM) = sv;
            }
            named_sync(BAR_EPI0 + cw, 128);
        };
        auto load_x = [&](uint4 (&xv)[4], int mb, int a) {
            const bf16* xp = x + (size_t)(mb * 128 + cw * 64 + ((tid & 127) >> 3)) * DM + a * 64 + (tid & 7) * 8;
#pragma unroll
            for (int i = 0; i < 4; i++) xv[i] = *reinterpret_cast<const uint4*>(xp + (size_t)i * 16 * DM);
        };
        auto stage_p = [&](uint32_t (&P)[32]) {
            mbar_wait(smem_u32(&sm.st_free[cw]), (cnt & 1) ^ 1);
            cnt++;
#pragma unroll
            for (int i = 0; i < 16; i += 2) {
                const int cc = i + (lane >> 4);
                const uint32_t addr = obase + (cc >> 3) * 8192 + st_row * 128 + (((cc & 7) ^ (st_row & 7)) << 4);
                stmatrix_x4(addr, P[2 * i], P[2 * i + 1], P[2 * i + 2], P[2 * i + 3]);
            }
            fence_proxy_async();
        };
        auto issue_qk = [&](uint32_t dk) {
            wgmma_fence();
#pragma unroll
            for (int kk = 0; kk < 8; kk++)
                wgmma_ss_lo<0>(S, dq + (((kk >> 2) * 8192 + (kk & 3) * 32) >> 4),
                               dk + (((kk >> 2) * 16384 + (kk & 3) * 32) >> 4), kk != 0);
            wgmma_commit();
        };
        auto issue_pv = [&](float (&O)[64], float (&L)[4], uint32_t (&Pc)[32], int vs) {
            const uint32_t dv = dv0 + vs * (TILE_BYTES >> 4), dw = dw0 + vs * DW_ST;
            wgmma_fence();
#pragma unroll
            for (int kk = 0; kk < 8; kk++) {
                wgmma_rs_n64(O, Pc[4 * kk], Pc[4 * kk + 1], Pc[4 * kk + 2], Pc[4 * kk + 3], dv + ((kk * 2048) >> 4));
                wgmma_rs_n72(O, L, Pc[4 * kk], Pc[4 * kk + 1], Pc[4 * kk + 2], Pc[4 * kk + 3], dw + kk * DW_K);
            }
            wgmma_commit();
        };
        auto epilogue = [&](float (&O)[64], float (&L)[4]) {
            const float i0 = 1.0f / L[0], i1 = 1.0f / L[2];
            named_sync(BAR_EPI0 + cw, 128);
#pragma unroll
            for (int i = 0; i < 16; i += 2) {
                const int cc = i + (lane >> 4);
                const uint32_t addr = obase + (cc >> 3) * 8192 + st_row * 128 + (((cc & 7) ^ (st_row & 7)) << 4);
                stmatrix_x4(addr, pack_bf16(O[4 * i] * i0, O[4 * i + 1] * i0), pack_bf16(O[4 * i + 2] * i1, O[4 * i + 3] * i1),
                            pack_bf16(O[4 * i + 4] * i0, O[4 * i + 5] * i0), pack_bf16(O[4 * i + 6] * i1, O[4 * i + 7] * i1));
            }
            fence_proxy_async();
            named_arrive(BAR_ST0 + cw, 160);
        };
        auto scores_max = [&](uint32_t (&T)[32], float& x0, float& x1) {
#pragma unroll
            for (int i = 0; i < 32; i++) {
                const uint32_t sb = pack_bf16(S[2 * i], S[2 * i + 1]);
                T[i] = fma_bf16x2(sb, SCALE_HI2, mul_bf16x2(sb, SCALE_LO2));
            }
            uint32_t y0 = max_bf16x2(T[0], T[2]), y1 = max_bf16x2(T[1], T[3]);
#pragma unroll
            for (int i = 2; i < 16; i++) {
                y0 = max_bf16x2(y0, T[2 * i]);
                y1 = max_bf16x2(y1, T[2 * i + 1]);
            }
            x0 = fmaxf(bf16lo(y0), bf16hi(y0));
            x1 = fmaxf(bf16lo(y1), bf16hi(y1));
            x0 = fmaxf(x0, __shfl_xor_sync(0xffffffffu, x0, 1));
            x1 = fmaxf(x1, __shfl_xor_sync(0xffffffffu, x1, 1));
            x0 = fmaxf(x0, __shfl_xor_sync(0xffffffffu, x0, 2));
            x1 = fmaxf(x1, __shfl_xor_sync(0xffffffffu, x1, 2));
        };
        auto first_block = [&]() {
            stage_p(P);
            named_sync(BAR_EPI0 + cw, 128);
            vstage = stage;
            vphase = phase;
            mbar_wait(fk0 + stage * 8, phase);
            PP(named_sync(BAR_SCHED0 + cw, 256));
            issue_qk(dk0 + stage * (TILE_BYTES >> 4));
            PP(named_arrive(BAR_SCHED0 + (cw ^ 1), 256));
            if (++stage == AT_STAGES) { stage = 0; phase ^= 1; }
            okk = mbar_try_wait(fk0 + stage * 8, phase);
            okv = mbar_try_wait(fv0 + vstage * 8, vphase);
            wgmma_wait<0>();
            if (lane == 0) mbar_arrive(ek0 + vstage * 8);
        };

        int nfin = 0;
        gemm_chunk(S, false, true);
#pragma unroll 1
        for (; it < sched.end_att[blockIdx.x]; it++) {
            const int item = sched.item[blockIdx.x][it];
            const int type = item >> 12;
            const bool has_next = it + 1 < sched.end_att[blockIdx.x];
            gemm_rest(S, DM / 128);
            if (type == T_F1) {
                pack_p(S);
                gemm_chunk(S, false, has_next);
#pragma unroll
                for (int i = 0; i < 32; i++) P[i] = pack_bf16(silu_f(bf16lo(P[i])), silu_f(bf16hi(P[i])));
                stage_p(P);
                named_arrive(BAR_ST0 + cw, 160);
            } else {
                pack_p(S);
                first_block();
                float O[64], L[4] = {0.f, 0.f, 0.f, 0.f};
#pragma unroll
                for (int i = 0; i < 64; i++) O[i] = 0.f;
                float n0, n1;
                {
                    float x0, x1;
                    scores_max(P2, x0, x1);
                    n0 = fmaf(-x0, c, FAST_BIAS);
                    n1 = fmaf(-x1, c, FAST_BIAS);
#pragma unroll
                    for (int i = 0; i < 16; i++) {
                        const float e0 = ex2(fmaf(bf16lo(P2[2 * i]), c, n0));
                        const float e1 = ex2(fmaf(bf16hi(P2[2 * i]), c, n0));
                        const float e2 = ex2(fmaf(bf16lo(P2[2 * i + 1]), c, n1));
                        const float e3 = ex2(fmaf(bf16hi(P2[2 * i + 1]), c, n1));
                        P[2 * i] = pack_bf16(e0, e1);
                        P[2 * i + 1] = pack_bf16(e2, e3);
                    }
                }
                auto expo = [&](uint32_t (&Pn)[32], int i_lo, int i_hi) {
#pragma unroll
                    for (int i = i_lo; i < i_hi; i++) {
                        const uint32_t sa = pack_bf16(S[4 * i], S[4 * i + 1]), sb = pack_bf16(S[4 * i + 2], S[4 * i + 3]);
                        const uint32_t ta = fma_bf16x2(sa, SCALE_HI2, mul_bf16x2(sa, SCALE_LO2));
                        const uint32_t tb = fma_bf16x2(sb, SCALE_HI2, mul_bf16x2(sb, SCALE_LO2));
                        const float e0 = ex2(fmaf(bf16lo(ta), c, n0));
                        const float e1 = ex2(fmaf(bf16hi(ta), c, n0));
                        const float e2 = ex2(fmaf(bf16lo(tb), c, n1));
                        float e3 = ex2(fmaf(bf16hi(tb), c, n1));
                        if (i == i_hi - 1 && i_hi < 16) while (e3 < 0.f) e3 = g_dummy;
                        Pn[2 * i] = pack_bf16(e0, e1);
                        Pn[2 * i + 1] = pack_bf16(e2, e3);
                    }
                };
                auto step = [&](uint32_t (&Pc)[32], uint32_t (&Pn)[32]) {
                    const int ust = __shfl_sync(0xffffffffu, stage, 0), uvs = __shfl_sync(0xffffffffu, vstage, 0);
                    if (!okk) mbar_wait(fk0 + stage * 8, phase);
                    if (!okv) mbar_wait(fv0 + vstage * 8, vphase);
                    PP(named_sync(BAR_SCHED0 + cw, 256));
                    issue_qk(dk0 + ust * (TILE_BYTES >> 4));
                    issue_pv(O, L, Pc, uvs);
                    PP(named_arrive(BAR_SCHED0 + (cw ^ 1), 256));
                    const int pv = vstage;
                    vstage = stage;
                    vphase = phase;
                    if (++stage == AT_STAGES) { stage = 0; phase ^= 1; }
                    okk = mbar_try_wait(fk0 + stage * 8, phase);
                    okv = mbar_try_wait(fv0 + vstage * 8, vphase);
                    wgmma_wait<1>();
                    if (lane == 0) mbar_arrive(ek0 + vstage * 8);
                    EXPO(expo(Pn, 0, 8));
                    wgmma_wait<0>();
                    if (lane == 0) mbar_arrive(ev0 + pv * 8);
                    EXPO(expo(Pn, 8, 16));
                };
#pragma unroll 1
                for (int j = 0; j < 7; j++) {
                    step(P, P2);
                    step(P2, P);
                }
                step(P, P2);
                if (!okv) mbar_wait(fv0 + vstage * 8, vphase);
                issue_pv(O, L, P2, vstage);
                gemm_chunk(S, false, has_next);
                wgmma_wait<1>();
                if (lane == 0) mbar_arrive(ev0 + vstage * 8);
                float z = fmaf(L[0], 0.f, L[2] * 0.f);
#pragma unroll
                for (int i = 0; i < 64; i++) z = fmaf(O[i], 0.f, z);
                if (__any_sync(0xffffffffu, z != 0.f) && lane == 0) atomicOr(&sm.redo, 1u << (16 * cw + it));
                epilogue(O, L);
            }
        }
        wgmma_wait<0>();
#pragma unroll 1
        for (; it < sched.end_wide[blockIdx.x]; it++) {
            const int item = sched.item[blockIdx.x][it];
            const int type = item >> 12, a = (item >> 4) & 0xff, b = item & 15;
            const int nk = type == T_F2 ? FF / 64 : 2 * min(OPE_H, NH - (a >> 2) * OPE_H);
            float acc[128];
            int prev = -1;
#pragma unroll 1
            for (int kt = 0; kt < nk; kt++) {
                mbar_wait(fk0 + stage * 8, phase);
                mbar_wait(fv0 + stage * 8, phase);
                const uint64_t da = make_desc(smem_u32(sm.k[stage]) + cw * 64 * 128, 16, 1024);
                const uint64_t db = make_desc(smem_u32(sm.v[stage]), 8192, 1024);
                wgmma_fence();
#pragma unroll
                for (int kk = 0; kk < 4; kk++)
                    wgmma_ss_n256_tb(acc, da + (uint64_t)((kk * 32) >> 4), db + (uint64_t)((kk * 2048) >> 4), (kt | kk) != 0);
                wgmma_commit();
                wgmma_wait<1>();
                if (prev >= 0 && lane == 0) {
                    mbar_arrive(ek0 + prev * 8);
                    mbar_arrive(ev0 + prev * 8);
                }
                prev = stage;
                if (++stage == AT_STAGES) { stage = 0; phase ^= 1; }
            }
            wgmma_wait<0>();
            if (lane == 0) {
                mbar_arrive(ek0 + prev * 8);
                mbar_arrive(ev0 + prev * 8);
            }
            if (type == T_F2) {
                uint4* gp = g_g + (b * 4 + a * 2) * (8 * 256) + (tid - 128);
#pragma unroll
                for (int j = 0; j < 16; j++) {
                    uint32_t y[4];
#pragma unroll
                    for (int i = 0; i < 4; i++)
                        y[i] = pack_bf16(silu_f(bf16_round(acc[8 * j + 2 * i])), silu_f(bf16_round(acc[8 * j + 2 * i + 1])));
                    __stcg(gp + j * 256, make_uint4(y[0], y[1], y[2], y[3]));
                }
            } else {
                float4* part = g_part + (size_t)(((a >> 2) * 16 + b) * 4 + (a & 1) * 2) * (16 * 256) + (tid - 128);
#pragma unroll
                for (int j = 0; j < 32; j++) __stcg(part + j * 256, make_float4(acc[4 * j], acc[4 * j + 1], acc[4 * j + 2], acc[4 * j + 3]));
            }
            named_arrive(BAR_ST0 + cw, 160);
        }
#pragma unroll 1
        for (; it < n_items; it++) {
            const int item = sched.item[blockIdx.x][it];
            const int a = (item >> 4) & 0xff, b = item & 15;
            uint4 xv[4];
            load_x(xv, b, a);
            mbar_wait(smem_u32(&sm.fin_bar[nfin++]), 0);
            if (!((*reinterpret_cast<volatile uint32_t*>(&sm.redo) >> it) & 1)) {
                const float4* part = g_part + (size_t)(b * 8 + a) * (8 * 256) + (tid - 128);
                float4 v[OPE_N][8];
#pragma unroll
                for (int g = 0; g < OPE_N; g++) {
#pragma unroll
                    for (int j = 0; j < 8; j++) v[g][j] = __ldcg(part + (size_t)g * (64 * 16 * 256) + j * 256);
                }
                float T[32];
#pragma unroll
                for (int j = 0; j < 8; j++) {
                    T[4 * j] = v[0][j].x + v[1][j].x + v[2][j].x;
                    T[4 * j + 1] = v[0][j].y + v[1][j].y + v[2][j].y;
                    T[4 * j + 2] = v[0][j].z + v[1][j].z + v[2][j].z;
                    T[4 * j + 3] = v[0][j].w + v[1][j].w + v[2][j].w;
                }
                final_epi(T, xv, b, a);
            }
        }
        __syncwarp();
        if (lane == 0) mbar_arrive(smem_u32(&sm.redo_bar));
        mbar_wait(smem_u32(&sm.redo_bar), 0);
        rmask = *reinterpret_cast<volatile uint32_t*>(&sm.redo);
        rmask = (rmask | (rmask >> 16)) & 0xffffu;
#pragma unroll 1
        for (; rmask && (sched.item[blockIdx.x][__ffs(rmask) - 1] >> 12) == T_ATT; rmask &= rmask - 1) {
            gemm_chunk(S, false, true);
            gemm_rest(S, DM / 128);
            pack_p(S);
            first_block();
            float O[64], L[4] = {0.f, 0.f, 0.f, 0.f};
#pragma unroll
            for (int i = 0; i < 64; i++) O[i] = 0.f;
            float m0 = -INFINITY, m1 = -INFINITY;
#pragma unroll 1
            for (int j = 0; j < 16; j++) {
                float x0, x1;
                scores_max(P2, x0, x1);
                x0 = fmaxf(x0, m0);
                x1 = fmaxf(x1, m1);
                const float a0 = ex2((m0 - x0) * c), a1 = ex2((m1 - x1) * c);
                m0 = x0;
                m1 = x1;
                const float n0 = -m0 * c, n1 = -m1 * c;
#pragma unroll
                for (int i = 0; i < 16; i++) {
                    const float e0 = ex2(fmaf(bf16lo(P2[2 * i]), c, n0));
                    const float e1 = ex2(fmaf(bf16hi(P2[2 * i]), c, n0));
                    const float e2 = ex2(fmaf(bf16lo(P2[2 * i + 1]), c, n1));
                    const float e3 = ex2(fmaf(bf16hi(P2[2 * i + 1]), c, n1));
                    P[2 * i] = pack_bf16(e0, e1);
                    P[2 * i + 1] = pack_bf16(e2, e3);
                    O[4 * i] *= a0;
                    O[4 * i + 1] *= a0;
                    O[4 * i + 2] *= a1;
                    O[4 * i + 3] *= a1;
                }
                L[0] *= a0;
                L[1] *= a0;
                L[2] *= a1;
                L[3] *= a1;
                mbar_wait(fv0 + vstage * 8, vphase);
                issue_pv(O, L, P, vstage);
                wgmma_wait<0>();
                if (lane == 0) mbar_arrive(ev0 + vstage * 8);
                if (j < 15) {
                    mbar_wait(fk0 + stage * 8, phase);
                    issue_qk(dk0 + stage * (TILE_BYTES >> 4));
                    wgmma_wait<0>();
                    if (lane == 0) mbar_arrive(ek0 + stage * 8);
                    vstage = stage;
                    vphase = phase;
                    if (++stage == AT_STAGES) { stage = 0; phase ^= 1; }
                }
            }
            epilogue(O, L);
        }
#pragma unroll 1
        for (; rmask; rmask &= rmask - 1) {
            const int item = sched.item[blockIdx.x][__ffs(rmask) - 1];
            gemm_chunk(S, false, true);
            gemm_rest(S, NH);
            const int a = (item >> 4) & 0xff, b = item & 15;
            float T[32];
#pragma unroll
            for (int i = 0; i < 32; i++) T[i] = (a & 1) ? S[32 + i] : S[i];
            uint4 xv[4];
            load_x(xv, b, a);
            final_epi(T, xv, b, a);
        }
    }
}

typedef CUresult (*EncodeFn)(CUtensorMap*, CUtensorMapDataType, cuuint32_t, void*, const cuuint64_t*, const cuuint64_t*,
                             const cuuint32_t*, const cuuint32_t*, CUtensorMapInterleave, CUtensorMapSwizzle,
                             CUtensorMapL2promotion, CUtensorMapFloatOOBfill);

static CUtensorMap make_map(EncodeFn fn, const void* ptr, uint64_t rows, uint64_t cols, uint32_t box_rows, uint32_t box_blk) {
    CUtensorMap m;
    cuuint64_t dims[3] = {64, rows, cols / 64};
    cuuint64_t strides[2] = {cols * 2, 128};
    cuuint32_t box[3] = {64, box_rows, box_blk};
    cuuint32_t es[3] = {1, 1, 1};
    fn(&m, CU_TENSOR_MAP_DATA_TYPE_BFLOAT16, 3, const_cast<void*>(ptr), dims, strides, box, es, CU_TENSOR_MAP_INTERLEAVE_NONE,
       CU_TENSOR_MAP_SWIZZLE_128B, CU_TENSOR_MAP_L2_PROMOTION_L2_256B, CU_TENSOR_MAP_FLOAT_OOB_FILL_NONE);
    return m;
}

extern "C" void kernel_launch(void* const* d_in, const int* in_sizes, int n_in, void* d_out, int out_size) {
    const bf16* x = (const bf16*)d_in[0];
    const bf16* kc = (const bf16*)d_in[1];
    const bf16* vc = (const bf16*)d_in[2];
    const bf16* wq = (const bf16*)d_in[3];
    const bf16* wo = (const bf16*)d_in[4];
    const bf16* w1 = (const bf16*)d_in[6];
    const bf16* w2 = (const bf16*)d_in[7];
    bf16* out = (bf16*)d_out;

    static EncodeFn fn = nullptr;
    static void *p_xn = nullptr, *p_h = nullptr, *p_o = nullptr;
    static Sched sched;
    if (!fn) {
        void* f = nullptr;
        cudaDriverEntryPointQueryResult st;
        cudaGetDriverEntryPoint("cuTensorMapEncodeTiled", &f, cudaEnableDefault, &st);
        fn = (EncodeFn)f;
        cudaGetSymbolAddress(&p_xn, g_xn);
        cudaGetSymbolAddress(&p_h, g_h);
        cudaGetSymbolAddress(&p_o, g_o);
        cudaFuncSetAttribute(attn_kernel, cudaFuncAttributeMaxDynamicSharedMemorySize, (int)sizeof(AttnSmem) + 1024);
        static const struct { int n, n1; const char* tail; } cls[] = {
            {16, 0, "GO"}, {32, 1, "DO"}, {32, 1, "EO"}, {32, 1, "FO"}, {4, 4, "O"}, {12, 7, "GO"}, {4, 7, "G"}};
        int t1 = 0, t2 = 0, t3[3] = {0, 0, 0}, t4 = 0, i = 0;
        for (const auto& cl : cls) {
            for (int c = 0; c < cl.n; c++, i++) {
                int n = 0;
                for (int j = 0; j < cl.n1; j++, t1++) sched.item[i][n++] = (uint16_t)((T_F1 << 12) | ((t1 % 14) << 4) | (t1 / 14));
                for (int t = i; t < NH * 16; t += NUM_CTAS) sched.item[i][n++] = (uint16_t)((T_ATT << 12) | ((t >> 4) << 4) | (t & 15));
                sched.end_att[i] = sched.end_wide[i] = (uint8_t)n;
                for (const char* p = cl.tail; *p; p++) {
                    if (*p == 'G') { sched.item[i][n++] = (uint16_t)((T_F2 << 12) | ((t2 & 1) << 4) | (t2 >> 1)); t2++; }
                    if (*p >= 'D' && *p <= 'F') {
                        const int g = *p - 'D', t = t3[g]++;
                        sched.item[i][n++] = (uint16_t)((T_OPE << 12) | (((t & 1) | (g << 2)) << 4) | (t >> 1));
                    }
                    if (*p != 'O') sched.end_wide[i] = (uint8_t)n;
                    if (*p == 'O') { sched.item[i][n++] = (uint16_t)((T_OPF << 12) | ((t4 & 7) << 4) | (t4 >> 3)); t4++; }
                }
                sched.count[i] = (uint8_t)n;
            }
        }
    }
    CUtensorMap tm_xn_at = make_map(fn, p_xn, SEQ, DM, 128, 2);
    CUtensorMap tm_wq = make_map(fn, wq, DM, NH * DH, 128, 2);
    CUtensorMap tm_k = make_map(fn, kc, NH * SEQ, DH, 128, 2);
    CUtensorMap tm_v = make_map(fn, vc, NH * SEQ, DH, 128, 2);
    CUtensorMap tm_o_st = make_map(fn, p_o, SEQ, NH * DH, 64, 2);
    CUtensorMap tm_w1 = make_map(fn, w1, DM, FF, 128, 2);
    CUtensorMap tm_h_st = make_map(fn, p_h, SEQ, FF, 64, 2);
    CUtensorMap tm_h_ld = make_map(fn, p_h, SEQ, FF, 128, 1);
    CUtensorMap tm_w2 = make_map(fn, w2, FF, DM, 64, 4);
    CUtensorMap tm_o_g = make_map(fn, p_o, SEQ, NH * DH, 128, 2);
    CUtensorMap tm_wo = make_map(fn, wo, NH * DH, DM, 128, 2);
    CUtensorMap tm_o_gw = make_map(fn, p_o, SEQ, NH * DH, 128, 1);
    CUtensorMap tm_wow = make_map(fn, wo, NH * DH, DM, 64, 4);

    ln_kernel<<<SEQ / 8, 256>>>(x);
    cudaLaunchAttribute pdl[1];
    pdl[0].id = cudaLaunchAttributeProgrammaticStreamSerialization;
    pdl[0].val.programmaticStreamSerializationAllowed = 1;
    cudaLaunchConfig_t cfg = {};
    cfg.gridDim = dim3(NUM_CTAS);
    cfg.blockDim = dim3(384);
    cfg.dynamicSmemBytes = sizeof(AttnSmem) + 1024;
    cfg.stream = cudaStreamPerThread;
    cfg.attrs = pdl;
    cfg.numAttrs = 1;
    cudaLaunchKernelEx(&cfg, attn_kernel, tm_xn_at, tm_wq, tm_k, tm_v, tm_o_st, tm_w1, tm_h_st, tm_h_ld, tm_w2, tm_o_g,
                       tm_wo, tm_o_gw, tm_wow, x, out, sched);
}
```

```cpp
#include <cuda_runtime.h>
#include <cuda_bf16.h>
#include <cuda.h>
#include <stdint.h>

typedef __nv_bfloat16 bf16;
#define PP(x) x

constexpr int SEQ = 2048, DM = 512, NH = 32, DH = 128, FF = 1792;

__device__ __align__(1024) bf16 g_xn[SEQ * DM];
__device__ __align__(1024) bf16 g_h[SEQ * FF];
__device__ __align__(1024) bf16 g_o[SEQ * NH * DH];
__device__ uint4 g_g[64 * 8 * 256];
constexpr int C_H = 0, C_G = 16, C_BAD = C_G + 64, C_RED = C_BAD + 16;
__device__ unsigned int g_cnt[256];
__device__ unsigned long long g_mask[16];
#define CLS {32, 0, "E"}, {32, 0, "D"}, {52, 4, ""}, {16, 1, "GG"}
constexpr int HA = 14, HL = NH - 4;
__device__ volatile float g_dummy;

__device__ __forceinline__ uint32_t smem_u32(const void* p) { return (uint32_t)__cvta_generic_to_shared(p); }

__device__ __forceinline__ void mbar_init(uint32_t bar, uint32_t count) {
    asm volatile("mbarrier.init.shared::cta.b64 [%0], %1;" ::"r"(bar), "r"(count) : "memory");
}
__device__ __forceinline__ void mbar_expect_tx(uint32_t bar, uint32_t bytes) {
    asm volatile("mbarrier.arrive.expect_tx.shared::cta.b64 _, [%0], %1;" ::"r"(bar), "r"(bytes) : "memory");
}
__device__ __forceinline__ void mbar_arrive(uint32_t bar) {
    asm volatile("mbarrier.arrive.shared::cta.b64 _, [%0];" ::"r"(bar) : "memory");
}
__device__ __forceinline__ bool mbar_try_wait(uint32_t bar, uint32_t parity) {
    uint32_t ok;
    asm volatile(
        "{\n.reg .pred p;\n"
        "mbarrier.test_wait.parity.shared::cta.b64 p, [%1], %2;\n"
        "selp.u32 %0, 1, 0, p;\n}\n"
        : "=r"(ok)
        : "r"(bar), "r"(parity)
        : "memory");
    return ok != 0;
}
__device__ __forceinline__ void mbar_wait(uint32_t bar, uint32_t parity) {
    asm volatile(
        "{\n.reg .pred P1;\n.reg .u32 n;\nmov.u32 n, 0;\n"
        "LAB_WAIT:\n"
        "mbarrier.try_wait.parity.shared::cta.b64 P1, [%0], %1;\n"
        "@P1 bra DONE;\n"
        "add.u32 n, n, 1;\n"
        "setp.lt.u32 P1, n, 4194304;\n"
        "@P1 bra LAB_WAIT;\n"
        "trap;\n"
        "DONE:\n}\n" ::"r"(bar), "r"(parity)
        : "memory");
}
__device__ __forceinline__ void mbar_wait_cluster(uint32_t bar, uint32_t parity) {
    asm volatile(
        "{\n.reg .pred P1;\n.reg .u32 n;\nmov.u32 n, 0;\n"
        "LAB_WAIT:\n"
        "mbarrier.try_wait.parity.acquire.cluster.shared::cta.b64 P1, [%0], %1;\n"
        "@P1 bra DONE;\n"
        "add.u32 n, n, 1;\n"
        "setp.lt.u32 P1, n, 4194304;\n"
        "@P1 bra LAB_WAIT;\n"
        "trap;\n"
        "DONE:\n}\n" ::"r"(bar), "r"(parity)
        : "memory");
}
__device__ __forceinline__ uint32_t peer_addr(uint32_t a) {
    uint32_t r;
    asm volatile("mapa.shared::cluster.u32 %0, %1, %2;" : "=r"(r) : "r"(a), "r"((blockIdx.x & 1) ^ 1));
    return r;
}
__device__ __forceinline__ void tma_load_3d(uint32_t dst, const CUtensorMap* map, uint32_t bar, int c0, int c1, int c2) {
    asm volatile(
        "cp.async.bulk.tensor.3d.shared::cluster.global.mbarrier::complete_tx::bytes [%0], [%1, {%3, %4, %5}], [%2];"
        ::"r"(dst), "l"((uint64_t)map), "r"(bar), "r"(c0), "r"(c1), "r"(c2)
        : "memory");
}
__device__ __forceinline__ void tma_store_3d(const CUtensorMap* map, uint32_t src, int c0, int c1, int c2) {
    asm volatile("cp.async.bulk.tensor.3d.global.shared::cta.bulk_group [%0, {%2, %3, %4}], [%1];"
                 ::"l"((uint64_t)map), "r"(src), "r"(c0), "r"(c1), "r"(c2)
                 : "memory");
}
__device__ __forceinline__ void tma_commit() { asm volatile("cp.async.bulk.commit_group;" ::: "memory"); }
__device__ __forceinline__ void tma_wait_read0() { asm volatile("cp.async.bulk.wait_group.read 0;" ::: "memory"); }
__device__ __forceinline__ void tma_wait_all0() { asm volatile("cp.async.bulk.wait_group 0;" ::: "memory"); }
__device__ __forceinline__ void fence_proxy_async() { asm volatile("fence.proxy.async.shared::cta;" ::: "memory"); }
__device__ __forceinline__ void prefetch_tmap(const CUtensorMap* map) {
    asm volatile("prefetch.tensormap [%0];" ::"l"((uint64_t)map) : "memory");
}
__device__ __forceinline__ void pdl_wait() { asm volatile("griddepcontrol.wait;" ::: "memory"); }
__device__ __forceinline__ void pdl_launch() { asm volatile("griddepcontrol.launch_dependents;" ::: "memory"); }
__device__ __forceinline__ void named_sync(int id, int n) { asm volatile("bar.sync %0, %1;" ::"r"(id), "r"(n) : "memory"); }
__device__ __forceinline__ void named_arrive(int id, int n) { asm volatile("bar.arrive %0, %1;" ::"r"(id), "r"(n) : "memory"); }

__device__ __forceinline__ void wgmma_fence() { asm volatile("wgmma.fence.sync.aligned;" ::: "memory"); }
__device__ __forceinline__ void wgmma_commit() { asm volatile("wgmma.commit_group.sync.aligned;" ::: "memory"); }
template <int N>
__device__ __forceinline__ void wgmma_wait() { asm volatile("wgmma.wait_group.sync.aligned %0;" ::"n"(N) : "memory"); }

__device__ __forceinline__ void fence_acc(float (&d)[64]) {
#pragma unroll
    for (int i = 0; i < 64; i++) asm volatile("" : "+f"(d[i])::"memory");
}

template <int R>
__device__ __forceinline__ void reg_alloc() { asm volatile("setmaxnreg.inc.sync.aligned.u32 %0;" ::"n"(R)); }
template <int R>
__device__ __forceinline__ void reg_dealloc() { asm volatile("setmaxnreg.dec.sync.aligned.u32 %0;" ::"n"(R)); }

__device__ __forceinline__ uint64_t make_desc(uint32_t saddr, uint32_t lbo_bytes, uint32_t sbo_bytes) {
    uint64_t d = 0;
    d |= (uint64_t)((saddr & 0x3FFFF) >> 4);
    d |= (uint64_t)((lbo_bytes >> 4) & 0x3FFF) << 16;
    d |= (uint64_t)((sbo_bytes >> 4) & 0x3FFF) << 32;
    d |= (uint64_t)1 << 62;
    return d;
}

__device__ __forceinline__ float ex2(float x) {
    float y;
    asm volatile("ex2.approx.ftz.f32 %0, %1;" : "=f"(y) : "f"(x));
    return y;
}
__device__ __forceinline__ uint32_t pack_bf16(float lo, float hi) {
    uint32_t r;
    asm("cvt.rn.bf16x2.f32 %0, %1, %2;" : "=r"(r) : "f"(hi), "f"(lo));
    return r;
}
__device__ __forceinline__ uint32_t mul_bf16x2(uint32_t a, uint32_t b) {
    uint32_t r;
    asm("mul.rn.bf16x2 %0, %1, %2;" : "=r"(r) : "r"(a), "r"(b));
    return r;
}
__device__ __forceinline__ uint32_t add_bf16x2(uint32_t a, uint32_t b) {
    uint32_t r;
    asm("add.rn.bf16x2 %0, %1, %2;" : "=r"(r) : "r"(a), "r"(b));
    return r;
}
__device__ __forceinline__ unsigned int ld_acq(const unsigned int* p) {
    unsigned int v;
    asm volatile("ld.acquire.gpu.global.u32 %0, [%1];" : "=r"(v) : "l"(p) : "memory");
    return v;
}
__device__ __forceinline__ unsigned long long ld_acq64(const unsigned long long* p) {
    unsigned long long v;
    asm volatile("ld.acquire.gpu.global.u64 %0, [%1];" : "=l"(v) : "l"(p) : "memory");
    return v;
}
__device__ __forceinline__ uint32_t fma_bf16x2(uint32_t a, uint32_t b, uint32_t c) {
    uint32_t r;
    asm("fma.rn.bf16x2 %0, %1, %2, %3;" : "=r"(r) : "r"(a), "r"(b), "r"(c));
    return r;
}
__device__ __forceinline__ uint32_t max_bf16x2(uint32_t a, uint32_t b) {
    uint32_t r;
    asm("max.bf16x2 %0, %1, %2;" : "=r"(r) : "r"(a), "r"(b));
    return r;
}
__device__ __forceinline__ float bf16lo(uint32_t v) { return __uint_as_float(v << 16); }
__device__ __forceinline__ float bf16hi(uint32_t v) { return __uint_as_float(v & 0xffff0000u); }

__device__ __forceinline__ float scale_lo(uint32_t v) {
    uint32_t r;
    asm("{\n.reg .b16 l, h;\n.reg .b32 d;\nmov.b32 {l, h}, %1;\nmov.b32 d, {l, l};\nfma.rn.bf16x2 %0, d, %2, d;\n}\n"
        : "=r"(r) : "r"(v), "r"(0x4635BF80u));
    return __uint_as_float(r);
}
__device__ __forceinline__ float scale_hi(uint32_t v) {
    uint32_t r;
    asm("{\n.reg .b16 l, h;\n.reg .b32 d;\nmov.b32 {l, h}, %1;\nmov.b32 d, {h, h};\nfma.rn.bf16x2 %0, d, %2, d;\n}\n"
        : "=r"(r) : "r"(v), "r"(0x4635BF80u));
    return __uint_as_float(r);
}
__device__ __forceinline__ float bf16_round(float x) { return __bfloat162float(__float2bfloat16_rn(x)); }
__device__ __forceinline__ float silu_f(float x) {
    const float h = 0.5f * x;
    float t;
    asm("tanh.approx.f32 %0, %1;" : "=f"(t) : "f"(h));
    return fmaf(h, t, h);
}

__device__ __forceinline__ void stmatrix_x4(uint32_t addr, uint32_t r0, uint32_t r1, uint32_t r2, uint32_t r3) {
    asm volatile("stmatrix.sync.aligned.m8n8.x4.shared.b16 [%0], {%1, %2, %3, %4};"
                 ::"r"(addr), "r"(r0), "r"(r1), "r"(r2), "r"(r3)
                 : "memory");
}

#define ACC64(d) \
    "+f"(d[0]), "+f"(d[1]), "+f"(d[2]), "+f"(d[3]), "+f"(d[4]), "+f"(d[5]), "+f"(d[6]), "+f"(d[7]), \
    "+f"(d[8]), "+f"(d[9]), "+f"(d[10]), "+f"(d[11]), "+f"(d[12]), "+f"(d[13]), "+f"(d[14]), "+f"(d[15]), \
    "+f"(d[16]), "+f"(d[17]), "+f"(d[18]), "+f"(d[19]), "+f"(d[20]), "+f"(d[21]), "+f"(d[22]), "+f"(d[23]), \
    "+f"(d[24]), "+f"(d[25]), "+f"(d[26]), "+f"(d[27]), "+f"(d[28]), "+f"(d[29]), "+f"(d[30]), "+f"(d[31]), \
    "+f"(d[32]), "+f"(d[33]), "+f"(d[34]), "+f"(d[35]), "+f"(d[36]), "+f"(d[37]), "+f"(d[38]), "+f"(d[39]), \
    "+f"(d[40]), "+f"(d[41]), "+f"(d[42]), "+f"(d[43]), "+f"(d[44]), "+f"(d[45]), "+f"(d[46]), "+f"(d[47]), \
    "+f"(d[48]), "+f"(d[49]), "+f"(d[50]), "+f"(d[51]), "+f"(d[52]), "+f"(d[53]), "+f"(d[54]), "+f"(d[55]), \
    "+f"(d[56]), "+f"(d[57]), "+f"(d[58]), "+f"(d[59]), "+f"(d[60]), "+f"(d[61]), "+f"(d[62]), "+f"(d[63])

#define ACC64_STR \
    "{%0, %1, %2, %3, %4, %5, %6, %7, %8, %9, %10, %11, %12, %13, %14, %15, " \
    "%16, %17, %18, %19, %20, %21, %22, %23, %24, %25, %26, %27, %28, %29, %30, %31, " \
    "%32, %33, %34, %35, %36, %37, %38, %39, %40, %41, %42, %43, %44, %45, %46, %47, " \
    "%48, %49, %50, %51, %52, %53, %54, %55, %56, %57, %58, %59, %60, %61, %62, %63}"

template <int TB>
__device__ __forceinline__ void wgmma_ss_n128(float (&d)[64], uint64_t da, uint64_t db, int scale_d) {
    asm volatile(
        "{\n.reg .pred p;\nsetp.ne.b32 p, %66, 0;\n"
        "wgmma.mma_async.sync.aligned.m64n128k16.f32.bf16.bf16 " ACC64_STR ", %64, %65, p, 1, 1, 0, %67;\n}\n"
        : ACC64(d)
        : "l"(da), "l"(db), "r"(scale_d), "n"(TB));
}
template <int TB>
__device__ __forceinline__ void wgmma_rs_n128(float (&d)[64], uint32_t a0, uint32_t a1, uint32_t a2, uint32_t a3,
                                              uint64_t db, int scale_d) {
    asm volatile(
        "{\n.reg .pred p;\nsetp.ne.b32 p, %69, 0;\n"
        "wgmma.mma_async.sync.aligned.m64n128k16.f32.bf16.bf16 " ACC64_STR ", {%64, %65, %66, %67}, %68, p, 1, 1, %70;\n}\n"
        : ACC64(d)
        : "r"(a0), "r"(a1), "r"(a2), "r"(a3), "l"(db), "r"(scale_d), "n"(TB));
}

constexpr uint32_t DESC_HI = 0x40000040u;
__device__ __forceinline__ uint32_t desc_lo(uint32_t saddr, uint32_t lbo_bytes) {
    return ((saddr & 0x3FFFF) >> 4) | ((lbo_bytes >> 4) << 16);
}
template <int TB>
__device__ __forceinline__ void wgmma_ss_lo(float (&d)[64], uint32_t da, uint32_t db, int scale_d) {
    asm volatile(
        "{\n.reg .pred p;\n.reg .b64 xa, xb;\nsetp.ne.b32 p, %66, 0;\n"
        "mov.b64 xa, {%64, %68};\nmov.b64 xb, {%65, %68};\n"
        "wgmma.mma_async.sync.aligned.m64n128k16.f32.bf16.bf16 " ACC64_STR ", xa, xb, p, 1, 1, 0, %67;\n}\n"
        : ACC64(d)
        : "r"(da), "r"(db), "r"(scale_d), "n"(TB), "r"(DESC_HI));
}
__device__ __forceinline__ void wgmma_rs_lo_tb(float (&d)[64], uint32_t a0, uint32_t a1, uint32_t a2, uint32_t a3, uint32_t db) {
    asm volatile(
        "{\n.reg .b64 xb;\nmov.b64 xb, {%68, %69};\n"
        "wgmma.mma_async.sync.aligned.m64n128k16.f32.bf16.bf16 " ACC64_STR ", {%64, %65, %66, %67}, xb, 1, 1, 1, 1;\n}\n"
        : ACC64(d)
        : "r"(a0), "r"(a1), "r"(a2), "r"(a3), "r"(db), "r"(DESC_HI));
}

#define ACC8(d, o) "+f"(d[o]), "+f"(d[o + 1]), "+f"(d[o + 2]), "+f"(d[o + 3]), "+f"(d[o + 4]), "+f"(d[o + 5]), "+f"(d[o + 6]), "+f"(d[o + 7])
__device__ __forceinline__ void wgmma_rs_n64(float (&d)[64], uint32_t a0, uint32_t a1, uint32_t a2, uint32_t a3, uint32_t db) {
    asm volatile(
        "{\n.reg .b64 xb;\nmov.b64 xb, {%36, %37};\n"
        "wgmma.mma_async.sync.aligned.m64n64k16.f32.bf16.bf16 "
        "{%0, %1, %2, %3, %4, %5, %6, %7, %8, %9, %10, %11, %12, %13, %14, %15, "
        "%16, %17, %18, %19, %20, %21, %22, %23, %24, %25, %26, %27, %28, %29, %30, %31}, "
        "{%32, %33, %34, %35}, xb, 1, 1, 1, 1;\n}\n"
        : ACC8(d, 0), ACC8(d, 8), ACC8(d, 16), ACC8(d, 24)
        : "r"(a0), "r"(a1), "r"(a2), "r"(a3), "r"(db), "r"(DESC_HI));
}
__device__ __forceinline__ void wgmma_rs_n72(float (&d)[64], float (&l)[4], uint32_t a0, uint32_t a1, uint32_t a2, uint32_t a3, uint32_t db) {
    asm volatile(
        "{\n.reg .b64 xb;\nmov.b64 xb, {%40, %41};\n"
        "wgmma.mma_async.sync.aligned.m64n72k16.f32.bf16.bf16 "
        "{%0, %1, %2, %3, %4, %5, %6, %7, %8, %9, %10, %11, %12, %13, %14, %15, "
        "%16, %17, %18, %19, %20, %21, %22, %23, %24, %25, %26, %27, %28, %29, %30, %31, %32, %33, %34, %35}, "
        "{%36, %37, %38, %39}, xb, 1, 1, 1, 1;\n}\n"
        : ACC8(d, 32), ACC8(d, 40), ACC8(d, 48), ACC8(d, 56), "+f"(l[0]), "+f"(l[1]), "+f"(l[2]), "+f"(l[3])
        : "r"(a0), "r"(a1), "r"(a2), "r"(a3), "r"(db), "r"(DESC_HI));
}

__device__ __forceinline__ void wgmma_ss_n256_tb(float (&d)[128], uint64_t da, uint64_t db, int scale_d) {
    asm volatile(
        "{\n.reg .pred p;\nsetp.ne.b32 p, %130, 0;\n"
        "wgmma.mma_async.sync.aligned.m64n256k16.f32.bf16.bf16 "
        "{%0, %1, %2, %3, %4, %5, %6, %7, %8, %9, %10, %11, %12, %13, %14, %15, "
        "%16, %17, %18, %19, %20, %21, %22, %23, %24, %25, %26, %27, %28, %29, %30, %31, "
        "%32, %33, %34, %35, %36, %37, %38, %39, %40, %41, %42, %43, %44, %45, %46, %47, "
        "%48, %49, %50, %51, %52, %53, %54, %55, %56, %57, %58, %59, %60, %61, %62, %63, "
        "%64, %65, %66, %67, %68, %69, %70, %71, %72, %73, %74, %75, %76, %77, %78, %79, "
        "%80, %81, %82, %83, %84, %85, %86, %87, %88, %89, %90, %91, %92, %93, %94, %95, "
        "%96, %97, %98, %99, %100, %101, %102, %103, %104, %105, %106, %107, %108, %109, %110, %111, "
        "%112, %113, %114, %115, %116, %117, %118, %119, %120, %121, %122, %123, %124, %125, %126, %127}, "
        "%128, %129, p, 1, 1, 0, 1;\n}\n"
        : ACC8(d, 0), ACC8(d, 8), ACC8(d, 16), ACC8(d, 24), ACC8(d, 32), ACC8(d, 40), ACC8(d, 48), ACC8(d, 56),
          ACC8(d, 64), ACC8(d, 72), ACC8(d, 80), ACC8(d, 88), ACC8(d, 96), ACC8(d, 104), ACC8(d, 112), ACC8(d, 120)
        : "l"(da), "l"(db), "r"(scale_d));
}

__global__ void __launch_bounds__(256) ln_kernel(const bf16* __restrict__ x) {
    pdl_launch();
    int warp = threadIdx.x >> 5, lane = threadIdx.x & 31;
    int row = blockIdx.x * 8 + warp;
    if (blockIdx.x == 0) g_cnt[threadIdx.x] = 0;
    if (blockIdx.x == 1 && threadIdx.x < 16) g_mask[threadIdx.x] = 0;
    const uint4* src = reinterpret_cast<const uint4*>(x + (size_t)row * DM);
    uint4 v[2];
    v[0] = src[lane];
    v[1] = src[lane + 32];
    float f[16];
#pragma unroll
    for (int i = 0; i < 2; i++) {
        const __nv_bfloat162* p = reinterpret_cast<const __nv_bfloat162*>(&v[i]);
#pragma unroll
        for (int j = 0; j < 4; j++) {
            float2 t = __bfloat1622float2(p[j]);
            f[i * 8 + j * 2] = t.x;
            f[i * 8 + j * 2 + 1] = t.y;
        }
    }
    float s = 0.f;
#pragma unroll
    for (int i = 0; i < 16; i++) s += f[i];
#pragma unroll
    for (int o = 16; o > 0; o >>= 1) s += __shfl_xor_sync(0xffffffffu, s, o);
    float mean = s * (1.0f / DM);
    float q = 0.f;
#pragma unroll
    for (int i = 0; i < 16; i++) {
        float d = f[i] - mean;
        q += d * d;
    }
#pragma unroll
    for (int o = 16; o > 0; o >>= 1) q += __shfl_xor_sync(0xffffffffu, q, o);
    float var_b = bf16_round(q * (1.0f / DM));
    float mean_b = bf16_round(mean);
    const float rden = 1.0f / bf16_round(sqrtf(bf16_round(var_b + 1e-5f)));
    uint4 o[2];
#pragma unroll
    for (int i = 0; i < 2; i++) {
        uint32_t* p = reinterpret_cast<uint32_t*>(&o[i]);
#pragma unroll
        for (int j = 0; j < 4; j++) {
            const uint32_t d = pack_bf16(f[i * 8 + j * 2] - mean_b, f[i * 8 + j * 2 + 1] - mean_b);
            p[j] = pack_bf16(bf16lo(d) * rden, bf16hi(d) * rden);
        }
    }
    uint4* dst = reinterpret_cast<uint4*>(g_xn + (size_t)row * DM);
    dst[lane] = o[0];
    dst[lane + 32] = o[1];
}

constexpr int AT_STAGES = 3;
constexpr int TILE_BYTES = 128 * 128 * 2;
struct __align__(1024) AttnSmem {
    uint8_t k[AT_STAGES][TILE_BYTES];
    uint8_t v[AT_STAGES][TILE_BYTES];
    uint8_t o[TILE_BYTES];
    uint32_t ones0[4];
    uint64_t full_k[AT_STAGES], full_v[AT_STAGES], empty_k[AT_STAGES], empty_v[AT_STAGES];
    uint64_t st_free[2];
    uint64_t redo_bar;
    uint32_t redo;
    uint32_t pad0;
    uint32_t ones1[4];
    uint64_t fin_bar[2];
    uint64_t xrdy, xchg[8];
    uint32_t pad1[10];
    uint32_t ones2[(2048 - 288) / 4];
};

#define EXPO(x) x
#define N8(x) x
#define PPK 8
#define XP_A 16
#define IL_K 2
#define IL_0 1
#define XP_B 10
#define FAST_BIAS (-40.0f)
constexpr int NUM_CTAS = 132;
constexpr int MAX_ITEMS = 12;
enum { T_ATT = 0, T_F1 = 1, T_F2 = 2, T_OPE = 3 };
struct Sched {
    uint16_t item[NUM_CTAS][MAX_ITEMS];
    uint8_t count[NUM_CTAS], end_att[NUM_CTAS];
    int zero;
};

enum { M_XN, M_WQ, M_XN2, M_W1, M_HLD, M_W2, M_OLDW, M_WOW, M_OLD, M_WO, M_K, M_V, M_O, M_HST, M_COUNT };
struct Maps { CUtensorMap m[M_COUNT]; };
#define tm_wq maps.m[M_WQ]
#define tm_w1 maps.m[M_W1]
#define tm_k maps.m[M_K]
#define tm_v maps.m[M_V]
#define tm_o maps.m[M_O]
#define tm_hst maps.m[M_HST]

__global__ void __launch_bounds__(384, 1)
attn_kernel(const __grid_constant__ Maps maps, const bf16* __restrict__ x, bf16* __restrict__ out, const __grid_constant__ Sched sched) {
    extern __shared__ uint8_t smem_raw[];
    AttnSmem& sm = *reinterpret_cast<AttnSmem*>((reinterpret_cast<uintptr_t>(smem_raw) + 1023) & ~uintptr_t(1023));
    const int tid = threadIdx.x;
    const int wg = __shfl_sync(0xffffffffu, tid >> 7, 0);
    const int n_items = sched.count[blockIdx.x];
    if (tid >= 32 && tid < 32 + M_COUNT) prefetch_tmap(&maps.m[tid - 32]);

    if (tid == 0) {
#pragma unroll
        for (int s = 0; s < AT_STAGES; s++) {
            mbar_init(smem_u32(&sm.full_k[s]), 1);
            mbar_init(smem_u32(&sm.full_v[s]), 1);
            mbar_init(smem_u32(&sm.empty_k[s]), 8);
            mbar_init(smem_u32(&sm.empty_v[s]), 8);
        }
        mbar_init(smem_u32(&sm.st_free[0]), 1);
        mbar_init(smem_u32(&sm.st_free[1]), 1);
        mbar_init(smem_u32(&sm.redo_bar), 8);
        mbar_init(smem_u32(&sm.xrdy), 2);
#pragma unroll
        for (int s = 0; s < 8; s++) {
            mbar_init(smem_u32(&sm.xchg[s]), 1);
            mbar_expect_tx(smem_u32(&sm.xchg[s]), TILE_BYTES / 4);
        }
#pragma unroll
        for (int s = 0; s < 2; s++) mbar_init(smem_u32(&sm.fin_bar[s]), 1);
        sm.redo = 0;
        asm volatile("fence.mbarrier_init.release.cluster;" ::: "memory");
    }
    if (tid < 64) {
        const int r = tid >> 2;
        sm.ones0[(r >> 3) * 256 + (r & 7) * 36 + (tid & 3)] = 0x3F803F80u;
        fence_proxy_async();
    }
    asm volatile("barrier.cluster.arrive.release.aligned;\nbarrier.cluster.wait.acquire.aligned;" ::: "memory");
    if (tid == 0) {
        const int item = sched.item[blockIdx.x][0];
        const CUtensorMap* tb = (item >> 12) == T_ATT ? &tm_wq : &tm_w1;
#pragma unroll
        for (int s = 0; s < AT_STAGES; s++) {
            mbar_expect_tx(smem_u32(&sm.full_v[s]), TILE_BYTES);
            tma_load_3d(smem_u32(sm.v[s]), tb, smem_u32(&sm.full_v[s]), 0, s * 128, ((item >> 4) & 0xff) * 2);
        }
    }
    pdl_wait();
    int it = 0;
    uint32_t rmask = 0;
    bool redo = false;
    auto next_item = [&]() -> bool {
        if (!redo) {
            if (++it < n_items) return true;
            mbar_wait(smem_u32(&sm.redo_bar), 0);
            rmask = *reinterpret_cast<volatile uint32_t*>(&sm.redo);
            rmask = (rmask | (rmask >> 16)) & 0xffffu;
            redo = true;
        }
        if (!rmask) return false;
        it = __ffs(rmask) - 1;
        rmask &= rmask - 1;
        return true;
    };
    constexpr int BAR_SCHED0 = 1, BAR_EPI0 = 3, BAR_ST0 = 5;

    if (wg == 0) {
        reg_dealloc<40>();
        if (tid >= 32 && tid < 96) {
            const int cw = (tid >> 5) - 1;
            const uint32_t obase = smem_u32(sm.o) + cw * 16384;
            do {
                const int item = sched.item[blockIdx.x][it];
                const int type = item >> 12, a = (item >> 4) & 0xff, b = item & 15;
                if (type == T_OPE) continue;
                named_sync(BAR_ST0 + cw, 160);
                if ((tid & 31) == 0) {
                    if (type >= T_F2) {
                        __threadfence();
                        atomicAdd(&g_cnt[C_G + b * 2 + (a & 1)], 1u);
                    } else {
                        if (redo) tma_wait_all0();
                        tma_store_3d(type == T_ATT ? &tm_o : &tm_hst, obase, 0, b * 128 + cw * 64, a * 2);
                        tma_commit();
                        tma_wait_read0();
                        mbar_arrive(smem_u32(&sm.st_free[cw]));
                        if (!redo && (sched.item[blockIdx.x][it + 1] >> 12) == T_OPE && it + 1 < n_items)
                            asm volatile("mbarrier.arrive.release.cluster.shared::cluster.b64 _, [%0];" ::"r"(peer_addr(smem_u32(&sm.xrdy))) : "memory");
                        const bool bad = (*reinterpret_cast<volatile uint32_t*>(&sm.redo) >> (16 * cw + it)) & 1;
                        if (bad && !redo) atomicAdd(&g_cnt[C_BAD + b], 1u);
                        tma_wait_all0();
                        asm volatile("fence.proxy.async;" ::: "memory");
                        __threadfence();
                        if (type != T_ATT) atomicAdd(&g_cnt[C_H + b], 1u);
                        else if (!redo) atomicOr(&g_mask[b], 1ull << (2 * a + cw));
                        else if (bad) atomicAdd(&g_cnt[C_RED + b], 1u);
                    }
                }
                __syncwarp();
            } while (next_item());
            if ((tid & 31) == 0) tma_wait_all0();
        }
        if (tid == 96) {
            int ord = 0;
            for (int i = 0; i < n_items; i++) {
                const int item = sched.item[blockIdx.x][i];
                const int a = (item >> 4) & 0xff, b = item & 15;
                if ((item >> 12) != T_OPE) continue;
                unsigned int spins = 0;
                while (ld_acq(&g_cnt[C_G + b * 2 + (a & 1)]) < 2 && ++spins < (1u << 24)) {}
                mbar_arrive(smem_u32(&sm.fin_bar[ord++]));
                while (ld_acq64(&g_mask[b]) != ~0ull && ++spins < (1u << 24)) {}
                if (ld_acq(&g_cnt[C_BAD + b])) atomicOr(&sm.redo, 1u << i);
                mbar_arrive(smem_u32(&sm.fin_bar[ord++]));
            }
        }
        if (tid == 0) {
            int stage = 0, pre = AT_STAGES;
            uint32_t phase = 0;
            do {
                const int item = sched.item[blockIdx.x][it];
                const int type = item >> 12, a = (item >> 4) & 0xff, b = item & 15;
                int im = type * 2 + (type == T_OPE && redo ? 2 : 0);
                bool wide = type >= T_F2 && !redo;
                int nch = DM / 128, kc0 = 0, kc1 = 0xff, nb = a;
                unsigned long long mask = type == T_OPE && !redo ? 0ull : ~0ull;
                unsigned int spins = 0;
                if (type == T_F2) {
                    nch = FF / 128;
                    nb = a * 2;
                    while (ld_acq(&g_cnt[C_H + b]) < 2 * (FF / 128) && ++spins < (1u << 24)) {}
                    asm volatile("fence.proxy.async;" ::: "memory");
                } else if (type == T_OPE) {
                    nb = (a & 1) * 2 + (a >> 2);
                    if (!redo) {
                        kc0 = (a >> 2) * HA;
                        kc1 = (a >> 2) ? HL : HA;
                        nch = kc1 - kc0 + 2;
                    } else {
                        nch = NH;
                        const unsigned int nbad = ld_acq(&g_cnt[C_BAD + b]);
                        while (ld_acq(&g_cnt[C_RED + b]) < nbad && ++spins < (1u << 24)) {}
                        asm volatile("fence.proxy.async;" ::: "memory");
                    }
                }
                for (int kc = kc0; nch > 0; nch--, kc++) {
                    if (kc == kc1) kc = HL + (a >> 2) * 2;
                    if (((uint32_t)(mask >> (2 * kc)) & 3u) != 3u) {
                        do mask = ld_acq64(&g_mask[b]); while (((uint32_t)(mask >> (2 * kc)) & 3u) != 3u && ++spins < (1u << 24));
                        asm volatile("fence.proxy.async;" ::: "memory");
                    }
#pragma unroll 1
                    for (int hk = 0; hk <= (int)wide; hk++) {
                        mbar_wait(smem_u32(&sm.empty_k[stage]), phase ^ 1);
                        mbar_expect_tx(smem_u32(&sm.full_k[stage]), wide ? TILE_BYTES / 2 : TILE_BYTES);
                        tma_load_3d(smem_u32(sm.k[stage]), &maps.m[im], smem_u32(&sm.full_k[stage]), 0, b * 128, kc * 2 + hk);
                        if (pre > 0) pre--;
                        else {
                            mbar_wait(smem_u32(&sm.empty_v[stage]), phase ^ 1);
                            mbar_expect_tx(smem_u32(&sm.full_v[stage]), TILE_BYTES);
                            tma_load_3d(smem_u32(sm.v[stage]), &maps.m[im + 1], smem_u32(&sm.full_v[stage]), 0, kc * 128 + hk * 64, nb * 2);
                            if (im == M_OLDW)
                                tma_load_3d(smem_u32(sm.v[stage]) + TILE_BYTES / 2, &maps.m[M_WOW], smem_u32(&sm.full_v[stage]), 0, kc * 128 + hk * 64, (nb ^ 1) * 2);
                        }
                        if (++stage == AT_STAGES) { stage = 0; phase ^= 1; }
                    }
                }
                if (type == T_ATT) {
                    for (int j = 0; j < 16; j++) {
                        mbar_wait(smem_u32(&sm.empty_k[stage]), phase ^ 1);
                        mbar_expect_tx(smem_u32(&sm.full_k[stage]), TILE_BYTES);
                        tma_load_3d(smem_u32(sm.k[stage]), &tm_k, smem_u32(&sm.full_k[stage]), 0, a * SEQ + j * 128, 0);
                        mbar_wait(smem_u32(&sm.empty_v[stage]), phase ^ 1);
                        mbar_expect_tx(smem_u32(&sm.full_v[stage]), TILE_BYTES);
                        tma_load_3d(smem_u32(sm.v[stage]), &tm_v, smem_u32(&sm.full_v[stage]), 0, a * SEQ + j * 128, 0);
                        if (++stage == AT_STAGES) { stage = 0; phase ^= 1; }
                    }
                }
            } while (next_item());
        }
    } else {
        reg_alloc<232>();
        const int cw = wg - 1;
        const int lane = tid & 31;
        const int warp_in_wg = (tid >> 5) & 3;
        const float c = 1.4426950408889634f;
        const float c17 = c * (1.f / 131072.f);
        const uint32_t SCALE_HI2 = 0x3DB53DB5u, SCALE_LO2 = 0x371E371Eu;
        const uint32_t obase = smem_u32(sm.o) + cw * 16384;
        const int st_row = warp_in_wg * 16 + ((lane >> 3) & 1) * 8 + (lane & 7);

        const uint32_t dq = __shfl_sync(0xffffffffu, desc_lo(obase, 16), 0);
        const uint32_t dk0 = __shfl_sync(0xffffffffu, desc_lo(smem_u32(sm.k[0]), 16), 0);
        const uint32_t dv0 = dk0 - (1u << 16) + (1024u << 16) + AT_STAGES * (TILE_BYTES >> 4);

        PP(if (cw == 1) named_arrive(BAR_SCHED0 + 0, 256));

        int stage = 0;
        uint32_t phase = 0;
        float S[64];
        uint32_t P[32], P2[32];
        uint32_t cnt = 0;
        const uint32_t dw0 = __shfl_sync(0xffffffffu, desc_lo(smem_u32(sm.v[0]) + 16384, smem_u32(sm.ones0) - smem_u32(sm.v[0]) - 16384), 0);
        constexpr uint32_t DW_K = 128u - (128u << 16), DW_ST = 2048u - (2048u << 16);

        const uint32_t fk0 = smem_u32(&sm.full_k[0]), fv0 = smem_u32(&sm.full_v[0]);
        const uint32_t ek0 = smem_u32(&sm.empty_k[0]), ev0 = smem_u32(&sm.empty_v[0]);
        int vstage = 0;
        uint32_t vphase = 0;
        bool okk = false, okv = false;

        auto gemm_chunk = [&](float (&S)[64], bool acc, bool real) {
            if (real) {
                mbar_wait(fk0 + stage * 8, phase);
                mbar_wait(fv0 + stage * 8, phase);
            }
            const uint64_t da = make_desc(smem_u32(sm.k[stage]) + cw * 64 * 128, 16, 1024);
            const uint64_t db = make_desc(smem_u32(sm.v[stage]), 16384, 1024);
            wgmma_fence();
#pragma unroll
            for (int kk = 0; kk < 8; kk++) {
                wgmma_ss_n128<1>(S, da + (uint64_t)(((kk >> 2) * 16384 + (kk & 3) * 32) >> 4),
                                 db + (uint64_t)((kk * 2048) >> 4), acc || kk != 0);
            }
            wgmma_commit();
        };
        auto gemm_rest = [&](float (&S)[64], int nch) {
            int prev = stage;
            if (++stage == AT_STAGES) { stage = 0; phase ^= 1; }
#pragma unroll 1
            for (int kc = 1; kc < nch; kc++) {
                gemm_chunk(S, true, true);
                wgmma_wait<1>();
                if (lane == 0) {
                    mbar_arrive(ek0 + prev * 8);
                    mbar_arrive(ev0 + prev * 8);
                }
                prev = stage;
                if (++stage == AT_STAGES) { stage = 0; phase ^= 1; }
            }
            wgmma_wait<0>();
            if (lane == 0) {
                mbar_arrive(ek0 + prev * 8);
                mbar_arrive(ev0 + prev * 8);
            }
        };
        auto gemm_chunk1 = [&](bool real) {
            const int s0 = stage;
            const uint32_t p0 = phase;
            if (++stage == AT_STAGES) { stage = 0; phase ^= 1; }
            gemm_chunk(S, true, real);
            stage = s0;
            phase = p0;
        };
        auto release = [&](int st) {
            if (lane == 0) {
                mbar_arrive(ek0 + st * 8);
                mbar_arrive(ev0 + st * 8);
            }
        };
        auto gemm_rest2 = [&]() {
            if (++stage == AT_STAGES) { stage = 0; phase ^= 1; }
            const int p1 = stage;
            if (++stage == AT_STAGES) { stage = 0; phase ^= 1; }
            gemm_chunk(S, true, true);
            wgmma_wait<1>();
            release(p1);
            const int p2 = stage;
            if (++stage == AT_STAGES) { stage = 0; phase ^= 1; }
            gemm_chunk(S, true, true);
            wgmma_wait<1>();
            release(p2);
            wgmma_wait<0>();
            release(stage);
            if (++stage == AT_STAGES) { stage = 0; phase ^= 1; }
        };
        auto pack_p = [&](float (&S)[64]) {
#pragma unroll
            for (int i = 0; i < 32; i++) P[i] = pack_bf16(S[2 * i], S[2 * i + 1]);
        };
        auto load_x = [&](uint4 (&xv)[8], int mb, int nb) {
            const int t = tid & 127, ch = t & 15, row0 = t >> 4;
            const size_t off = (size_t)(mb * 128 + cw * 64 + row0) * DM + nb * 128 + ch * 8;
#pragma unroll
            for (int i = 0; i < 8; i++)
                asm volatile("ld.global.nc.v4.u32 {%0, %1, %2, %3}, [%4];" : "=r"(xv[i].x), "=r"(xv[i].y), "=r"(xv[i].z), "=r"(xv[i].w)
                             : "l"(x + off + (size_t)i * 8 * DM));
        };
        auto load_g = [&](uint4 (&gw)[8], int mb, int nb) {
#pragma unroll
            for (int i = 0; i < 8; i++) gw[i] = __ldcg(g_g + ((mb * 4 + nb) * 8 + i) * 256 + (tid - 128));
        };
        auto final_epi = [&](float (&T)[64], uint4 (&xv)[8], uint4 (&gw)[8], int mb, int nb) {
            const int t = tid & 127, ch = t & 15, row0 = t >> 4;
            const size_t off = (size_t)(mb * 128 + cw * 64 + row0) * DM + nb * 128 + ch * 8;
            mbar_wait(smem_u32(&sm.st_free[cw]), (cnt & 1) ^ 1);
#pragma unroll
            for (int i = 0; i < 16; i += 2) {
                const uint4 gv = gw[i >> 1];
                const int cc = i + (lane >> 4);
                const uint32_t addr = obase + (cc >> 3) * 8192 + st_row * 128 + (((cc & 7) ^ (st_row & 7)) << 4);
                stmatrix_x4(addr, mul_bf16x2(pack_bf16(T[4 * i], T[4 * i + 1]), gv.x), mul_bf16x2(pack_bf16(T[4 * i + 2], T[4 * i + 3]), gv.y),
                            mul_bf16x2(pack_bf16(T[4 * i + 4], T[4 * i + 5]), gv.z), mul_bf16x2(pack_bf16(T[4 * i + 6], T[4 * i + 7]), gv.w));
            }
            named_sync(BAR_EPI0 + cw, 128);
            const uint32_t sa = obase + (ch >> 3) * 8192 + row0 * 128 + (((ch & 7) ^ row0) << 4);
#pragma unroll
            for (int i = 0; i < 8; i++) {
                uint4 sv;
                asm volatile("ld.shared.v4.u32 {%0, %1, %2, %3}, [%4];" : "=r"(sv.x), "=r"(sv.y), "=r"(sv.z), "=r"(sv.w) : "r"(sa + i * 1024));
                sv.x = add_bf16x2(xv[i].x, sv.x);
                sv.y = add_bf16x2(xv[i].y, sv.y);
                sv.z = add_bf16x2(xv[i].z, sv.z);
                sv.w = add_bf16x2(xv[i].w, sv.w);
                *reinterpret_cast<uint4*>(out + off + (size_t)i * 8 * DM) = sv;
            }
            named_sync(BAR_EPI0 + cw, 128);
        };
        auto stage_p = [&](uint32_t (&P)[32]) {
            mbar_wait(smem_u32(&sm.st_free[cw]), (cnt & 1) ^ 1);
            cnt++;
#pragma unroll
            for (int i = 0; i < 16; i += 2) {
                const int cc = i + (lane >> 4);
                const uint32_t addr = obase + (cc >> 3) * 8192 + st_row * 128 + (((cc & 7) ^ (st_row & 7)) << 4);
                stmatrix_x4(addr, P[2 * i], P[2 * i + 1], P[2 * i + 2], P[2 * i + 3]);
            }
            fence_proxy_async();
        };
        auto issue_qk2 = [&](float (&S)[64], uint32_t dk) {
            wgmma_fence();
#pragma unroll
            for (int kk = 0; kk < 8; kk++)
                wgmma_ss_lo<0>(S, dq + (((kk >> 2) * 8192 + (kk & 3) * 32) >> 4),
                               dk + (((kk >> 2) * 16384 + (kk & 3) * 32) >> 4), kk != 0);
            wgmma_commit();
        };
        auto issue_qk = [&](uint32_t dk) { issue_qk2(S, dk); };
        auto issue_pv = [&](float (&O)[64], float (&L)[4], uint32_t (&Pc)[32], int vs) {
            const uint32_t dv = dv0 + vs * (TILE_BYTES >> 4), dw = dw0 + vs * DW_ST;
            wgmma_fence();
#pragma unroll
            for (int kk = 0; kk < 8; kk++) {
                wgmma_rs_n64(O, Pc[4 * kk], Pc[4 * kk + 1], Pc[4 * kk + 2], Pc[4 * kk + 3], dv + ((kk * 2048) >> 4));
                wgmma_rs_n72(O, L, Pc[4 * kk], Pc[4 * kk + 1], Pc[4 * kk + 2], Pc[4 * kk + 3], dw + kk * DW_K);
            }
            wgmma_commit();
        };
        auto epilogue = [&](float (&O)[64], float (&L)[4]) {
            const float i0 = 1.0f / L[0], i1 = 1.0f / L[2];
            named_sync(BAR_EPI0 + cw, 128);
#pragma unroll
            for (int i = 0; i < 16; i += 2) {
                const int cc = i + (lane >> 4);
                const uint32_t addr = obase + (cc >> 3) * 8192 + st_row * 128 + (((cc & 7) ^ (st_row & 7)) << 4);
                stmatrix_x4(addr, pack_bf16(O[4 * i] * i0, O[4 * i + 1] * i0), pack_bf16(O[4 * i + 2] * i1, O[4 * i + 3] * i1),
                            pack_bf16(O[4 * i + 4] * i0, O[4 * i + 5] * i0), pack_bf16(O[4 * i + 6] * i1, O[4 * i + 7] * i1));
            }
            fence_proxy_async();
            named_arrive(BAR_ST0 + cw, 160);
        };
        auto scores_max = [&](uint32_t (&T)[32], float& x0, float& x1) {
#pragma unroll
            for (int i = 0; i < 32; i++) {
                const uint32_t sb = pack_bf16(S[2 * i], S[2 * i + 1]);
                T[i] = fma_bf16x2(sb, SCALE_HI2, mul_bf16x2(sb, SCALE_LO2));
            }
            uint32_t y0 = max_bf16x2(T[0], T[2]), y1 = max_bf16x2(T[1], T[3]);
#pragma unroll
            for (int i = 2; i < 16; i++) {
                y0 = max_bf16x2(y0, T[2 * i]);
                y1 = max_bf16x2(y1, T[2 * i + 1]);
            }
            x0 = fmaxf(bf16lo(y0), bf16hi(y0));
            x1 = fmaxf(bf16lo(y1), bf16hi(y1));
            x0 = fmaxf(x0, __shfl_xor_sync(0xffffffffu, x0, 1));
            x1 = fmaxf(x1, __shfl_xor_sync(0xffffffffu, x1, 1));
            x0 = fmaxf(x0, __shfl_xor_sync(0xffffffffu, x0, 2));
            x1 = fmaxf(x1, __shfl_xor_sync(0xffffffffu, x1, 2));
        };
        auto first_block = [&]() {
            stage_p(P);
            named_sync(BAR_EPI0 + cw, 128);
            vstage = stage;
            vphase = phase;
            mbar_wait(fk0 + stage * 8, phase);
            PP(named_sync(BAR_SCHED0 + cw, 256));
            issue_qk(dk0 + stage * (TILE_BYTES >> 4));
            PP(named_arrive(BAR_SCHED0 + (cw ^ 1), 256));
            if (++stage == AT_STAGES) { stage = 0; phase ^= 1; }
            okk = mbar_try_wait(fk0 + stage * 8, phase);
            okv = mbar_try_wait(fv0 + vstage * 8, vphase);
            wgmma_wait<0>();
            if (lane == 0) mbar_arrive(ek0 + vstage * 8);
        };

        gemm_chunk(S, false, true);
        gemm_chunk1(true);
        wgmma_wait<1>();
        release(stage);
#pragma unroll 1
        for (; it < sched.end_att[blockIdx.x]; it++) {
            const int item = sched.item[blockIdx.x][it];
            const int type = item >> 12;
            const bool has_next = it + 1 < sched.end_att[blockIdx.x];
            gemm_rest2();
            if (type == T_F1) {
                pack_p(S);
                gemm_chunk(S, false, has_next);
#pragma unroll
                for (int i = 0; i < 32; i++) P[i] = pack_bf16(silu_f(bf16lo(P[i])), silu_f(bf16hi(P[i])));
                gemm_chunk1(has_next);
                wgmma_wait<1>();
                if (has_next) release(stage);
                stage_p(P);
                named_arrive(BAR_ST0 + cw, 160);
            } else {
                pack_p(S);
                float O[64], L[4];
#pragma unroll
                for (int i = 0; i < 64; i++) O[i] = 0.f;
                stage_p(P);
                named_sync(BAR_EPI0 + cw, 128);
                vstage = stage;
                vphase = phase;
                mbar_wait(fk0 + stage * 8, phase);
                PP(named_sync(BAR_SCHED0 + cw, 256));
                issue_qk(dk0 + stage * (TILE_BYTES >> 4));
                if (++stage == AT_STAGES) { stage = 0; phase ^= 1; }
                mbar_wait(fk0 + stage * 8, phase);
                issue_qk2(O, dk0 + stage * (TILE_BYTES >> 4));
                PP(named_arrive(BAR_SCHED0 + (cw ^ 1), 256));
                if (++stage == AT_STAGES) { stage = 0; phase ^= 1; }
                wgmma_wait<1>();
                if (lane == 0) mbar_arrive(ek0 + vstage * 8);
                float n0, n1;
                {
                    float x0, x1;
                    scores_max(P2, x0, x1);
                    n0 = fmaf(-x0, c, FAST_BIAS);
                    n1 = fmaf(-x1, c, FAST_BIAS);
#pragma unroll
                    for (int i = 0; i < 16; i++) {
                        const float e0 = ex2(fmaf(bf16lo(P2[2 * i]), c, n0));
                        const float e1 = ex2(fmaf(bf16hi(P2[2 * i]), c, n0));
                        const float e2 = ex2(fmaf(bf16lo(P2[2 * i + 1]), c, n1));
                        const float e3 = ex2(fmaf(bf16hi(P2[2 * i + 1]), c, n1));
                        P[2 * i] = pack_bf16(e0, e1);
                        P[2 * i + 1] = pack_bf16(e2, e3);
                    }
                }
                auto prep = [&](float (&S)[64], float (&A)[64], int i_lo, int i_hi) {
#pragma unroll
                    for (int i = i_lo; i < i_hi; i++) {
                        const uint32_t sa = pack_bf16(S[4 * i], S[4 * i + 1]), sb = pack_bf16(S[4 * i + 2], S[4 * i + 3]);
                        A[4 * i] = fmaf(scale_lo(sa), c17, n0);
                        A[4 * i + 1] = fmaf(scale_hi(sa), c17, n0);
                        A[4 * i + 2] = fmaf(scale_lo(sb), c17, n1);
                        A[4 * i + 3] = fmaf(scale_hi(sb), c17, n1);
                    }
                };
                auto fin = [&](float (&S)[64], uint32_t (&Pn)[32], int i_lo, int i_hi) {
#pragma unroll
                    for (int i = i_lo; i < i_hi; i++) {
                        const float e0 = ex2(S[4 * i]);
                        const float e1 = ex2(S[4 * i + 1]);
                        const float e2 = ex2(S[4 * i + 2]);
                        const float e3 = ex2(S[4 * i + 3]);
                        Pn[2 * i] = pack_bf16(e0, e1);
                        Pn[2 * i + 1] = pack_bf16(e2, e3);
                    }
                };
                auto expo2 = [&](float (&S)[64], float (&A)[64], uint32_t (&Pn)[32], int i_lo, int i_hi) {
                    prep(S, A, i_lo ? XP_A : 0, i_hi < 16 ? XP_A : 16);
                    fin(A, Pn, i_lo ? XP_B : 0, i_hi < 16 ? XP_B : 16);
                };
                auto expo = [&](float (&A)[64], uint32_t (&Pn)[32], int i_lo, int i_hi) { expo2(S, A, Pn, i_lo, i_hi); };
                mbar_wait(fk0 + stage * 8, phase);
                PP(named_sync(BAR_SCHED0 + cw, 256));
                issue_qk(dk0 + stage * (TILE_BYTES >> 4));
                PP(named_arrive(BAR_SCHED0 + (cw ^ 1), 256));
                wgmma_wait<1>();
                if (lane == 0) mbar_arrive(ek0 + (vstage == AT_STAGES - 1 ? 0 : vstage + 1) * 8);
                {
                    float A[64];
                    expo2(O, A, P2, 0, 16);
                }
#pragma unroll
                for (int i = 0; i < 64; i++) O[i] = 0.f;
                L[0] = L[1] = L[2] = L[3] = 0.f;
                const int sa = vstage, sb = vstage == AT_STAGES - 1 ? 0 : vstage + 1;
                mbar_wait(fv0 + sa * 8, vphase);
                mbar_wait(fv0 + sb * 8, vphase ^ (sb == 0));
                PP(named_sync(BAR_SCHED0 + cw, 256));
                issue_pv(O, L, P, sa);
                issue_pv(O, L, P2, sb);
                PP(named_arrive(BAR_SCHED0 + (cw ^ 1), 256));
                vstage = stage;
                vphase = phase;
                if (++stage == AT_STAGES) { stage = 0; phase ^= 1; }
                wgmma_wait<1>();
                if (lane == 0) {
                    mbar_arrive(ek0 + vstage * 8);
                    mbar_arrive(ev0 + sa * 8);
                }
                okk = mbar_try_wait(fk0 + stage * 8, phase);
                okv = mbar_try_wait(fv0 + vstage * 8, vphase);
                float A[64];
                expo(A, P, 0, 8);
                if (!(okk && okv)) {
                    mbar_wait(fk0 + stage * 8, phase);
                    mbar_wait(fv0 + vstage * 8, vphase);
                }
                wgmma_wait<0>();
                if (lane == 0) mbar_arrive(ev0 + sb * 8);
                auto step = [&](uint32_t (&Pc)[32], uint32_t (&Pn)[32], bool last) {
                    const int ust = __shfl_sync(0xffffffffu, stage, 0), uvs = __shfl_sync(0xffffffffu, vstage, 0);
                    PP(named_sync(BAR_SCHED0 + cw, 256));
                    {
                        const uint32_t dk = dk0 + ust * (TILE_BYTES >> 4);
                        const uint32_t dv = dv0 + uvs * (TILE_BYTES >> 4), dw = dw0 + uvs * DW_ST;
                        wgmma_fence();
#pragma unroll
                        for (int s = 0; s < 16; s++) {
                            const int kk = s & 7;
                            if (s < 8) {
                                wgmma_ss_lo<0>(S, dq + (((kk >> 2) * 8192 + (kk & 3) * 32) >> 4),
                                               dk + (((kk >> 2) * 16384 + (kk & 3) * 32) >> 4), kk != 0);
                                if (s == 7) {
                                    wgmma_commit();
                                    wgmma_fence();
                                }
                            } else {
                                wgmma_rs_n64(O, Pc[4 * kk], Pc[4 * kk + 1], Pc[4 * kk + 2], Pc[4 * kk + 3], dv + ((kk * 2048) >> 4));
                                wgmma_rs_n72(O, L, Pc[4 * kk], Pc[4 * kk + 1], Pc[4 * kk + 2], Pc[4 * kk + 3], dw + kk * DW_K);
                            }
                            if (s >= IL_0 && (s - IL_0) % IL_K == 0) {
                                const int g = XP_B + (s - IL_0) / IL_K;
                                if (g < 16) {
#pragma unroll
                                    for (int i = 4 * g; i < 4 * g + 4; i++) A[i] = ex2(A[i]);
                                }
                                if (g > XP_B && g <= 16) {
                                    Pc[2 * g - 2] = pack_bf16(A[4 * g - 4], A[4 * g - 3]);
                                    Pc[2 * g - 1] = pack_bf16(A[4 * g - 2], A[4 * g - 1]);
                                }
                                if (g <= 16) {
                                    if (sched.zero) {
                                        float d;
                                        do { d = g_dummy; } while (d < 0.f);
                                        if (g < 16) {
#pragma unroll
                                            for (int i = 4 * g; i < 4 * g + 4; i++) A[i] += d;
                                        }
                                        if (g > XP_B) {
                                            Pc[2 * g - 2] ^= __float_as_uint(d);
                                            Pc[2 * g - 1] ^= __float_as_uint(d);
                                        }
                                    }
                                    if (s >= 7) wgmma_fence();
                                }
                            }
                        }
                        wgmma_commit();
                    }
                    PP(named_arrive(BAR_SCHED0 + (cw ^ 1), 256));
                    const int pv = vstage;
                    vstage = stage;
                    vphase = phase;
                    if (++stage == AT_STAGES) { stage = 0; phase ^= 1; }
                    okk = last || mbar_try_wait(fk0 + stage * 8, phase);
                    okv = mbar_try_wait(fv0 + vstage * 8, vphase);
                    wgmma_wait<1>();
                    if (lane == 0) mbar_arrive(ek0 + vstage * 8);
                    expo(A, Pn, 0, 8);
                    if (!(okk && okv)) {
                        if (!last) mbar_wait(fk0 + stage * 8, phase);
                        mbar_wait(fv0 + vstage * 8, vphase);
                    }
                    wgmma_wait<0>();
                    if (lane == 0) mbar_arrive(ev0 + pv * 8);
                };
#pragma unroll 1
                for (int j = 0; j < 6; j++) {
                    step(P, P2, false);
                    step(P2, P, false);
                }
                step(P, P2, true);
                fin(A, P2, XP_B, 16);
                issue_pv(O, L, P2, vstage);
                gemm_chunk(S, false, has_next);
                wgmma_wait<1>();
                if (lane == 0) mbar_arrive(ev0 + vstage * 8);
                gemm_chunk1(has_next);
                float z = fmaf(L[0], 0.f, L[2] * 0.f);
#pragma unroll
                for (int i = 0; i < 64; i++) z = fmaf(O[i], 0.f, z);
                if (__any_sync(0xffffffffu, z != 0.f) && lane == 0) atomicOr(&sm.redo, 1u << (16 * cw + it));
                wgmma_wait<1>();
                if (has_next) release(stage);
                epilogue(O, L);
            }
        }
        wgmma_wait<0>();
#pragma unroll 1
        for (; it < n_items; it++) {
            const int item = sched.item[blockIdx.x][it];
            const int type = item >> 12, a = (item >> 4) & 0xff, b = item & 15;
            const int nk = type == T_F2 ? FF / 64 : ((a >> 2) ? 2 * (HL - HA + 2) : 2 * (HA + 2));
            float acc[128];
            float (&T)[64] = *reinterpret_cast<float (*)[64]>(&acc[0]);
            float (&Y)[64] = *reinterpret_cast<float (*)[64]>(&acc[64]);
            int prev = -1;
#pragma unroll 1
            for (int kt = 0; kt < nk; kt++) {
                mbar_wait(fk0 + stage * 8, phase);
                mbar_wait(fv0 + stage * 8, phase);
                const uint64_t da = make_desc(smem_u32(sm.k[stage]) + cw * 64 * 128, 16, 1024);
                const uint64_t db = make_desc(smem_u32(sm.v[stage]), 8192, 1024);
                wgmma_fence();
#pragma unroll
                for (int kk = 0; kk < 4; kk++)
                    wgmma_ss_n256_tb(acc, da + (uint64_t)((kk * 32) >> 4), db + (uint64_t)((kk * 2048) >> 4), (kt | kk) != 0);
                wgmma_commit();
                wgmma_wait<1>();
                if (prev >= 0 && lane == 0) {
                    mbar_arrive(ek0 + prev * 8);
                    mbar_arrive(ev0 + prev * 8);
                }
                prev = stage;
                if (++stage == AT_STAGES) { stage = 0; phase ^= 1; }
            }
            uint4 xv[8], gw[8];
            bool gok = false;
            if (type == T_OPE) {
                load_x(xv, b, (a & 1) * 2 + (a >> 2));
                gok = mbar_try_wait(smem_u32(&sm.fin_bar[0]), 0);
                if (gok) load_g(gw, b, (a & 1) * 2 + (a >> 2));
            }
            wgmma_wait<0>();
            release(prev);
            if (type == T_F2) {
                uint4* gp = g_g + (b * 4 + a * 2) * (8 * 256) + (tid - 128);
#pragma unroll
                for (int j = 0; j < 16; j++) {
                    uint32_t y[4];
#pragma unroll
                    for (int i = 0; i < 4; i++) {
                        const uint32_t u = pack_bf16(acc[8 * j + 2 * i], acc[8 * j + 2 * i + 1]);
                        y[i] = pack_bf16(silu_f(bf16lo(u)), silu_f(bf16hi(u)));
                    }
                    __stcg(gp + j * 256, make_uint4(y[0], y[1], y[2], y[3]));
                }
                named_arrive(BAR_ST0 + cw, 160);
            } else {
                const int keep = (a & 1) * 2 + (a >> 2);
                {
                    const uint32_t xk = smem_u32(sm.k[0]) + TILE_BYTES / 2 + cw * 8192 + (tid & 127) * 16;
                    const uint32_t rk = peer_addr(xk), rb = peer_addr(smem_u32(&sm.xchg[cw * 4]));
                    mbar_wait_cluster(smem_u32(&sm.xrdy), 0);
#pragma unroll
                    for (int q = 0; q < 4; q++) {
                        uint32_t W[12];
#pragma unroll
                        for (int j = 0; j < 4; j++) {
                            const uint32_t w0 = __float_as_uint(Y[16 * q + 4 * j]), w1 = __float_as_uint(Y[16 * q + 4 * j + 1]);
                            const uint32_t w2 = __float_as_uint(Y[16 * q + 4 * j + 2]), w3 = __float_as_uint(Y[16 * q + 4 * j + 3]);
                            W[3 * j] = __byte_perm(w0, w1, 0x5321);
                            W[3 * j + 1] = __byte_perm(w1, w2, 0x6532);
                            W[3 * j + 2] = __byte_perm(w2, w3, 0x7653);
                        }
#pragma unroll
                        for (int j = 0; j < 3; j++) {
                            const int m = 3 * q + j;
                            asm volatile("st.async.weak.shared::cluster.mbarrier::complete_tx::bytes.v4.b32 [%0], {%1, %2, %3, %4}, [%5];" ::"r"(
                                             rk + (m >> 2) * TILE_BYTES + (m & 3) * 2048),
                                         "r"(W[4 * j]), "r"(W[4 * j + 1]), "r"(W[4 * j + 2]), "r"(W[4 * j + 3]), "r"(rb + (m >> 2) * 8)
                                         : "memory");
                        }
                    }
                    if (!gok) {
                        mbar_wait(smem_u32(&sm.fin_bar[0]), 0);
                        load_g(gw, b, keep);
                    }
                    mbar_wait(smem_u32(&sm.fin_bar[1]), 0);
                    const bool ok = !((*reinterpret_cast<volatile uint32_t*>(&sm.redo) >> it) & 1);
                    {
#pragma unroll
                        for (int q = 0; q < 4; q++) {
                            uint32_t W[12];
#pragma unroll
                            for (int j = 0; j < 3; j++) {
                                const int m = 3 * q + j;
                                if ((m & 3) == 0) mbar_wait_cluster(smem_u32(&sm.xchg[cw * 4 + (m >> 2)]), 0);
                                asm volatile("ld.shared.v4.u32 {%0, %1, %2, %3}, [%4];" : "=r"(W[4 * j]), "=r"(W[4 * j + 1]), "=r"(W[4 * j + 2]), "=r"(W[4 * j + 3])
                                             : "r"(xk + (m >> 2) * TILE_BYTES + (m & 3) * 2048));
                            }
#pragma unroll
                            for (int i = 0; i < 4; i++) {
                                T[16 * q + 4 * i] += __uint_as_float(W[3 * i] << 8);
                                T[16 * q + 4 * i + 1] += __uint_as_float(__byte_perm(W[3 * i], W[3 * i + 1], 0x5433) & 0xffffff00u);
                                T[16 * q + 4 * i + 2] += __uint_as_float(__byte_perm(W[3 * i + 1], W[3 * i + 2], 0x4322) & 0xffffff00u);
                                T[16 * q + 4 * i + 3] += __uint_as_float(W[3 * i + 2] & 0xffffff00u);
                            }
                        }
                        if (ok) final_epi(T, xv, gw, b, keep);
                    }
                }
            }
        }
        wgmma_wait<0>();
        __syncwarp();
        if (lane == 0) mbar_arrive(smem_u32(&sm.redo_bar));
        mbar_wait(smem_u32(&sm.redo_bar), 0);
        rmask = *reinterpret_cast<volatile uint32_t*>(&sm.redo);
        rmask = (rmask | (rmask >> 16)) & 0xffffu;
#pragma unroll 1
        for (; rmask && (sched.item[blockIdx.x][__ffs(rmask) - 1] >> 12) == T_ATT; rmask &= rmask - 1) {
            gemm_chunk(S, false, true);
            gemm_rest(S, DM / 128);
            pack_p(S);
            first_block();
            float O[64], L[4] = {0.f, 0.f, 0.f, 0.f};
#pragma unroll
            for (int i = 0; i < 64; i++) O[i] = 0.f;
            float m0 = -INFINITY, m1 = -INFINITY;
#pragma unroll 1
            for (int j = 0; j < 16; j++) {
                float x0, x1;
                scores_max(P2, x0, x1);
                x0 = fmaxf(x0, m0);
                x1 = fmaxf(x1, m1);
                const float a0 = ex2((m0 - x0) * c), a1 = ex2((m1 - x1) * c);
                m0 = x0;
                m1 = x1;
                const float n0 = -m0 * c, n1 = -m1 * c;
#pragma unroll
                for (int i = 0; i < 16; i++) {
                    const float e0 = ex2(fmaf(bf16lo(P2[2 * i]), c, n0));
                    const float e1 = ex2(fmaf(bf16hi(P2[2 * i]), c, n0));
                    const float e2 = ex2(fmaf(bf16lo(P2[2 * i + 1]), c, n1));
                    const float e3 = ex2(fmaf(bf16hi(P2[2 * i + 1]), c, n1));
                    P[2 * i] = pack_bf16(e0, e1);
                    P[2 * i + 1] = pack_bf16(e2, e3);
                    O[4 * i] *= a0;
                    O[4 * i + 1] *= a0;
                    O[4 * i + 2] *= a1;
                    O[4 * i + 3] *= a1;
                }
                L[0] *= a0;
                L[1] *= a0;
                L[2] *= a1;
                L[3] *= a1;
                mbar_wait(fv0 + vstage * 8, vphase);
                issue_pv(O, L, P, vstage);
                wgmma_wait<0>();
                if (lane == 0) mbar_arrive(ev0 + vstage * 8);
                if (j < 15) {
                    mbar_wait(fk0 + stage * 8, phase);
                    issue_qk(dk0 + stage * (TILE_BYTES >> 4));
                    wgmma_wait<0>();
                    if (lane == 0) mbar_arrive(ek0 + stage * 8);
                    vstage = stage;
                    vphase = phase;
                    if (++stage == AT_STAGES) { stage = 0; phase ^= 1; }
                }
            }
            epilogue(O, L);
        }
#pragma unroll 1
        for (; rmask; rmask &= rmask - 1) {
            const int item = sched.item[blockIdx.x][__ffs(rmask) - 1];
            gemm_chunk(S, false, true);
            gemm_rest(S, NH);
            const int keep = ((item >> 4) & 1) * 2 + ((item >> 6) & 1);
            uint4 xv[8], gw[8];
            load_x(xv, item & 15, keep);
            load_g(gw, item & 15, keep);
            final_epi(S, xv, gw, item & 15, keep);
        }
    }
}

typedef CUresult (*EncodeFn)(CUtensorMap*, CUtensorMapDataType, cuuint32_t, void*, const cuuint64_t*, const cuuint64_t*,
                             const cuuint32_t*, const cuuint32_t*, CUtensorMapInterleave, CUtensorMapSwizzle,
                             CUtensorMapL2promotion, CUtensorMapFloatOOBfill);

static CUtensorMap make_map(EncodeFn fn, const void* ptr, uint64_t rows, uint64_t cols, uint32_t box_rows, uint32_t box_blk) {
    CUtensorMap m;
    cuuint64_t dims[3] = {64, rows, cols / 64};
    cuuint64_t strides[2] = {cols * 2, 128};
    cuuint32_t box[3] = {64, box_rows, box_blk};
    cuuint32_t es[3] = {1, 1, 1};
    fn(&m, CU_TENSOR_MAP_DATA_TYPE_BFLOAT16, 3, const_cast<void*>(ptr), dims, strides, box, es, CU_TENSOR_MAP_INTERLEAVE_NONE,
       CU_TENSOR_MAP_SWIZZLE_128B, CU_TENSOR_MAP_L2_PROMOTION_L2_256B, CU_TENSOR_MAP_FLOAT_OOB_FILL_NONE);
    return m;
}

extern "C" void kernel_launch(void* const* d_in, const int* in_sizes, int n_in, void* d_out, int out_size) {
    const bf16* x = (const bf16*)d_in[0];
    const bf16* kc = (const bf16*)d_in[1];
    const bf16* vc = (const bf16*)d_in[2];
    const bf16* wq = (const bf16*)d_in[3];
    const bf16* wo = (const bf16*)d_in[4];
    const bf16* w1 = (const bf16*)d_in[6];
    const bf16* w2 = (const bf16*)d_in[7];
    bf16* out = (bf16*)d_out;

    static EncodeFn fn = nullptr;
    static void *p_xn = nullptr, *p_h = nullptr, *p_o = nullptr;
    static Sched sched;
    if (!fn) {
        void* f = nullptr;
        cudaDriverEntryPointQueryResult st;
        cudaGetDriverEntryPoint("cuTensorMapEncodeTiled", &f, cudaEnableDefault, &st);
        fn = (EncodeFn)f;
        cudaGetSymbolAddress(&p_xn, g_xn);
        cudaGetSymbolAddress(&p_h, g_h);
        cudaGetSymbolAddress(&p_o, g_o);
        cudaFuncSetAttribute(attn_kernel, cudaFuncAttributeMaxDynamicSharedMemorySize, (int)sizeof(AttnSmem) + 1024);
        static const struct { int n, n1; const char* tail; } cls[] = {
            CLS};
        int t1 = 0, t2 = 0, t3[2] = {0, 0}, l = 0;
        for (const auto& cl : cls) {
            for (int c = 0; c < cl.n; c++, l++) {
                const int i = l < 64 ? (l & 31) * 2 + (l >> 5) : l;
                int n = 0;
                for (int j = 0; j < cl.n1; j++, t1++) sched.item[i][n++] = (uint16_t)((T_F1 << 12) | ((t1 % 14) << 4) | (t1 / 14));
                for (int t = l; t < NH * 16; t += NUM_CTAS) sched.item[i][n++] = (uint16_t)((T_ATT << 12) | ((t >> 4) << 4) | (t & 15));
                sched.end_att[i] = (uint8_t)n;
                for (const char* p = cl.tail; *p; p++) {
                    if (*p == 'G') { sched.item[i][n++] = (uint16_t)((T_F2 << 12) | ((t2 & 1) << 4) | (t2 >> 1)); t2++; }
                    if (*p == 'D' || *p == 'E') {
                        const int g = *p - 'D', t = t3[g]++;
                        sched.item[i][n++] = (uint16_t)((T_OPE << 12) | (((t & 1) | (g << 2)) << 4) | (t >> 1));
                    }
                }
                sched.count[i] = (uint8_t)n;
            }
        }
    }
    Maps maps;
    maps.m[M_XN] = maps.m[M_XN2] = make_map(fn, p_xn, SEQ, DM, 128, 2);
    maps.m[M_WQ] = make_map(fn, wq, DM, NH * DH, 128, 2);
    maps.m[M_K] = make_map(fn, kc, NH * SEQ, DH, 128, 2);
    maps.m[M_V] = make_map(fn, vc, NH * SEQ, DH, 128, 2);
    maps.m[M_O] = make_map(fn, p_o, SEQ, NH * DH, 64, 2);
    maps.m[M_W1] = make_map(fn, w1, DM, FF, 128, 2);
    maps.m[M_HST] = make_map(fn, p_h, SEQ, FF, 64, 2);
    maps.m[M_HLD] = make_map(fn, p_h, SEQ, FF, 128, 1);
    maps.m[M_W2] = make_map(fn, w2, FF, DM, 64, 4);
    maps.m[M_OLD] = make_map(fn, p_o, SEQ, NH * DH, 128, 2);
    maps.m[M_WO] = make_map(fn, wo, NH * DH, DM, 128, 2);
    maps.m[M_OLDW] = make_map(fn, p_o, SEQ, NH * DH, 128, 1);
    maps.m[M_WOW] = make_map(fn, wo, NH * DH, DM, 64, 2);

    ln_kernel<<<SEQ / 8, 256>>>(x);
    cudaLaunchAttribute pdl[2];
    pdl[1].id = cudaLaunchAttributeClusterDimension;
    pdl[1].val.clusterDim.x = 2;
    pdl[1].val.clusterDim.y = 1;
    pdl[1].val.clusterDim.z = 1;
    pdl[0].id = cudaLaunchAttributeProgrammaticStreamSerialization;
    pdl[0].val.programmaticStreamSerializationAllowed = 1;
    cudaLaunchConfig_t cfg = {};
    cfg.gridDim = dim3(NUM_CTAS);
    cfg.blockDim = dim3(384);
    cfg.dynamicSmemBytes = sizeof(AttnSmem) + 1024;
    cfg.stream = cudaStreamPerThread;
    cfg.attrs = pdl;
    cfg.numAttrs = 2;
    cudaLaunchKernelEx(&cfg, attn_kernel, maps, x, out, sched);
}
```
